```python
import torch

def _softmax(x, axis=-1):
    return torch.softmax(x, dim=axis)
def _gelu(x):
    return torch.nn.functional.gelu(x, approximate="tanh")
def _silu(x):
    return torch.nn.functional.silu(x)
def _sigmoid(x):
    return torch.sigmoid(x)
def _layernorm(x, axis=-1, eps=1e-5):
    m = x.mean(dim=axis, keepdim=True)
    v = x.var(dim=axis, keepdim=True, unbiased=False)
    return (x - m) / torch.sqrt(v + eps)
def _scatter_add(tgt, idx, src, axis=0):
    return tgt.clone().index_add_(axis, idx, src)
def _segment_sum(src, seg, n):
    out = torch.zeros((n,) + src.shape[1:], dtype=src.dtype)
    return out.index_add_(0, seg, src)
def _pad(x, pw):
    flat = tuple(v for pair in reversed(pw) for v in pair)
    return torch.nn.functional.pad(x, flat)

kernel_name = 'sequential_preLN__sliding_block_cached__glu_gated_swiglu__decode'

def setup_inputs():

    _w = (lambda a: (lambda t: t.to(torch.bfloat16) if t.is_floating_point() else t)(torch.as_tensor(a)))
    def _A_setup():
        B, Sq, D = 1, 1, 640
        Hq, Hkv, Sk, Dh = 32, 32, 32768, 192
        assert Hq % Hkv == 0, (Hq, Hkv)
        return {
            "x": _w((lambda *s: torch.randn(*s, dtype=torch.bfloat16) * 0.05)(B, Sq, D)),
            "k_cache": _w((lambda *s: torch.randn(*s, dtype=torch.bfloat16) * 1.6)(B, Hkv, Sk, Dh)),
            "v_cache": _w((lambda *s: torch.randn(*s, dtype=torch.bfloat16) * 0.8)(B, Hkv, Sk, Dh)),
            "wq": _w((lambda *s: torch.randn(*s, dtype=torch.bfloat16) * 1.6)(D, Hq * Dh) * (D ** -0.5)),
            "wo": _w((lambda *s: torch.randn(*s, dtype=torch.bfloat16) * 0.8)(Hq * Dh, D) * ((Hq * Dh) ** -0.5)),
        }
    _A_in = _A_setup()

    def _B_setup():
        B, S, D, F = 1, 1, 640, 1536
        return {
            "x": _w((lambda *s: torch.randn(*s, dtype=torch.bfloat16) * 0.05)(B, S, D)),
            "w1": _w((lambda *s: torch.randn(*s, dtype=torch.bfloat16) * 0.4)(D, F) * (2.0 / D) ** 0.5),
            "w3": _w((lambda *s: torch.randn(*s, dtype=torch.bfloat16) * 0.4)(D, F) * (2.0 / D) ** 0.5),
            "w2": _w((lambda *s: torch.randn(*s, dtype=torch.bfloat16) * 0.4)(F, D) * (2.0 / F) ** 0.5),
        }
    _B_in = _B_setup()

    return {
        "A_x": _A_in["x"],
        "A_k_cache": _A_in["k_cache"],
        "A_v_cache": _A_in["v_cache"],
        "A_wq": _A_in["wq"],
        "A_wo": _A_in["wo"],
        "B_x": _B_in["x"],
        "B_w1": _B_in["w1"],
        "B_w3": _B_in["w3"],
        "B_w2": _B_in["w2"],
    }

def reference(A_x, A_k_cache, A_v_cache, A_wq, A_wo, B_x, B_w1, B_w3, B_w2):
    def _A_ref(x, k_cache, v_cache, wq, wo):
        B, Sq, D = x.shape
        Hq, Dh = 32, 192
        Hkv, Sk = k_cache.shape[1], k_cache.shape[2]
        W = min(4096, max(256, Sk // 4))
        rep = Hq // Hkv
        q = (lambda x, *d: x.permute(*d))((x @ wq).reshape(B, Sq, Hq, Dh), 0, 2, 1, 3)
        k = (lambda x, n, axis: torch.repeat_interleave(x, n, dim=axis))(k_cache[:, :, Sk - W:, :], rep, axis=1)
        v = (lambda x, n, axis: torch.repeat_interleave(x, n, dim=axis))(v_cache[:, :, Sk - W:, :], rep, axis=1)
        scores = torch.einsum("bhqd,bhkd->bhqk", q, k) * (Dh ** -0.5)
        p = _softmax(scores, axis=-1)
        o = torch.einsum("bhqk,bhkd->bhqd", p, v)
        return (lambda x, *d: x.permute(*d))(o, 0, 2, 1, 3).reshape(B, Sq, Hq * Dh) @ wo

    def _B_ref(x, w1, w3, w2):
        gate = torch.einsum("bsd,df->bsf", x, w1)
        up = torch.einsum("bsd,df->bsf", x, w3)
        h = _silu(gate) * up
        out = torch.einsum("bsf,fd->bsd", h, w2)
        return out

    x = A_x
    h = x + _A_ref(_layernorm(x, axis=-1), A_k_cache, A_v_cache, A_wq, A_wo)
    h2 = h + _B_ref(_layernorm(h, axis=-1), B_w1, B_w3, B_w2)
    return h2
```

```cpp
#include <cuda_runtime.h>
#include <cuda_bf16.h>
#include <cuda.h>
#include <stdint.h>

namespace {

constexpr int D_MODEL = 640;
constexpr int NHEAD = 32;
constexpr int DH = 192;
constexpr int SK = 32768;
constexpr int WIN = 4096;
constexpr int FF = 1536;

constexpr int NCTA = 128;
constexpr int NTHREADS = 256 + 64;
constexpr int TILE_BYTES = 32 * DH * 2;
constexpr int NSLOT = 16;
constexpr int NKT = 32;
constexpr int NQT = 5;
constexpr int QSLOT = NSLOT - NQT;
constexpr int NG = 6;
constexpr int NWP = 8, NF1 = 4, NF2 = 6;
constexpr int NTAIL = NWP + NF1 + NF2;
constexpr int NONE = 255;

#define CFG_INFLIGHT 7
#define CFG_NPROBE 6
#define CFG_PDELAY 90
constexpr int INFLIGHT = CFG_INFLIGHT;

constexpr int SM_W1 = NWP * 8192, SM_W3 = SM_W1 + 20480;
constexpr int SM_P = NSLOT * TILE_BYTES;
constexpr int SM_Q = SM_P + 2048;
constexpr int SM_RED = SM_Q + 384;
constexpr int SM_BC = SM_RED + 128 * 48;
constexpr int SM_ONE = SM_BC + 4096;
constexpr int SM_MAX = SM_ONE + 64;
constexpr int SM_SUM = SM_MAX + 32;
constexpr int SM_LN = SM_SUM + 32;
constexpr int SM_MISC = SM_LN + 64;
constexpr int SM_LATE = SM_MISC + 32;
constexpr int SM_BAR = SM_LATE + 32;
constexpr int SM_TOTAL = SM_BAR + 512;
static_assert(SM_TOTAL <= 232448, "shared memory");

struct __align__(128) Scratch {
    uint4 qbuf[NCTA * 96];
    uint4 mbuf[NCTA * 2];
    uint32_t ready[NCTA];
    uint32_t late[32];
    uint32_t epoch;
};
__device__ Scratch g_scratch;
constexpr int XA_ALIGN = 1 << 20;
constexpr uint32_t SENT = 0xffffffffu;
constexpr int B_O = 0;
constexpr int B_H = 32;
constexpr int B_A = 38;
__device__ unsigned char g_xarea[2 * XA_ALIGN];
__host__ __device__ constexpr uint32_t xa_par(uint32_t k) { return (k ^ (k >> 3) ^ (k >> 4) ^ (k >> 6)) & 1; }
__device__ __forceinline__ uint32_t xa_blk(uint32_t k, uint32_t side) { return (2 * k + ((side ^ __popc(k & 0x59)) & 1)) * 4096; }

constexpr uint32_t SPIN_LIMIT = 1u << 22;

__device__ __forceinline__ uint32_t smem_u32(const void* p) { return (uint32_t)__cvta_generic_to_shared(p); }
__device__ __forceinline__ uint32_t now_ns() { uint64_t t; asm volatile("mov.u64 %0, %globaltimer;" : "=l"(t)); return (uint32_t)t; }
__device__ __forceinline__ void mbar_init(uint32_t bar, uint32_t cnt) {
    asm volatile("mbarrier.init.shared::cta.b64 [%0], %1;" ::"r"(bar), "r"(cnt) : "memory");
}
__device__ __forceinline__ void mbar_expect_tx(uint32_t bar, uint32_t bytes) {
    asm volatile("mbarrier.arrive.expect_tx.shared::cta.b64 _, [%0], %1;" ::"r"(bar), "r"(bytes) : "memory");
}
__device__ __forceinline__ void mbar_arrive(uint32_t bar) {
    asm volatile("mbarrier.arrive.shared::cta.b64 _, [%0];" ::"r"(bar) : "memory");
}
__device__ __forceinline__ void mbar_arrive8(uint32_t bar) {
    asm volatile("mbarrier.arrive.shared::cta.b64 _, [%0], 8;" ::"r"(bar) : "memory");
}
__device__ __forceinline__ bool mbar_test(uint32_t bar, uint32_t parity) {
    uint32_t ok;
    asm volatile("{\n.reg .pred p;\nmbarrier.test_wait.parity.shared::cta.b64 p, [%1], %2;\nselp.u32 %0, 1, 0, p;\n}"
                 : "=r"(ok) : "r"(bar), "r"(parity) : "memory");
    return ok;
}
__device__ __forceinline__ void mbar_wait(uint32_t bar, uint32_t parity) {
    asm volatile("{\n.reg .pred p;\nW_%=:\nmbarrier.try_wait.parity.shared::cta.b64 p, [%0], %1;\n@!p bra.uni W_%=;\n}" ::"r"(bar), "r"(parity) : "memory");
}
__device__ __forceinline__ void tma_load(uint32_t dst, const CUtensorMap* tm, int c0, int c4, uint32_t bar, uint64_t pol) {
    asm volatile("cp.async.bulk.tensor.5d.shared::cluster.global.mbarrier::complete_tx::bytes.L2::cache_hint [%0], [%1, {%3, %5, %5, %5, %4}], [%2], %6;"
                 ::"r"(dst), "l"(reinterpret_cast<uint64_t>(tm)), "r"(bar), "r"(c0), "r"(c4), "r"(0), "l"(pol) : "memory");
}
__device__ __forceinline__ void pin(uint32_t& v) { asm volatile("shfl.sync.bfly.b32 %0, %0, 0, 31, -1;" : "+r"(v) :: "memory"); }
__device__ __forceinline__ void pin_u(uint32_t& v) { asm volatile("shfl.sync.idx.b32 %0, %0, 0, 31, -1;" : "+r"(v) :: "memory"); }
template <class T> __device__ __forceinline__ void pin(T*& v) {
    asm volatile("{\n.reg .b32 a, b;\nmov.b64 {a, b}, %0;\nshfl.sync.bfly.b32 a, a, 0, 31, -1;\nshfl.sync.bfly.b32 b, b, 0, 31, -1;\nmov.b64 %0, {a, b};\n}" : "+l"(v) :: "memory");
}
__device__ __forceinline__ void sts16(uint32_t a, uint32_t v) { asm volatile("st.shared.u16 [%0], %1;" ::"r"(a), "h"((unsigned short)v) : "memory"); }
__device__ __forceinline__ void sts32(uint32_t a, float v) { asm volatile("st.shared.f32 [%0], %1;" ::"r"(a), "f"(v) : "memory"); }
__device__ __forceinline__ void sts32(uint32_t a, uint32_t v) { asm volatile("st.shared.u32 [%0], %1;" ::"r"(a), "r"(v) : "memory"); }
__device__ __forceinline__ void sts64(uint32_t a, uint32_t x, uint32_t y) { asm volatile("st.shared.v2.u32 [%0], {%1, %2};" ::"r"(a), "r"(x), "r"(y) : "memory"); }
__device__ __forceinline__ void sts128(uint32_t a, const uint4& v) { asm volatile("st.shared.v4.u32 [%0], {%1, %2, %3, %4};" ::"r"(a), "r"(v.x), "r"(v.y), "r"(v.z), "r"(v.w) : "memory"); }
__device__ __forceinline__ void cons_sync() { asm volatile("bar.sync 1, 256;" ::: "memory"); }
template <int ID> __device__ __forceinline__ void fin_arrive() { asm volatile("bar.arrive %0, 288;" ::"n"(ID) : "memory"); }
template <int ID> __device__ __forceinline__ void fin_sync() { asm volatile("bar.sync %0, 288;" ::"n"(ID) : "memory"); }

__device__ __forceinline__ uint4 lds128(uint32_t a) {
    uint4 v;
    asm volatile("ld.shared.v4.u32 {%0,%1,%2,%3}, [%4];" : "=r"(v.x), "=r"(v.y), "=r"(v.z), "=r"(v.w) : "r"(a) : "memory");
    return v;
}
__device__ __forceinline__ float4 lds128f(uint32_t a) {
    float4 v;
    asm volatile("ld.shared.v4.f32 {%0,%1,%2,%3}, [%4];" : "=f"(v.x), "=f"(v.y), "=f"(v.z), "=f"(v.w) : "r"(a) : "memory");
    return v;
}
__device__ __forceinline__ uint2 lds64(uint32_t a) {
    uint2 v;
    asm volatile("ld.shared.v2.u32 {%0,%1}, [%2];" : "=r"(v.x), "=r"(v.y) : "r"(a) : "memory");
    return v;
}
__device__ __forceinline__ uint32_t lds32(uint32_t a) {
    uint32_t v;
    asm volatile("ld.shared.u32 %0, [%1];" : "=r"(v) : "r"(a) : "memory");
    return v;
}
__device__ __forceinline__ float sum8(uint32_t a) {
    const float4 x = lds128f(a), y = lds128f(a + 16);
    return ((x.x + x.y) + (x.z + x.w)) + ((y.x + y.y) + (y.z + y.w));
}
__device__ __forceinline__ void ldsm_x4(uint32_t* r, uint32_t a) {
    asm volatile("ldmatrix.sync.aligned.m8n8.x4.shared.b16 {%0,%1,%2,%3}, [%4];"
                 : "=r"(r[0]), "=r"(r[1]), "=r"(r[2]), "=r"(r[3]) : "r"(a) : "memory");
}
__device__ __forceinline__ void ldsm_x4_t(uint32_t* r, uint32_t a) {
    asm volatile("ldmatrix.sync.aligned.m8n8.x4.trans.shared.b16 {%0,%1,%2,%3}, [%4];"
                 : "=r"(r[0]), "=r"(r[1]), "=r"(r[2]), "=r"(r[3]) : "r"(a) : "memory");
}
__device__ __forceinline__ void ldsm5_if(uint32_t (&r)[5][4], uint32_t a, uint32_t bar, uint32_t& got) {
    asm volatile("{\n.reg .pred p, q;\nsetp.eq.u32 q, %20, 0;\nmbarrier.test_wait.parity.shared::cta.b64 p, [%22], 0;\nand.pred p, p, q;\n"
                 "@p ldmatrix.sync.aligned.m8n8.x4.trans.shared.b16 {%0,%1,%2,%3}, [%21];\n"
                 "@p ldmatrix.sync.aligned.m8n8.x4.trans.shared.b16 {%4,%5,%6,%7}, [%21+512];\n"
                 "@p ldmatrix.sync.aligned.m8n8.x4.trans.shared.b16 {%8,%9,%10,%11}, [%21+1024];\n"
                 "@p ldmatrix.sync.aligned.m8n8.x4.trans.shared.b16 {%12,%13,%14,%15}, [%21+1536];\n"
                 "@p ldmatrix.sync.aligned.m8n8.x4.trans.shared.b16 {%16,%17,%18,%19}, [%21+2048];\n"
                 "@p mov.u32 %20, 1;\n}"
                 : "+r"(r[0][0]), "+r"(r[0][1]), "+r"(r[0][2]), "+r"(r[0][3]), "+r"(r[1][0]), "+r"(r[1][1]), "+r"(r[1][2]), "+r"(r[1][3]),
                   "+r"(r[2][0]), "+r"(r[2][1]), "+r"(r[2][2]), "+r"(r[2][3]), "+r"(r[3][0]), "+r"(r[3][1]), "+r"(r[3][2]), "+r"(r[3][3]),
                   "+r"(r[4][0]), "+r"(r[4][1]), "+r"(r[4][2]), "+r"(r[4][3]), "+r"(got) : "r"(a), "r"(bar) : "memory");
}
__device__ __forceinline__ void mma_bf16(float* c, uint32_t a0, uint32_t a1, uint32_t a2, uint32_t a3, uint32_t b0, uint32_t b1) {
    asm volatile("mma.sync.aligned.m16n8k16.row.col.f32.bf16.bf16.f32 {%0,%1,%2,%3}, {%4,%5,%6,%7}, {%8,%9}, {%0,%1,%2,%3};"
                 : "+f"(c[0]), "+f"(c[1]), "+f"(c[2]), "+f"(c[3]) : "r"(a0), "r"(a1), "r"(a2), "r"(a3), "r"(b0), "r"(b1));
}
__device__ __forceinline__ void mma_bf16(float* c, const uint32_t* a, uint32_t b0, uint32_t b1) { mma_bf16(c, a[0], a[1], a[2], a[3], b0, b1); }
__device__ __forceinline__ void zero4(float* c) { c[0] = c[1] = c[2] = c[3] = 0.f; }
__device__ __forceinline__ float bf_lo(uint32_t u) { return __uint_as_float(u << 16); }
__device__ __forceinline__ float bf_hi(uint32_t u) { return __uint_as_float(u & 0xffff0000u); }
__device__ __forceinline__ uint32_t pack_bf(float hi, float lo) { uint32_t r; asm("cvt.rn.bf16x2.f32 %0, %1, %2;" : "=r"(r) : "f"(hi), "f"(lo)); return r; }
__device__ __forceinline__ uint32_t add_bf2(uint32_t a, uint32_t b) { uint32_t r; asm("add.rn.bf16x2 %0, %1, %2;" : "=r"(r) : "r"(a), "r"(b)); return r; }
__device__ __forceinline__ float bfr(float x) { return __uint_as_float(pack_bf(x, 0.f)); }

__device__ __forceinline__ uint32_t in_word(float v) { return __float_as_uint(v); }
__device__ __forceinline__ void st1(void* p, uint32_t v) {
    asm volatile("st.relaxed.gpu.global.u32 [%0], %1;" ::"l"(p), "r"(v) : "memory");
}
__device__ __forceinline__ void st2(void* p, uint32_t a, uint32_t b) {
    asm volatile("st.relaxed.gpu.global.v2.u32 [%0], {%1, %2};" ::"l"(p), "r"(a), "r"(b) : "memory");
}
__device__ __forceinline__ void st4(void* p, uint32_t a, uint32_t b, uint32_t c, uint32_t d) {
    asm volatile("st.relaxed.gpu.global.v4.u32 [%0], {%1, %2, %3, %4};" ::"l"(p), "r"(a), "r"(b), "r"(c), "r"(d) : "memory");
}
__device__ __forceinline__ uint32_t ld1(const void* p) {
    uint32_t v;
    asm volatile("ld.relaxed.gpu.global.u32 %0, [%1];" : "=r"(v) : "l"(p) : "memory");
    return v;
}
__device__ __forceinline__ uint4 ld4(const void* p) {
    uint4 v;
    asm volatile("ld.relaxed.gpu.global.v4.u32 {%0, %1, %2, %3}, [%4];" : "=r"(v.x), "=r"(v.y), "=r"(v.z), "=r"(v.w) : "l"(p) : "memory");
    return v;
}
__device__ __forceinline__ void ld4p(const void* p, uint4& v, bool on) {
    asm volatile("{\n.reg .pred q;\nsetp.ne.u32 q, %5, 0;\n@q ld.relaxed.gpu.global.v4.u32 {%0, %1, %2, %3}, [%4];\n}"
                 : "+r"(v.x), "+r"(v.y), "+r"(v.z), "+r"(v.w) : "l"(p), "r"((uint32_t)on) : "memory");
}
__device__ __forceinline__ bool ok8(const uint4& v) {
    const uint32_t m = __vimax3_u16x2(__vimax3_u16x2(v.x, v.y, v.z), v.w, v.w);
    return __vimax3_u16x2(m, m << 16, m >> 16) != SENT;
}
__device__ __forceinline__ void poll4(const void* p, uint4& v) {
    asm volatile("{\n.reg .pred q;\n.reg .u32 m;\nmax.u32 m, %0, %1;\nmax.u32 m, m, %2;\nmax.u32 m, m, %3;\nsetp.eq.u32 q, m, 0xffffffff;\n"
                 "@q ld.relaxed.gpu.global.v4.u32 {%0, %1, %2, %3}, [%4];\n}"
                 : "+r"(v.x), "+r"(v.y), "+r"(v.z), "+r"(v.w) : "l"(p) : "memory");
}
__device__ __forceinline__ uint32_t max4(const uint4& v) { return max(max(v.x, v.y), max(v.z, v.w)); }
__device__ __forceinline__ void pkt_st2(uint4* p, float a, float b, uint32_t tag) {
    asm volatile("st.relaxed.gpu.global.v2.b64 [%0], {%1, %2};" ::"l"(p), "l"(((uint64_t)tag << 32) | __float_as_uint(a)), "l"(((uint64_t)tag << 32) | __float_as_uint(b)) : "memory");
}
__device__ __forceinline__ void pkt_ld2(const uint4* p, uint64_t& a, uint64_t& b) {
    asm volatile("ld.relaxed.gpu.global.v2.b64 {%0, %1}, [%2];" : "=l"(a), "=l"(b) : "l"(p) : "memory");
}
__device__ __forceinline__ bool tag_ok(uint64_t v, uint32_t tag) { return (uint32_t)(v >> 32) == tag; }
__device__ __forceinline__ float val_of(uint64_t v) { return __uint_as_float((uint32_t)v); }

__device__ __forceinline__ float warp_sum(float v) {
#pragma unroll
    for (int o = 16; o > 0; o >>= 1) v += __shfl_xor_sync(0xffffffffu, v, o);
    return v;
}
__device__ __forceinline__ float warp_max(float v) {
#pragma unroll
    for (int o = 16; o > 0; o >>= 1) v = fmaxf(v, __shfl_xor_sync(0xffffffffu, v, o));
    return v;
}
__device__ __forceinline__ float sqrt_fast(float x) { float r; asm("sqrt.approx.ftz.f32 %0, %1;" : "=f"(r) : "f"(x)); return r; }
__device__ __forceinline__ float rcp_fast(float x) { float r; asm("rcp.approx.ftz.f32 %0, %1;" : "=f"(r) : "f"(x)); return r; }
__device__ __forceinline__ float ex2(float x) { float r; asm("ex2.approx.ftz.f32 %0, %1;" : "=f"(r) : "f"(x)); return r; }
constexpr float L2E = 1.4426950408889634f;
__device__ __forceinline__ void ln_finish(float s1, float s2, float& mean_b, float& inv_den) {
    const float mean = s1 * (1.0f / D_MODEL);
    const float var = fmaxf(fmaf(-mean, mean, s2 * (1.0f / D_MODEL)), 0.f);
    mean_b = bfr(mean);
    inv_den = rcp_fast(bfr(sqrt_fast(bfr(bfr(var) + 1e-5f))));
}
__device__ __forceinline__ uint32_t ln_apply2(uint32_t u, float mean_b, float inv_den) {
    const uint32_t d = pack_bf(bf_hi(u) - mean_b, bf_lo(u) - mean_b);
    return pack_bf(bf_hi(d) * inv_den, bf_lo(d) * inv_den);
}
__device__ __forceinline__ void ln_acc(uint32_t u, float& s1, float& s2) {
    const float a = bf_lo(u), b = bf_hi(u);
    s1 += a + b;
    s2 = fmaf(a, a, fmaf(b, b, s2));
}
__device__ __forceinline__ float silu_b(float g) { return bfr(__fdividef(g, 1.0f + ex2(-g * L2E))); }

#define STAMP(i) do { } while (0)

struct KParams {
    const __nv_bfloat16* x;
    const __nv_bfloat16* wq;
    __nv_bfloat16* out;
    Scratch* sc;
    unsigned char* xa;
    int t_k0, per, stag;
    uint32_t item[NTAIL];
    int t_q, t_ready, t_stat, ogate, hgate, dbg, t_probe, nprobe, target, maxneg;
    uint32_t role[NHEAD];
};
struct TMaps { CUtensorMap k, v, wo, w1, w3, w2; };

__global__ void __launch_bounds__(NTHREADS, 1)
fused_decode_kernel(const __grid_constant__ KParams p, const __grid_constant__ TMaps tm) {
    extern __shared__ __align__(1024) unsigned char smem[];
    uint32_t sbase = smem_u32(smem);
    const int tid = threadIdx.x;
    const int warp = __shfl_sync(0xffffffffu, tid >> 5, 0), lane = tid & 31;
    const int b = blockIdx.x;
    const int head = b >> 2, sp = b & 3;
    if (tid < 256) {
        const int r = tid >> 3, ch = tid & 7;
        const char* src = reinterpret_cast<const char*>(p.wq) + (size_t)(sp * 160 + r) * (NHEAD * DH * 2) + head * (DH * 2) + ch * 16;
#pragma unroll
        for (int i = 0; i < NQT; i++) {
#pragma unroll
            for (int j = 0; j < 3; j++)
                asm volatile("cp.async.cg.shared.global [%0], [%1], 16;"
                             ::"r"(sbase + (QSLOT + i) * TILE_BYTES + (3 * r + j) * 128 + ((ch ^ ((3 * r + j) & 7)) << 4)),
                               "l"(src + (size_t)i * 32 * (NHEAD * DH * 2) + j * 128) : "memory");
        }
    }
    const uint32_t t0 = now_ns();
    const uint32_t role = p.role[head];
    const int wt = (role & 255) * 4 + sp, u1 = (role >> 8 & 255) * 4 + sp, u2 = (role >> 16 & 255) * 4 + sp;
    const bool has_wo = wt < 4 * NONE, has_f1 = u1 < 4 * NONE, has_f2 = u2 < 4 * NONE;
    const int kg = wt / 20, ng = wt - kg * 20;
    const uint32_t sm_w2 = has_wo ? SM_W1 : 0;
    const uint32_t bar_full = sbase + SM_BAR;
    const uint32_t bar_empty = sbase + SM_BAR + 128;
    const uint32_t bar_tail = sbase + SM_BAR + 256;
    const uint32_t bar_scale = bar_tail + 8 * NTAIL;
    const uint32_t bar_stat = bar_scale + 8;

    if (warp == 8) {
        if (lane < 6) asm volatile("prefetch.tensormap [%0];" ::"l"(reinterpret_cast<uint64_t>(&tm.k + lane)) : "memory");
        mbar_init(bar_full + 8 * lane, lane < 16 ? 1 : 8);
        if (lane < NTAIL + 2) mbar_init(bar_tail + 8 * lane, lane == NTAIL + 1 ? 8 : 1);
        if (lane < 8) sts32(sbase + SM_LATE + lane * 4, 0u);
        asm volatile("fence.mbarrier_init.release.cluster;" ::: "memory");
        __syncwarp();
        asm volatile("bar.arrive 2, 320;" ::: "memory");
        if (lane == 0) {
            uint64_t pol;
            asm volatile("createpolicy.fractional.L2::evict_first.b64 %0, 1.0;" : "=l"(pol));
            uint32_t tb;
            asm volatile("mov.u32 %0, %laneid;" : "=r"(tb));
            tb += t0;
            if (b == 0) { st4(p.sc->late, 0, 0, 0, 0); st4(p.sc->late + 4, 0, 0, 0, 0); }
            const int tile0 = (head * SK + (SK - WIN)) / 32 + sp;
            uint32_t tn = tb + p.t_k0 + sp * p.stag, tw = tn, acc = 0;
            int slip = 0, w = 0;
#pragma unroll 1
            for (int n = 0; n < 2 * NKT; n++) {
                const int slot = n & (NSLOT - 1);
                const int use = (n >> 4) + (slot >= QSLOT);
                if (use >= 1) mbar_wait(bar_empty + 8 * slot, (use - 1) & 1);
                mbar_expect_tx(bar_full + 8 * slot, TILE_BYTES);
                uint32_t t;
                do {
                    t = now_ns();
                    if (mbar_test(bar_full + 8 * (w & (NSLOT - 1)), (w >> 4) & 1)) {
                        acc += t - tw;
                        tw += p.per;
                        if ((++w & 7) == 0) {
                            asm volatile("red.relaxed.gpu.global.add.u32 [%0], %1;" ::"l"(p.sc->late + (w >> 3)), "r"((1u << 24) + min(acc >> 3, 65535u)) : "memory");
                            acc = 0;
                        }
                    }
                } while ((int)(t - tn) < slip || w <= n - INFLIGHT);
                tma_load(sbase + slot * TILE_BYTES, &tm.k + (n >> 5), 0, tile0 + (n & (NKT - 1)) * 4, bar_full + 8 * slot, pol);
                tn += p.per;
                if ((n & 7) == 5 && p.target)
                    asm volatile("cp.async.cg.shared.global [%0], [%1], 16;\ncp.async.cg.shared.global [%0+16], [%1+16], 16;" ::"r"(sbase + SM_LATE), "l"(p.sc->late) : "memory");
                uint32_t rep = lds32(sbase + SM_LATE + (n >> 3) * 4);
                if (!(rep >> 30)) rep = lds32(sbase + SM_LATE + max((n >> 3) - 1, 0) * 4);
                if (rep >> 30) slip = max((int)((float)(rep & 0xffffffu) * rcp_fast((float)(rep >> 24))) - p.target, -p.maxneg);
            }
            tb += slip;
#pragma unroll 1
            for (int k = 0; k < NTAIL; k++) {
                const int j = p.item[k] & 255;
                const int seg = (j >= NWP) + (j >= NWP + NF1);
                if (!(seg == 0 ? has_wo : seg == 1 ? has_f1 : has_f2)) continue;
                const int i = j - (seg == 0 ? 0 : seg == 1 ? NWP : NWP + NF1);
                const int len = seg == 1 ? 10240 : 8192;
                const int off = (seg == 0 ? 0 : seg == 1 ? SM_W1 : sm_w2) + i * len;
                mbar_wait(bar_empty + 8 * (seg == 0 ? 5 : 9), 1);
                mbar_expect_tx(bar_tail + 8 * j, len);
                const CUtensorMap* m = &tm.wo + (seg == 0 ? 0 : seg == 1 ? 1 + (i >> 1) : 3);
                const int c0 = seg == 0 ? ng * 32 : seg == 1 ? u1 * 16 : u2 * 16;
                const int c4 = seg == 0 ? kg * 64 + i * 8 : seg == 1 ? (i & 1) * 20 : i * 8;
                tn = tb + (p.item[k] >> 8);
                while ((int)(now_ns() - tn) < 0) {}
                tma_load(sbase + off, m, c0, c4, bar_tail + 8 * j, pol);
            }
        }
    } else if (warp == 9) {
        const uint32_t tag = ld1(&p.sc->epoch) + 1;
        const int aoff = (u1 >> 1 & 7) * 384 + (u1 >> 4) * 64 + (u1 & 1) * 32;
        if (lane < 16) sts32(sbase + SM_ONE + lane * 4, 0x3f803f80u);
        unsigned char* slot[4];
#pragma unroll
        for (int i = 0; i < 3; i++) {
            const int e = lane + 32 * i, s = e >= 48;
            slot[i] = p.xa + xa_blk(B_O + head, s) + sp * (DH * 4) + (e - 48 * s) * 16;
        }
        slot[3] = p.xa + (lane < 16 ? xa_blk(B_H + kg, lane >> 3) + ng * 128 + (lane & 7) * 16 : xa_blk(B_A, lane >> 1 & 1) + aoff + (lane & 1) * 16);
        if (!(lane < 16 ? has_wo : lane < 20 && has_f1)) slot[3] = slot[0];
#pragma unroll
        for (int i = 0; i < 4; i++) st4(slot[i], SENT, SENT, SENT, SENT);
#pragma unroll
        for (int i = 0; i < 3; i++) st4(p.sc->qbuf + b * 96 + i * 32 + lane, 0, 0, 0, 0);
        if (lane < 2) st4(p.sc->mbuf + b * 2 + lane, 0, 0, 0, 0);
        if (lane == 0) sts32(sbase + SM_MISC, tag);
        asm volatile("bar.sync 2, 320;" ::: "memory");
        while ((int)(now_ns() - (t0 + p.t_ready)) < 0) __nanosleep(200);
        if (__any_sync(0xffffffffu, (ld1(slot[0]) & ld1(slot[1]) & ld1(slot[2]) & ld1(slot[3])) != SENT)) __trap();
        if (lane == 0) st1(p.sc->ready + b, tag);
        while (!mbar_test(bar_stat, 0)) __nanosleep(200);
        const float4 ma = lds128f(sbase + SM_MAX), mb = lds128f(sbase + SM_MAX + 16);
        const float m = fmaxf(fmaxf(fmaxf(ma.x, ma.y), fmaxf(ma.z, ma.w)), fmaxf(fmaxf(mb.x, mb.y), fmaxf(mb.z, mb.w)));
        if (lane < 2) pkt_st2(p.sc->mbuf + b * 2 + lane, m, sum8(sbase + SM_SUM), tag);
        int vote = 0;
#pragma unroll 1
        for (int r = 0; r < p.nprobe; r++) {
            __nanosleep(100);
            uint32_t d;
            asm volatile("{\n.reg .pred p, q;\n.reg .b32 a, b, c0, c1;\nmov.b32 c0, 0;\nmov.b32 c1, 0;\n"
                         "atom.relaxed.gpu.global.exch.b32 a, [%1], -1;\natom.relaxed.gpu.global.exch.b32 b, [%2], -1;\n"
                         "setp.eq.u32 p, a, -1;\n@p mov.u32 c0, %%clock;\nsetp.eq.u32 q, b, -1;\n@q mov.u32 c1, %%clock;\nsub.u32 %0, c1, c0;\n}"
                         : "=r"(d) : "l"(r & 1 ? slot[2] : slot[0]), "l"(r & 1 ? slot[0] : slot[2]) : "memory");
            vote += (d > 90) == (r & 1) ? 1 : -1;
        }
        const uint32_t side = __shfl_sync(0xffffffffu, vote, 0) > 0;
        uint32_t n = 0;
        {
            uint64_t em, el;
            while (true) {
                const uint4 e = ld4(p.sc->ready + lane * 4);
                pkt_ld2(p.sc->mbuf + (head * 4 + (lane & 3)) * 2, em, el);
                if (__all_sync(0xffffffffu, e.x == tag && e.y == tag && e.z == tag && e.w == tag && tag_ok(em, tag) && tag_ok(el, tag))) break;
                __nanosleep(500);
                if (++n > SPIN_LIMIT) __trap();
            }
            float M = fmaxf(val_of(em), __shfl_xor_sync(0xffffffffu, val_of(em), 1));
            M = fmaxf(M, __shfl_xor_sync(0xffffffffu, M, 2));
            float L = ex2((val_of(em) - M) * L2E) * val_of(el);
            L += __shfl_xor_sync(0xffffffffu, L, 1);
            L += __shfl_xor_sync(0xffffffffu, L, 2);
            if (lane == 0) {
                sts64(sbase + SM_MISC + 8, __float_as_uint(__fdividef(ex2((m - M) * L2E), L)), side);
                mbar_arrive(bar_scale);
                if (b == 0) p.sc->epoch = tag;
            }
        }
        unsigned char* hdst = p.xa + xa_blk(B_H + kg, side ^ 1) + ng * 128 + lane * 4;
        unsigned char* hdst2 = p.xa + xa_blk(B_H + kg, side) + ng * 128 + lane * 4;
        unsigned char* adst = p.xa + xa_blk(B_A, lane >> 4) + aoff + (lane & 15) * 2;
        __nv_bfloat16* odst = p.out + u2 * 16 + (lane & 15);
        uint32_t r0 = sbase + SM_RED + lane * 48, r1 = sbase + SM_RED + (lane & 15) * 48;
        uint32_t res = 0;
        if (has_f2) asm volatile("ld.global.nc.u16 %0, [%1];" : "=r"(res) : "l"(p.x + u2 * 16 + (lane & 15)));
        pin(hdst); pin(hdst2); pin(adst); pin(odst); pin(r0); pin(r1); pin(res);
        if (has_wo) {
            fin_sync<3>();
            const uint32_t v = in_word(sum8(r0));
            st1(hdst, v); st1(hdst2, v);
            STAMP(4);
        }
        if (has_f1) {
            fin_sync<4>();
            float mean_b, inv_den;
            ln_finish(sum8(sbase + SM_LN), sum8(sbase + SM_LN + 32), mean_b, inv_den);
            const uint32_t gs = pack_bf(fmaf(-mean_b, sum8(r1 + 48 * 48), sum8(r1 + 32 * 48)) * inv_den, 0.f);
            STAMP(7);
            asm volatile("{\n.reg .u32 i;\nand.b32 i, %0, 1;\nadd.u32 i, i, 5;\nbar.sync i, 288;\n}" ::"r"(gs) : "memory");
            const float up = bfr(fmaf(-mean_b, sum8(r1 + 80 * 48), sum8(r1 + 64 * 48)) * inv_den);
            asm volatile("st.relaxed.gpu.global.u16 [%0], %1;" ::"l"(adst), "h"((unsigned short)pack_bf(0.f, silu_b(__uint_as_float(gs)) * up)) : "memory");
            STAMP(8);
        }
        if (has_f2) {
            mbar_wait(bar_tail + 8 * (NWP + NF1 + p.hgate), 0);
            uint32_t e[3];
            do {
#pragma unroll
                for (int i = 0; i < 3; i++) e[i] = ld1(p.xa + xa_blk(B_H + 2 * i + (lane >> 4), side) + u2 * 64 + (lane & 15) * 4);
                if (++n > SPIN_LIMIT) __trap();
            } while (__any_sync(0xffffffffu, max(max(e[0], e[1]), e[2]) == SENT));
            float f[3];
#pragma unroll
            for (int i = 0; i < 3; i++) f[i] = __uint_as_float(e[i]) + __uint_as_float(__shfl_xor_sync(0xffffffffu, e[i], 16));
            res = add_bf2(res, pack_bf(0.f, (f[0] + f[1]) + f[2]));
            pin(res);
            fin_sync<6>();
            asm volatile("st.global.u16 [%0], %1;" ::"l"(odst), "h"((unsigned short)add_bf2(res, pack_bf(0.f, sum8(r1 + 96 * 48)))) : "memory");
            STAMP(11);
        }
    } else {
        const int g = lane >> 2, t = lane & 3;
        uint2 xres;
        {
            uint32_t xr;
            uint2 xu[5];
            const char* xb = reinterpret_cast<const char*>(p.x);
            asm volatile("ld.global.nc.u16 %0, [%1];" : "=r"(xr) : "l"(xb + (sp * 160 + min(tid, 159)) * 2));
#pragma unroll
            for (int i = 0; i < 5; i++) asm volatile("ld.global.nc.v2.u32 {%0, %1}, [%2];" : "=r"(xu[i].x), "=r"(xu[i].y) : "l"(xb + i * 256 + lane * 8));
            asm volatile("ld.global.nc.v2.u32 {%0, %1}, [%2];" : "=r"(xres.x), "=r"(xres.y) : "l"(xb + warp * 160 + min(lane, 19) * 8));
            if (lane >= 20) xres.x = xres.y = 0;
            float s1 = 0.f, s2 = 0.f, mean_b, inv_den;
#pragma unroll
            for (int i = 0; i < 5; i++) { ln_acc(xu[i].x, s1, s2); ln_acc(xu[i].y, s1, s2); }
            ln_finish(warp_sum(s1), warp_sum(s2), mean_b, inv_den);
            sts16(sbase + SM_P + warp * 64 + ((lane >> 1 & 3) * 8 + (lane >> 3) * 2 + (lane & 1)) * 2, ln_apply2(xr, mean_b, inv_den));
            asm volatile("cp.async.wait_all;" ::: "memory");
            asm volatile("bar.sync 2, 320;" ::: "memory");
        }
        STAMP(0);
        uint32_t va[3];
#pragma unroll
        for (int i = 0; i < 3; i++) {
            const int cc = 3 * warp + i, row = 3 * lane + (cc >> 3);
            va[i] = sbase + row * 128 + (((cc ^ row) & 7) << 4);
        }
        const int gi = g >= 3 ? g - 3 : g;
        unsigned char* odst = p.xa + xa_blk(B_O + head, g >= 3) + sp * (DH * 4) + (warp * 24 + gi * 8 + t * 2) * 4;
        pin(odst);

#pragma unroll 1
        for (int ph = 0; ph < 2; ph++) {
            if (ph == 1) {
                uint4 qf[6];
#pragma unroll
                for (int i = 0; i < 6; i++) qf[i] = lds128(sbase + SM_Q + t * 96 + i * 16);
                uint32_t ka[3];
#pragma unroll
                for (int j = 0; j < 3; j++) {
                    const int row = 3 * (lane & 15) + j;
                    ka[j] = sbase + row * 128 + ((((lane >> 4) ^ row) & 7) << 4) + warp * TILE_BYTES;
                }
                float s[4] = {0.f, 0.f, 0.f, 0.f};
#pragma unroll 1
                for (int it = 0; it < 4; it++) {
                    const int slot = (it & 1) * 8 + warp;
                    const uint32_t so = (it & 1) * 8 * TILE_BYTES;
                    float c[2][2][4];
                    zero4(c[0][0]); zero4(c[0][1]); zero4(c[1][0]); zero4(c[1][1]);
                    mbar_wait(bar_full + 8 * slot, it >> 1);
#pragma unroll
                    for (int ks = 0; ks < 12; ks++) {
                        const uint32_t a = (ka[ks >> 2] + so) ^ ((ks & 3) << 5);
                        uint32_t f0[4], f1[4];
                        ldsm_x4(f0, a); ldsm_x4(f1, a + 16 * DH * 2);
                        const uint32_t b0 = ks & 1 ? qf[ks >> 1].z : qf[ks >> 1].x, b1 = ks & 1 ? qf[ks >> 1].w : qf[ks >> 1].y;
                        mma_bf16(c[0][ks & 1], f0, b0, b1); mma_bf16(c[1][ks & 1], f1, b0, b1);
                    }
                    if (lane == 0) mbar_arrive8(bar_empty + 8 * slot);
                    const float v = t & 2 ? (t & 1 ? c[1][0][2] + c[1][1][2] : c[1][0][0] + c[1][1][0]) : (t & 1 ? c[0][0][2] + c[0][1][2] : c[0][0][0] + c[0][1][0]);
                    s[0] = s[1]; s[1] = s[2]; s[2] = s[3];
                    s[3] = bfr(bfr(v) * 0.07216878364870322f);
                }
                const float mw = warp_max(fmaxf(fmaxf(s[0], s[1]), fmaxf(s[2], s[3])));
                if (lane == 0) sts32(sbase + SM_MAX + warp * 4, mw);
                cons_sync();
                const float4 ma = lds128f(sbase + SM_MAX), mb = lds128f(sbase + SM_MAX + 16);
                const float m = fmaxf(fmaxf(fmaxf(ma.x, ma.y), fmaxf(ma.z, ma.w)), fmaxf(fmaxf(mb.x, mb.y), fmaxf(mb.z, mb.w)));
                float l = 0.f;
#pragma unroll
                for (int it = 0; it < 4; it++) {
                    const float e = ex2((s[it] - m) * L2E);
                    l += e;
                    sts16(sbase + SM_P + (it * 8 + warp) * 64 + ((g >> 1) * 8 + t * 2 + (g & 1)) * 2, pack_bf(0.f, e));
                }
                l = warp_sum(l);
                if (lane == 0) { sts32(sbase + SM_SUM + warp * 4, l); mbar_arrive(bar_stat); }
                cons_sync();
                STAMP(1);
            }
            float acc[2][3][4];
#pragma unroll
            for (int i = 0; i < 3; i++) { zero4(acc[0][i]); zero4(acc[1][i]); }
            const int nt = ph ? NKT : NQT;
            float scale = 1.f;
#pragma unroll 1
            for (int n = 0; n < nt; n++) {
                const int slot = ph ? (n & (NSLOT - 1)) : QSLOT + n;
                const uint4 w = lds128(sbase + SM_P + n * 64 + t * 16);
                if (n == NKT - 1) { mbar_wait(bar_scale, 0); scale = __uint_as_float(lds32(sbase + SM_MISC + 8)); }
                if (ph) mbar_wait(bar_full + 8 * slot, (n >> 4) & 1);
                uint32_t f[3][4];
#pragma unroll
                for (int i = 0; i < 3; i++) ldsm_x4_t(f[i], va[i] + slot * TILE_BYTES);
#pragma unroll
                for (int i = 0; i < 3; i++) {
                    mma_bf16(acc[0][i], w.x, w.x, w.y, w.y, f[i][0], f[i][1]);
                    mma_bf16(acc[1][i], w.z, w.z, w.w, w.w, f[i][2], f[i][3]);
                }
                if (lane == 0) mbar_arrive(bar_empty + 8 * slot);
            }
            const float v0 = (gi == 0 ? acc[0][0][0] + acc[1][0][0] : gi == 1 ? acc[0][1][0] + acc[1][1][0] : acc[0][2][0] + acc[1][2][0]) * scale;
            const float v1 = (gi == 0 ? acc[0][0][1] + acc[1][0][1] : gi == 1 ? acc[0][1][1] + acc[1][1][1] : acc[0][2][1] + acc[1][2][1]) * scale;
            if (ph == 1) {
                if (g < 6) st2(odst, in_word(v0), in_word(v1));
                break;
            }
            const uint32_t tag = lds32(sbase + SM_MISC);
            if (g < 3) pkt_st2(p.sc->qbuf + b * 96 + warp * 12 + lane, v0, v1, tag);
            if (warp < 3) {
                const uint4* src = p.sc->qbuf + head * 4 * 96 + tid;
                uint64_t e[4][2];
                uint32_t n = 0;
                bool ok;
#pragma unroll 1
                do {
                    __nanosleep(p.t_q);
                    ok = true;
#pragma unroll
                    for (int i = 0; i < 4; i++) { pkt_ld2(src + i * 96, e[i][0], e[i][1]); }
#pragma unroll
                    for (int i = 0; i < 4; i++) ok = ok && tag_ok(e[i][0], tag) && tag_ok(e[i][1], tag);
                    if (++n > SPIN_LIMIT) __trap();
                } while (!__all_sync(0xffffffffu, ok));
                sts32(sbase + SM_Q + (t * 24 + (tid >> 2)) * 4,
                      pack_bf((val_of(e[0][1]) + val_of(e[1][1])) + (val_of(e[2][1]) + val_of(e[3][1])), (val_of(e[0][0]) + val_of(e[1][0])) + (val_of(e[2][0]) + val_of(e[3][0]))));
            }
            cons_sync();
        }
        STAMP(2);
        const uint32_t side = lds32(sbase + SM_MISC + 12);
        const unsigned char* xs = p.xa + side * 4096;
        const int d16 = kg * 64 + g * 8 + warp, oh = d16 / 12;
        const unsigned char* osrc = p.xa + xa_blk(B_O + oh, side) + (d16 - oh * 12) * 64 + t * 16;
        const int r16 = (lane & 7) + ((lane >> 4) << 3), mi = lane >> 3 & 1;
        const uint32_t f32 = sbase + r16 * 32 + ((mi ^ (lane >> 2 & 1)) << 4);
        uint32_t rdst = sbase + SM_RED + (t * 8 + g) * 48 + warp * 4;
        uint32_t bl = sbase + SM_BC + warp * 512 + t * 80, bs = bl + g * 8;
        uint32_t hl = g < 4 ? bl : sbase + SM_ONE;
        uint32_t w1a = f32 + SM_W1 + warp * 2560, w2a = f32 + sm_w2 + warp * 1024;
        uint32_t gate = bar_tail + 8 * (NWP + (warp >> 2));
        uint32_t lnd = lane < 2 ? sbase + SM_LN + lane * 32 + warp * 4 : sbase + SM_BC + warp * 512 + 384 + lane * 4;
        const unsigned char* hs = xs + warp * 320 + lane * 16 + B_H * 8192;
        const unsigned char* hx = reinterpret_cast<const unsigned char*>(reinterpret_cast<uintptr_t>(hs) ^ 4096);
        const unsigned char* as = reinterpret_cast<const unsigned char*>(reinterpret_cast<uintptr_t>(xs) ^ (xa_par(B_A) * 4096)) + B_A * 8192 + warp * 384 + min(lane, 23) * 16;
        uint32_t al = sbase + SM_BC + warp * 512 + t * 16, at = sbase + SM_BC + warp * 512 + lane * 16;
        uint32_t fl = (has_f1 ? 1 : 0) | (has_f2 ? 2 : 0);
        pin_u(fl);
        const bool f1 = __builtin_expect(fl & 1, 1), f2 = fl & 2;
        uint32_t b2 = bar_tail + 8 * (NWP + NF1);
        pin_u(b2); pin(rdst); pin(bl); pin(bs); pin(hl); pin(w1a); pin(w2a); pin_u(gate); pin(lnd); pin(hs); pin(hx); pin(as); pin(al); pin(at);
#define F_(i, c) __uint_as_float(e[i].c)
        if (has_wo) {
            uint4 e[4];
#pragma unroll
            for (int i = 0; i < 4; i++) e[i].x = e[i].y = e[i].z = e[i].w = SENT;
            uint32_t n = 0;
            mbar_wait(bar_tail + 8 * p.ogate, 0);
#pragma unroll 1
            do {
                if (n) __nanosleep(100);
#pragma unroll
                for (int i = 0; i < 4; i++) poll4(osrc + i * (DH * 4), e[i]);
                if (++n > SPIN_LIMIT) __trap();
            } while (__any_sync(0xffffffffu, max(max(max4(e[0]), max4(e[1])), max(max4(e[2]), max4(e[3]))) == SENT));
            sts64(bs, pack_bf((F_(0, y) + F_(1, y)) + (F_(2, y) + F_(3, y)), (F_(0, x) + F_(1, x)) + (F_(2, x) + F_(3, x))),
                      pack_bf((F_(0, w) + F_(1, w)) + (F_(2, w) + F_(3, w)), (F_(0, z) + F_(1, z)) + (F_(2, z) + F_(3, z))));
            __syncwarp();
#pragma unroll
            for (int i = 0; i < 4; i++) e[i] = lds128(bl + i * 16);
            STAMP(3);
            const uint32_t wa = sbase + (warp * 16 + r16) * 64 + ((mi ^ (r16 >> 1 & 3)) << 4), wb = wa ^ 32;
            float c0[4], c1[4];
            zero4(c0); zero4(c1);
#pragma unroll
            for (int j = 0; j < NWP; j++) {
                mbar_wait(bar_tail + 8 * j, 0);
                uint32_t f0[4], f1[4];
                ldsm_x4_t(f0, wa + j * 8192); ldsm_x4_t(f1, wb + j * 8192);
                const uint32_t b0 = j & 1 ? e[j >> 1].z : e[j >> 1].x, b1 = j & 1 ? e[j >> 1].w : e[j >> 1].y;
                mma_bf16(c0, f0, b0, b1); mma_bf16(c1, f1, b0, b1);
            }
            sts32(rdst, t & 2 ? (t & 1 ? c1[2] : c1[0]) : (t & 1 ? c0[2] : c0[0]));
            fin_arrive<3>();
        }
        if (f1) {
            uint32_t a1[5][4], a3[5][4];
            uint4 e[NG];
#pragma unroll
            for (int i = 0; i < NG; i++) e[i].x = e[i].y = e[i].z = e[i].w = 0;
            uint32_t got3 = 0, n = 0;
#pragma unroll
            for (int i = 0; i < 5; i++) a3[i][0] = a3[i][1] = a3[i][2] = a3[i][3] = 0;
            mbar_wait(gate, 0);
#pragma unroll
            for (int i = 0; i < 5; i++) ldsm_x4_t(a1[i], w1a + i * 512);
#pragma unroll
            for (int i = 0; i < NG; i++) ld4p((xa_par(B_H + i) ? hx : hs) + i * 8192, e[i], lane < 20);
            ldsm5_if(a3, w1a + (SM_W3 - SM_W1), gate + 16, got3);
            uint4 hb0, hb1;
            uint2 hb2;
            float sv, sw1;
#pragma unroll 1
            while (true) {
#define S_(c) (((F_(0, c) + F_(1, c)) + (F_(2, c) + F_(3, c))) + (F_(4, c) + F_(5, c)))
                const float sx = S_(x), sy = S_(y), sz = S_(z), sw = S_(w), sa = (sx + sy) + (sz + sw);
#undef S_
                const uint32_t h0 = add_bf2(xres.x, pack_bf(sy, sx)), h1 = add_bf2(xres.y, pack_bf(sw, sz));
                sts64(bs, h0, h1);
                __syncwarp();
                hb0 = lds128(hl); hb1 = lds128(hl + 16); hb2 = lds64(hl + 32);
                const float a = bf_lo(h0), b = bf_hi(h0), c = bf_lo(h1), d = bf_hi(h1);
                const float s1 = (a + b) + (c + d), s2 = fmaf(a, a, b * b) + fmaf(c, c, d * d);
                sv = lane & 1 ? s2 : s1;
                sw1 = __shfl_xor_sync(0xffffffffu, lane & 1 ? s1 : s2, 1);
                bool miss = __any_sync(0xffffffffu, sa != sa);
                if (miss) {
                    miss = false;
#pragma unroll
                    for (int i = 0; i < NG; i++) {
                        const bool m = max4(e[i]) == SENT;
                        ld4p((xa_par(B_H + i) ? hx : hs) + i * 8192, e[i], m);
                        miss = miss || m;
                    }
                    ldsm5_if(a3, w1a + (SM_W3 - SM_W1), gate + 16, got3);
                    if (++n > SPIN_LIMIT) __trap();
                    miss = __any_sync(0xffffffffu, miss);
                }
                if (!miss) break;
            }
            STAMP(5);
            float c[3][4];
            zero4(c[0]); zero4(c[1]); zero4(c[2]);
            sv += sw1;
            const float x2 = __shfl_xor_sync(0xffffffffu, sv, 2);
            mma_bf16(c[0], a1[0], hb0.x, hb0.y); mma_bf16(c[1], a1[1], hb0.z, hb0.w); mma_bf16(c[2], a1[2], hb1.x, hb1.y);
            sv += x2;
            const float x4 = __shfl_xor_sync(0xffffffffu, sv, 4);
            mma_bf16(c[0], a1[3], hb1.z, hb1.w); mma_bf16(c[1], a1[4], hb2.x, hb2.y);
            sv += x4;
            sts32(lnd, (sv + __shfl_down_sync(0xffffffffu, sv, 8)) + __shfl_down_sync(0xffffffffu, sv, 16));
            sts32(rdst + 32 * 48, t & 1 ? (c[0][2] + c[2][2]) + c[1][2] : (c[0][0] + c[2][0]) + c[1][0]);
            fin_arrive<4>();
            STAMP(6);
            if (__any_sync(0xffffffffu, !got3)) {
                mbar_wait(gate + 16, 0);
#pragma unroll
                for (int i = 0; i < 5; i++) ldsm_x4_t(a3[i], w1a + (SM_W3 - SM_W1) + i * 512);
            }
            zero4(c[0]); zero4(c[1]); zero4(c[2]);
            mma_bf16(c[0], a3[0], hb0.x, hb0.y); mma_bf16(c[1], a3[1], hb0.z, hb0.w); mma_bf16(c[2], a3[2], hb1.x, hb1.y);
            mma_bf16(c[0], a3[3], hb1.z, hb1.w); mma_bf16(c[1], a3[4], hb2.x, hb2.y);
            sts32(rdst + 64 * 48, t & 1 ? (c[0][2] + c[2][2]) + c[1][2] : (c[0][0] + c[2][0]) + c[1][0]);
            fin_arrive<5>();
        }
        if (f2) {
            uint32_t a2[NF2][2][4];
#pragma unroll
            for (int j = 0; j < NF2 - 1; j++) {
                mbar_wait(b2 + 8 * j, 0);
                ldsm_x4_t(a2[j][0], w2a + j * 8192); ldsm_x4_t(a2[j][1], w2a + j * 8192 + 512);
            }
            STAMP(9);
            uint32_t n = 0;
#pragma unroll 1
            while (true) {
                const uint4 pa = ld4(as);
                if (++n > SPIN_LIMIT) __trap();
                sts128(at, pa);
                if (__all_sync(0xffffffffu, ok8(pa))) break;
            }
            STAMP(10);
            uint4 e[NF2];
#pragma unroll
            for (int j = 0; j < NF2; j++) e[j] = lds128(al + j * 64);
            mbar_wait(b2 + 8 * (NF2 - 1), 0);
            ldsm_x4_t(a2[NF2 - 1][0], w2a + (NF2 - 1) * 8192); ldsm_x4_t(a2[NF2 - 1][1], w2a + (NF2 - 1) * 8192 + 512);
            float c[4][4];
            zero4(c[0]); zero4(c[1]); zero4(c[2]); zero4(c[3]);
#pragma unroll
            for (int j = 0; j < NF2; j++) { mma_bf16(c[(j & 1) * 2], a2[j][0], e[j].x, e[j].y); mma_bf16(c[(j & 1) * 2 + 1], a2[j][1], e[j].z, e[j].w); }
            sts32(rdst + 96 * 48, t & 1 ? (c[0][2] + c[1][2]) + (c[2][2] + c[3][2]) : (c[0][0] + c[1][0]) + (c[2][0] + c[3][0]));
            fin_arrive<6>();
        }
#undef F_
    }
}

typedef CUresult (*EncodeTiledFn)(CUtensorMap*, CUtensorMapDataType, cuuint32_t, void*, const cuuint64_t*, const cuuint64_t*,
                                  const cuuint32_t*, const cuuint32_t*, CUtensorMapInterleave, CUtensorMapSwizzle,
                                  CUtensorMapL2promotion, CUtensorMapFloatOOBfill);

void make_map(EncodeTiledFn fn, CUtensorMap* tm, const void* w, const int (&d)[5], const int (&st)[4], const int (&bx)[5],
              CUtensorMapSwizzle sw, int promo) {
    cuuint64_t dims[5], strides[4];
    cuuint32_t box[5], estr[5];
    for (int i = 0; i < 5; i++) { dims[i] = (cuuint64_t)d[i]; box[i] = (cuuint32_t)bx[i]; estr[i] = 1; }
    for (int i = 0; i < 4; i++) strides[i] = (cuuint64_t)st[i];
    fn(tm, CU_TENSOR_MAP_DATA_TYPE_BFLOAT16, 5, const_cast<void*>(w), dims, strides, box, estr, CU_TENSOR_MAP_INTERLEAVE_NONE, sw,
       (CUtensorMapL2promotion)promo, CU_TENSOR_MAP_FLOAT_OOB_FILL_NONE);
}

enum { T_PER, T_LEAD, T_STAG, T_TD, T_PERO, T_F1D, T_PERF, T_F2, T_PER2, T_Q, T_READY, T_STAT, T_PWO, T_PW13, T_PW2, T_PRE, T_PERP, T_OG, T_HG, T_DBG, T_PROBE, T_NP, T_TG, T_MN, T_N };
#define TUNE_NAMES {"per", "lead", "stag", "td", "pero", "f1d", "perf", "f2", "per2", "q", "ready", "stat", "pwo", "pw13", "pw2", "pre", "perp", "og", "hg", "dbg", "probe", "np", "tg", "mn"}
int g_tune[T_N] = {480, 960, 120, 250, 299, 0, 299, 1000, 130, 1600, 8000, 2000, 1, 2, 2, 0, 299, 2, 1, 0, 7000, 9, 1720, 500};

}

extern "C" void kernel_launch(void* const* d_in, const int* in_sizes, int n_in, void* d_out, int out_size) {
    (void)in_sizes; (void)n_in; (void)out_size;
    static EncodeTiledFn encode = nullptr;
    static Scratch* scratch = nullptr;
    static unsigned char* xarea = nullptr;
    if (!encode) {
        void* sp = nullptr;
        cudaGetSymbolAddress(&sp, g_scratch);
        scratch = reinterpret_cast<Scratch*>(sp);
        cudaGetSymbolAddress(&sp, g_xarea);
        xarea = reinterpret_cast<unsigned char*>((reinterpret_cast<uintptr_t>(sp) + XA_ALIGN - 1) / XA_ALIGN * XA_ALIGN);
        void* fn = nullptr;
        cudaDriverEntryPointQueryResult st;
        cudaGetDriverEntryPoint("cuTensorMapEncodeTiled", &fn, cudaEnableDefault, &st);
        encode = reinterpret_cast<EncodeTiledFn>(fn);
        cudaFuncSetAttribute(fused_decode_kernel, cudaFuncAttributeMaxDynamicSharedMemorySize, SM_TOTAL);
    }
    const int* T = g_tune;
    KParams p;
    p.x = (const __nv_bfloat16*)d_in[0];
    p.wq = (const __nv_bfloat16*)d_in[3];
    p.out = (__nv_bfloat16*)d_out;
    p.sc = scratch;
    p.xa = xarea;
    p.per = T[T_PER];
    p.stag = T[T_STAG];
    p.t_k0 = (NQT + 1) * T[T_PER] - T[T_LEAD];
    {
        int t = p.t_k0 + 2 * NKT * T[T_PER] + T[T_STAG] * 3 / 2 + T[T_TD], n = 0;
        for (int i = 0; i < T[T_PRE]; i++, t += T[T_PERP]) p.item[n++] = t << 8 | (NWP + i);
        for (int i = 0; i < NWP; i++, t += T[T_PERO]) p.item[n++] = t << 8 | i;
        for (int i = T[T_PRE], t1 = t + T[T_F1D]; i < NF1; i++, t1 += T[T_PERF]) p.item[n++] = t1 << 8 | (NWP + i);
        for (int i = 0, t2 = t + T[T_F2]; i < NF2; i++, t2 += T[T_PER2]) p.item[n++] = t2 << 8 | (NWP + NF1 + i);
        for (int i = 0; i < NTAIL; i++) for (int j = i + 1; j < NTAIL; j++) if (p.item[j] < p.item[i]) { const uint32_t x = p.item[i]; p.item[i] = p.item[j]; p.item[j] = x; }
    }
    p.ogate = T[T_OG]; p.hgate = T[T_HG]; p.dbg = T[T_DBG]; p.t_probe = T[T_PROBE]; p.nprobe = T[T_NP]; p.target = T[T_TG]; p.maxneg = T[T_MN];
    p.t_q = T[T_Q]; p.t_ready = T[T_READY]; p.t_stat = T[T_STAT];
    for (int i = 0, nw = 0, n1 = 0, n2 = 0; i < NHEAD; i++) {
        const bool f2 = i % 3 == 2, both = i == 8 || i == 23;
        p.role[i] = (both ? NONE : nw++) | ((!f2 || both) ? n1++ : NONE) << 8 | (f2 ? n2++ : NONE) << 16;
    }
    TMaps tm;
    constexpr int R1 = FF * 2, R2 = D_MODEL * 2;
    for (int i = 0; i < 2; i++)
        make_map(encode, &tm.k + i, d_in[1 + i], {64, 96, 1, 1, NHEAD * SK / 32}, {128, TILE_BYTES, TILE_BYTES, TILE_BYTES}, {64, 96, 1, 1, 1}, CU_TENSOR_MAP_SWIZZLE_128B, 2);
    make_map(encode, &tm.wo, d_in[4], {D_MODEL, 2, 4, 2, NHEAD * DH / 16}, {R2, 4 * R2, 2 * R2, 16 * R2}, {32, 2, 4, 2, 8}, CU_TENSOR_MAP_SWIZZLE_64B, T[T_PWO]);
    make_map(encode, &tm.w1, d_in[6], {FF, 2, 4, 2, D_MODEL / 16}, {R1, 4 * R1, 2 * R1, 16 * R1}, {16, 2, 4, 2, 20}, CU_TENSOR_MAP_SWIZZLE_32B, T[T_PW13]);
    make_map(encode, &tm.w3, d_in[7], {FF, 2, 4, 2, D_MODEL / 16}, {R1, 4 * R1, 2 * R1, 16 * R1}, {16, 2, 4, 2, 20}, CU_TENSOR_MAP_SWIZZLE_32B, T[T_PW13]);
    make_map(encode, &tm.w2, d_in[8], {D_MODEL, 2, 4, 4, FF / 32}, {R2, 8 * R2, 2 * R2, 32 * R2}, {16, 2, 4, 4, 8}, CU_TENSOR_MAP_SWIZZLE_32B, T[T_PW2]);
    fused_decode_kernel<<<NCTA, NTHREADS, SM_TOTAL, cudaStreamPerThread>>>(p, tm);
}
```

```cpp
#include <cuda_runtime.h>
#include <cuda_bf16.h>
#include <cuda.h>
#include <stdint.h>

namespace {

constexpr int D_MODEL = 640;
constexpr int NHEAD = 32;
constexpr int DH = 192;
constexpr int SK = 32768;
constexpr int WIN = 4096;
constexpr int FF = 1536;

constexpr int NCTA = 128;
constexpr int NTHREADS = 256 + 64;
constexpr int TILE_BYTES = 32 * DH * 2;
constexpr int NSLOT = 16;
constexpr int NKT = 32;
constexpr int NQT = 5;
constexpr int QSLOT = NSLOT - NQT;
constexpr int NG = 6;
constexpr int NWP = 8, NF1 = 4, NF2 = 6;
constexpr int NTAIL = NWP + NF1 + NF2;

constexpr int INFLIGHT = 7;

constexpr uint32_t sbase = 1024;
constexpr int SM_W1 = NWP * 8192, SM_W3 = SM_W1 + 20480, SM_W2 = SM_W3 + 20480;
constexpr int SM_P = NSLOT * TILE_BYTES;
constexpr int SM_Q = SM_P + 2048;
constexpr int SM_RED = SM_Q + 384;
constexpr int SM_BC = SM_RED + 128 * 48;
constexpr int SM_ONE = SM_BC + 4096;
constexpr int SM_MAX = SM_ONE + 64;
constexpr int SM_SUM = SM_MAX + 32;
constexpr int SM_LN = SM_SUM + 32;
constexpr int SM_MISC = SM_LN + 64;
constexpr int SM_LATE = SM_MISC + 32;
constexpr int SM_BAR = SM_LATE + 32;
constexpr int SM_TOTAL = SM_BAR + 512;
static_assert(SM_TOTAL <= 232448, "shared memory");

struct __align__(128) Scratch {
    uint4 qbuf[NCTA * 96];
    uint4 mbuf[NCTA * 2];
    uint32_t ready[NCTA];
    uint32_t late[32];
    uint32_t epoch;
};
__device__ Scratch g_scratch;
constexpr int XA_ALIGN = 1 << 20;
constexpr uint32_t SENT = 0xffffffffu;
__device__ unsigned char g_xarea[2 * XA_ALIGN];
__host__ __device__ constexpr uint32_t xa_o(uint32_t h) { return (2 * h + ((h ^ (h >> 3) ^ (h >> 4)) & 1)) * 4096; }
__host__ __device__ constexpr uint32_t xa_h(uint32_t i) { return (1 << 18) + (i >> 2) * (3 << 16) + (i & 3) * (1 << 14); }
constexpr uint32_t XA_A = xa_h(NG);

constexpr uint32_t SPIN_LIMIT = 1u << 22;

__device__ __forceinline__ uint32_t smem_u32(const void* p) { return (uint32_t)__cvta_generic_to_shared(p); }
__device__ __forceinline__ uint32_t now_ns() { uint64_t t; asm volatile("mov.u64 %0, %globaltimer;" : "=l"(t)); return (uint32_t)t; }
__device__ __forceinline__ void mbar_init(uint32_t bar, uint32_t cnt) {
    asm volatile("mbarrier.init.shared::cta.b64 [%0], %1;" ::"r"(bar), "r"(cnt) : "memory");
}
__device__ __forceinline__ void mbar_expect_tx(uint32_t bar, uint32_t bytes) {
    asm volatile("mbarrier.arrive.expect_tx.shared::cta.b64 _, [%0], %1;" ::"r"(bar), "r"(bytes) : "memory");
}
__device__ __forceinline__ void mbar_arrive(uint32_t bar) {
    asm volatile("mbarrier.arrive.shared::cta.b64 _, [%0];" ::"r"(bar) : "memory");
}
__device__ __forceinline__ void mbar_arrive8(uint32_t bar) {
    asm volatile("mbarrier.arrive.shared::cta.b64 _, [%0], 8;" ::"r"(bar) : "memory");
}
__device__ __forceinline__ bool mbar_test(uint32_t bar, uint32_t parity) {
    uint32_t ok;
    asm volatile("{\n.reg .pred p;\nmbarrier.test_wait.parity.shared::cta.b64 p, [%1], %2;\nselp.u32 %0, 1, 0, p;\n}"
                 : "=r"(ok) : "r"(bar), "r"(parity) : "memory");
    return ok;
}
__device__ __forceinline__ void mbar_wait(uint32_t bar, uint32_t parity) {
    asm volatile("{\n.reg .pred p;\nW_%=:\nmbarrier.try_wait.parity.shared::cta.b64 p, [%0], %1;\n@!p bra.uni W_%=;\n}" ::"r"(bar), "r"(parity) : "memory");
}
__device__ __forceinline__ void mbar_wait_after(uint32_t bar, uint32_t dump, float v) {
    uint32_t ok;
    asm volatile("{\n.reg .pred p;\nmbarrier.try_wait.parity.shared::cta.b64 p, [%1], 0;\nselp.u32 %0, 1, 0, p;\n}" : "=r"(ok) : "r"(bar) : "memory");
    asm volatile("st.volatile.shared.f32 [%0], %1;" ::"r"(dump), "f"(v) : "memory");
    if (__builtin_expect(!ok, 0)) mbar_wait(bar, 0);
}
__device__ __forceinline__ void tma_load(uint32_t dst, const CUtensorMap* tm, int c0, int c4, uint32_t bar, uint64_t pol) {
    asm volatile("cp.async.bulk.tensor.5d.shared::cluster.global.mbarrier::complete_tx::bytes.L2::cache_hint [%0], [%1, {%3, %5, %5, %5, %4}], [%2], %6;"
                 ::"r"(dst), "l"(reinterpret_cast<uint64_t>(tm)), "r"(bar), "r"(c0), "r"(c4), "r"(0), "l"(pol) : "memory");
}
__device__ __forceinline__ void pin(uint32_t& v) { asm volatile("shfl.sync.bfly.b32 %0, %0, 0, 31, -1;" : "+r"(v) :: "memory"); }
__device__ __forceinline__ void pin_u(uint32_t& v) { asm volatile("shfl.sync.idx.b32 %0, %0, 0, 31, -1;" : "+r"(v) :: "memory"); }
template <class T> __device__ __forceinline__ void pin(T*& v) {
    asm volatile("{\n.reg .b32 a, b;\nmov.b64 {a, b}, %0;\nshfl.sync.bfly.b32 a, a, 0, 31, -1;\nshfl.sync.bfly.b32 b, b, 0, 31, -1;\nmov.b64 %0, {a, b};\n}" : "+l"(v) :: "memory");
}
__device__ __forceinline__ void sts16(uint32_t a, uint32_t v) { asm volatile("st.shared.u16 [%0], %1;" ::"r"(a), "h"((unsigned short)v) : "memory"); }
__device__ __forceinline__ void sts32(uint32_t a, float v) { asm volatile("st.shared.f32 [%0], %1;" ::"r"(a), "f"(v) : "memory"); }
__device__ __forceinline__ void sts32(uint32_t a, uint32_t v) { asm volatile("st.shared.u32 [%0], %1;" ::"r"(a), "r"(v) : "memory"); }
__device__ __forceinline__ void sts64(uint32_t a, uint32_t x, uint32_t y) { asm volatile("st.shared.v2.u32 [%0], {%1, %2};" ::"r"(a), "r"(x), "r"(y) : "memory"); }
__device__ __forceinline__ void sts128(uint32_t a, const uint4& v) { asm volatile("st.shared.v4.u32 [%0], {%1, %2, %3, %4};" ::"r"(a), "r"(v.x), "r"(v.y), "r"(v.z), "r"(v.w) : "memory"); }
__device__ __forceinline__ void cons_sync() { asm volatile("bar.sync 1, 256;" ::: "memory"); }
template <int ID> __device__ __forceinline__ void fin_arrive() { asm volatile("bar.arrive %0, 288;" ::"n"(ID) : "memory"); }
template <int ID> __device__ __forceinline__ void fin_sync() { asm volatile("bar.sync %0, 288;" ::"n"(ID) : "memory"); }

__device__ __forceinline__ uint4 lds128(uint32_t a) {
    uint4 v;
    asm volatile("ld.shared.v4.u32 {%0,%1,%2,%3}, [%4];" : "=r"(v.x), "=r"(v.y), "=r"(v.z), "=r"(v.w) : "r"(a) : "memory");
    return v;
}
__device__ __forceinline__ uint4 lds128v(uint32_t a) {
    uint4 v;
    asm volatile("ld.volatile.shared.v4.u32 {%0,%1,%2,%3}, [%4];" : "=r"(v.x), "=r"(v.y), "=r"(v.z), "=r"(v.w) : "r"(a) : "memory");
    return v;
}
__device__ __forceinline__ float4 lds128f(uint32_t a) {
    float4 v;
    asm volatile("ld.shared.v4.f32 {%0,%1,%2,%3}, [%4];" : "=f"(v.x), "=f"(v.y), "=f"(v.z), "=f"(v.w) : "r"(a) : "memory");
    return v;
}
__device__ __forceinline__ uint2 lds64(uint32_t a) {
    uint2 v;
    asm volatile("ld.shared.v2.u32 {%0,%1}, [%2];" : "=r"(v.x), "=r"(v.y) : "r"(a) : "memory");
    return v;
}
__device__ __forceinline__ uint32_t lds32(uint32_t a) {
    uint32_t v;
    asm volatile("ld.shared.u32 %0, [%1];" : "=r"(v) : "r"(a) : "memory");
    return v;
}
__device__ __forceinline__ float sum8(uint32_t a) {
    const float4 x = lds128f(a), y = lds128f(a + 16);
    return ((x.x + x.y) + (x.z + x.w)) + ((y.x + y.y) + (y.z + y.w));
}
__device__ __forceinline__ void ldsm_x4(uint32_t* r, uint32_t a) {
    asm volatile("ldmatrix.sync.aligned.m8n8.x4.shared.b16 {%0,%1,%2,%3}, [%4];"
                 : "=r"(r[0]), "=r"(r[1]), "=r"(r[2]), "=r"(r[3]) : "r"(a) : "memory");
}
__device__ __forceinline__ void ldsm_x4_t(uint32_t* r, uint32_t a) {
    asm volatile("ldmatrix.sync.aligned.m8n8.x4.trans.shared.b16 {%0,%1,%2,%3}, [%4];"
                 : "=r"(r[0]), "=r"(r[1]), "=r"(r[2]), "=r"(r[3]) : "r"(a) : "memory");
}
__device__ __forceinline__ void ldsm5_if(uint32_t (&r)[5][4], uint32_t a, uint32_t bar, uint32_t& got) {
    asm volatile("{\n.reg .pred p, q;\nsetp.eq.u32 q, %20, 0;\nmbarrier.test_wait.parity.shared::cta.b64 p, [%22], 0;\nand.pred p, p, q;\n"
                 "@p ldmatrix.sync.aligned.m8n8.x4.trans.shared.b16 {%0,%1,%2,%3}, [%21];\n"
                 "@p ldmatrix.sync.aligned.m8n8.x4.trans.shared.b16 {%4,%5,%6,%7}, [%21+512];\n"
                 "@p ldmatrix.sync.aligned.m8n8.x4.trans.shared.b16 {%8,%9,%10,%11}, [%21+1024];\n"
                 "@p ldmatrix.sync.aligned.m8n8.x4.trans.shared.b16 {%12,%13,%14,%15}, [%21+1536];\n"
                 "@p ldmatrix.sync.aligned.m8n8.x4.trans.shared.b16 {%16,%17,%18,%19}, [%21+2048];\n"
                 "@p mov.u32 %20, 1;\n}"
                 : "+r"(r[0][0]), "+r"(r[0][1]), "+r"(r[0][2]), "+r"(r[0][3]), "+r"(r[1][0]), "+r"(r[1][1]), "+r"(r[1][2]), "+r"(r[1][3]),
                   "+r"(r[2][0]), "+r"(r[2][1]), "+r"(r[2][2]), "+r"(r[2][3]), "+r"(r[3][0]), "+r"(r[3][1]), "+r"(r[3][2]), "+r"(r[3][3]),
                   "+r"(r[4][0]), "+r"(r[4][1]), "+r"(r[4][2]), "+r"(r[4][3]), "+r"(got) : "r"(a), "r"(bar) : "memory");
}
__device__ __forceinline__ void mma_bf16(float* c, uint32_t a0, uint32_t a1, uint32_t a2, uint32_t a3, uint32_t b0, uint32_t b1) {
    asm volatile("mma.sync.aligned.m16n8k16.row.col.f32.bf16.bf16.f32 {%0,%1,%2,%3}, {%4,%5,%6,%7}, {%8,%9}, {%0,%1,%2,%3};"
                 : "+f"(c[0]), "+f"(c[1]), "+f"(c[2]), "+f"(c[3]) : "r"(a0), "r"(a1), "r"(a2), "r"(a3), "r"(b0), "r"(b1));
}
__device__ __forceinline__ void mma_bf16(float* c, const uint32_t* a, uint32_t b0, uint32_t b1) { mma_bf16(c, a[0], a[1], a[2], a[3], b0, b1); }
__device__ __forceinline__ void zero4(float* c) { c[0] = c[1] = c[2] = c[3] = 0.f; }
__device__ __forceinline__ float bf_lo(uint32_t u) { return __uint_as_float(u << 16); }
__device__ __forceinline__ float bf_hi(uint32_t u) { return __uint_as_float(u & 0xffff0000u); }
__device__ __forceinline__ uint32_t pack_bf(float hi, float lo) { uint32_t r; asm("cvt.rn.bf16x2.f32 %0, %1, %2;" : "=r"(r) : "f"(hi), "f"(lo)); return r; }
__device__ __forceinline__ uint32_t add_bf2(uint32_t a, uint32_t b) { uint32_t r; asm("add.rn.bf16x2 %0, %1, %2;" : "=r"(r) : "r"(a), "r"(b)); return r; }
__device__ __forceinline__ float bfr(float x) { return __uint_as_float(pack_bf(x, 0.f)); }

__device__ __forceinline__ uint32_t in_word(float v) { return __float_as_uint(v); }
__device__ __forceinline__ void st1(void* p, uint32_t v) {
    asm volatile("st.relaxed.gpu.global.u32 [%0], %1;" ::"l"(p), "r"(v) : "memory");
}
__device__ __forceinline__ void st2(void* p, uint32_t a, uint32_t b) {
    asm volatile("st.relaxed.gpu.global.v2.u32 [%0], {%1, %2};" ::"l"(p), "r"(a), "r"(b) : "memory");
}
__device__ __forceinline__ void st4(void* p, uint32_t a, uint32_t b, uint32_t c, uint32_t d) {
    asm volatile("st.relaxed.gpu.global.v4.u32 [%0], {%1, %2, %3, %4};" ::"l"(p), "r"(a), "r"(b), "r"(c), "r"(d) : "memory");
}
__device__ __forceinline__ uint32_t ld1(const void* p) {
    uint32_t v;
    asm volatile("ld.relaxed.gpu.global.u32 %0, [%1];" : "=r"(v) : "l"(p) : "memory");
    return v;
}
__device__ __forceinline__ uint4 ld4(const void* p) {
    uint4 v;
    asm volatile("ld.relaxed.gpu.global.v4.u32 {%0, %1, %2, %3}, [%4];" : "=r"(v.x), "=r"(v.y), "=r"(v.z), "=r"(v.w) : "l"(p) : "memory");
    return v;
}
__device__ __forceinline__ void ld4p(const void* p, uint4& v, bool on) {
    asm volatile("{\n.reg .pred q;\nsetp.ne.u32 q, %5, 0;\n@q ld.relaxed.gpu.global.v4.u32 {%0, %1, %2, %3}, [%4];\n}"
                 : "+r"(v.x), "+r"(v.y), "+r"(v.z), "+r"(v.w) : "l"(p), "r"((uint32_t)on) : "memory");
}
__device__ __forceinline__ bool ok8(const uint4& v) {
    const uint32_t m = __vimax3_u16x2(__vimax3_u16x2(v.x, v.y, v.z), v.w, v.w);
    return __vimax3_u16x2(m, m << 16, m >> 16) != SENT;
}
__device__ __forceinline__ void poll4(const void* p, uint4& v) {
    asm volatile("{\n.reg .pred q;\n.reg .u32 m;\nmax.u32 m, %0, %1;\nmax.u32 m, m, %2;\nmax.u32 m, m, %3;\nsetp.eq.u32 q, m, 0xffffffff;\n"
                 "@q ld.relaxed.gpu.global.v4.u32 {%0, %1, %2, %3}, [%4];\n}"
                 : "+r"(v.x), "+r"(v.y), "+r"(v.z), "+r"(v.w) : "l"(p) : "memory");
}
__device__ __forceinline__ uint32_t max4(const uint4& v) { return max(max(v.x, v.y), max(v.z, v.w)); }
__device__ __forceinline__ void pkt_st2(uint4* p, float a, float b, uint32_t tag) {
    asm volatile("st.relaxed.gpu.global.v2.b64 [%0], {%1, %2};" ::"l"(p), "l"(((uint64_t)tag << 32) | __float_as_uint(a)), "l"(((uint64_t)tag << 32) | __float_as_uint(b)) : "memory");
}
__device__ __forceinline__ void pkt_ld2(const uint4* p, uint64_t& a, uint64_t& b) {
    asm volatile("ld.relaxed.gpu.global.v2.b64 {%0, %1}, [%2];" : "=l"(a), "=l"(b) : "l"(p) : "memory");
}
__device__ __forceinline__ bool tag_ok(uint64_t v, uint32_t tag) { return (uint32_t)(v >> 32) == tag; }
__device__ __forceinline__ float val_of(uint64_t v) { return __uint_as_float((uint32_t)v); }

__device__ __forceinline__ float warp_sum(float v) {
#pragma unroll
    for (int o = 16; o > 0; o >>= 1) v += __shfl_xor_sync(0xffffffffu, v, o);
    return v;
}
__device__ __forceinline__ float warp_max(float v) {
#pragma unroll
    for (int o = 16; o > 0; o >>= 1) v = fmaxf(v, __shfl_xor_sync(0xffffffffu, v, o));
    return v;
}
__device__ __forceinline__ float sqrt_fast(float x) { float r; asm("sqrt.approx.ftz.f32 %0, %1;" : "=f"(r) : "f"(x)); return r; }
__device__ __forceinline__ float rcp_fast(float x) { float r; asm("rcp.approx.ftz.f32 %0, %1;" : "=f"(r) : "f"(x)); return r; }
__device__ __forceinline__ float ex2(float x) { float r; asm("ex2.approx.ftz.f32 %0, %1;" : "=f"(r) : "f"(x)); return r; }
constexpr float L2E = 1.4426950408889634f;
__device__ __forceinline__ void ln_finish(float s1, float s2, float& mean_b, float& inv_den) {
    const float mean = s1 * (1.0f / D_MODEL);
    const float var = fmaxf(fmaf(-mean, mean, s2 * (1.0f / D_MODEL)), 0.f);
    mean_b = bfr(mean);
    inv_den = rcp_fast(bfr(sqrt_fast(bfr(bfr(var) + 1e-5f))));
}
__device__ __forceinline__ uint32_t ln_apply2(uint32_t u, float mean_b, float inv_den) {
    const uint32_t d = pack_bf(bf_hi(u) - mean_b, bf_lo(u) - mean_b);
    return pack_bf(bf_hi(d) * inv_den, bf_lo(d) * inv_den);
}
__device__ __forceinline__ void ln_acc(uint32_t u, float& s1, float& s2) {
    const float a = bf_lo(u), b = bf_hi(u);
    s1 += a + b;
    s2 = fmaf(a, a, fmaf(b, b, s2));
}
__device__ __forceinline__ float silu_b(float g) { return bfr(__fdividef(g, 1.0f + ex2(-g * L2E))); }

#define STAMP(i) do { } while (0)

struct KParams {
    const __nv_bfloat16* wq;
    const __nv_bfloat16* x;
    __nv_bfloat16* out;
    Scratch* sc;
    unsigned char* xa;
    int t_k0, per, stag;
    int target;
    int t_q, ogate, hgate, hdelay;
    uint32_t item[NTAIL];
    uint32_t role[NCTA];
};
struct TMaps { CUtensorMap k, v, wo, w1, w3, w2; };

__global__ void __launch_bounds__(NTHREADS, 1)
fused_decode_kernel(const __grid_constant__ KParams p, const __grid_constant__ TMaps tm) {
    extern __shared__ __align__(1024) unsigned char smem[];
    const int tid = threadIdx.x;
    const int b = blockIdx.x;
    const int head = b >> 2, sp = b & 3;
    if (tid < 256) {
        const uint32_t r = tid >> 3, ch = tid & 7;
        const char* src = reinterpret_cast<const char*>(p.wq) + ((sp * 160 + r) * (NHEAD * DH * 2) + head * (DH * 2) + ch * 16);
#pragma unroll
        for (int i = 0; i < NQT; i++) {
#pragma unroll
            for (int j = 0; j < 3; j++)
                asm volatile("cp.async.cg.shared.global [%0], [%1], 16;"
                             ::"r"(sbase + (QSLOT + i) * TILE_BYTES + (3 * r + j) * 128 + ((ch ^ ((3 * r + j) & 7)) << 4)),
                               "l"(src + (size_t)i * 32 * (NHEAD * DH * 2) + j * 128) : "memory");
        }
    }
    const uint32_t t0 = now_ns();
    const int warp = __shfl_sync(0xffffffffu, tid >> 5, 0), lane = tid & 31;
    const uint32_t role = p.role[b];
    const int kg = role >> 3 & 7, ng = role >> 6 & 31;
    const int u1 = role >> 11 & 127, u2 = role >> 18;
    const bool has_wo = role & 1, has_f1 = role & 2, has_f2 = role & 4;
    constexpr uint32_t bar_full = sbase + SM_BAR;
    constexpr uint32_t bar_empty = sbase + SM_BAR + 128;
    constexpr uint32_t bar_tail = sbase + SM_BAR + 256;
    constexpr uint32_t bar_scale = bar_tail + 8 * NTAIL;
    constexpr uint32_t bar_stat = bar_scale + 8;
    constexpr uint32_t bar_up = bar_scale + 16;

    if (warp == 8) {
        if (smem_u32(smem) != sbase) __trap();
        uint64_t pol;
        asm volatile("createpolicy.fractional.L2::evict_first.b64 %0, 1.0;" : "=l"(pol));
        sts32(sbase + SM_LATE + (lane & 7) * 4, 0u);
        if (lane == 0) {
#pragma unroll
            for (int i = 0; i < 32 + NTAIL + 3; i++) mbar_init(bar_full + 8 * i, (i >= 16 && i < 32) || i > 32 + NTAIL ? 8 : 1);
#pragma unroll
            for (int i = 0; i < 6; i++) asm volatile("prefetch.tensormap [%0];" ::"l"(reinterpret_cast<uint64_t>(&tm.k + i)) : "memory");
            asm volatile("fence.mbarrier_init.release.cluster;" ::: "memory");
        }
        __syncwarp();
        asm volatile("bar.arrive 2, 320;" ::: "memory");
        int slip = 0;
        if (lane == 0) {
            if (b == 0) { st4(p.sc->late, 0, 0, 0, 0); st4(p.sc->late + 4, 0, 0, 0, 0); }
            const int tile0 = (head * SK + (SK - WIN)) / 32 + sp;
            uint32_t tn = t0 + p.t_k0 + sp * p.stag, tw = tn, acc = 0;
            int w = 0;
#pragma unroll 1
            for (int n = 0; n < 2 * NKT; n++) {
                const int slot = n & (NSLOT - 1);
                mbar_wait(bar_empty + 8 * slot, (((n + NQT) >> 4) & 1) ^ 1);
                mbar_expect_tx(bar_full + 8 * slot, TILE_BYTES);
                uint32_t t;
                do {
                    t = now_ns();
                    if (mbar_test(bar_full + 8 * (w & (NSLOT - 1)), (w >> 4) & 1)) {
                        acc += t - tw;
                        tw += p.per;
                        if ((++w & 7) == 0) {
                            asm volatile("red.relaxed.gpu.global.add.u32 [%0], %1;" ::"l"(p.sc->late + (w >> 3)), "r"((1u << 24) + min(acc >> 3, 65535u)) : "memory");
                            acc = 0;
                        }
                    }
                } while ((int)(t - tn) < slip || w <= n - INFLIGHT);
                tma_load(sbase + slot * TILE_BYTES, &tm.k + (n >> 5), 0, tile0 + (n & (NKT - 1)) * 4, bar_full + 8 * slot, pol);
                tn += p.per;
                if ((n & 7) == 5)
                    asm volatile("cp.async.cg.shared.global [%0], [%1], 16;\ncp.async.cg.shared.global [%0+16], [%1+16], 16;" ::"r"(sbase + SM_LATE), "l"(p.sc->late) : "memory");
                uint32_t rep = lds32(sbase + SM_LATE + (n >> 3) * 4);
                if (!(rep >> 30)) rep = lds32(sbase + SM_LATE + (max(n - 8, 0) >> 3) * 4);
                if (rep >> 30) slip = max((int)((float)(rep & 0xffffffu) * rcp_fast((float)(rep >> 24))) - p.target, -500);
            }
        }
        const int seg = (lane >= NWP) + (lane >= NWP + NF1), i = lane - (seg == 0 ? 0 : seg == 1 ? NWP : NWP + NF1);
        bool todo = lane < NTAIL && (role >> seg & 1);
        const uint32_t len = seg == 1 ? 10240 : 8192, dst = sbase + (seg == 0 ? 0 : seg == 1 ? SM_W1 : SM_W2) + i * len;
        const CUtensorMap* m = &tm.wo + (seg == 0 ? 0 : seg == 1 ? 1 + (i >> 1) : 3);
        const int c0 = seg == 0 ? ng * 32 : seg == 1 ? u1 * 16 : u2 * 16;
        const int c4 = seg == 1 ? (i & 1) * 20 : (seg == 0 ? kg * 64 : 0) + i * 8;
        const uint32_t tn = __shfl_sync(0xffffffffu, t0 + slip, 0) + p.item[min(lane, NTAIL - 1)];
        if (todo) mbar_expect_tx(bar_tail + 8 * lane, len);
        do {
            if (todo && (int)(now_ns() - tn) >= 0 && mbar_test(bar_empty + 8 * (seg == 0 ? 5 : seg == 1 ? 8 : 12), seg != 2)) {
                tma_load(dst, m, c0, c4, bar_tail + 8 * lane, pol);
                todo = false;
            }
        } while (__any_sync(0xffffffffu, todo));
    } else if (warp == 9) {
        const uint32_t tag = ld1(&p.sc->epoch) + 1;
        const uint32_t aoff = XA_A + (u1 >> 1 & 7) * 384 + (u1 >> 4) * 64 + (u1 & 1) * 32, hoff = xa_h(kg) + ng * 128;
        sts32(sbase + SM_ONE + (lane & 15) * 4, 0x3f803f80u);
        const uint32_t ooff = xa_o(head) + sp * (DH * 4);
        unsigned char* slot[4] = {p.xa + (ooff + lane * 16), p.xa + ((ooff + 512 + (lane & 15) * 16) ^ (lane >> 4) << 12), p.xa + ((ooff + lane * 16) ^ 4096),
                                  p.xa + (lane < 16 ? (has_wo ? hoff + (lane >> 3) * 4096 + (lane & 7) * 16 : ooff) : has_f1 ? aoff + (lane >> 1 & 1) * 4096 + (lane & 1) * 16 : ooff)};
#pragma unroll
        for (int i = 0; i < 4; i++) st4(slot[i], SENT, SENT, SENT, SENT);
#pragma unroll
        for (int i = 0; i < 3; i++) st4(p.sc->qbuf + b * 96 + i * 32 + lane, 0, 0, 0, 0);
        uint4* mdst = p.sc->mbuf + b * 2 + (lane & 1);
        st4(mdst, 0, 0, 0, 0);
        sts32(sbase + SM_MISC, tag);
        asm volatile("bar.sync 2, 320;" ::: "memory");
        __nanosleep(3000);
        uint32_t ack = SENT;
#pragma unroll
        for (int i = 0; i < 4; i++) { uint32_t v; asm volatile("atom.relaxed.gpu.global.exch.b32 %0, [%1], -1;" : "=r"(v) : "l"(slot[i]) : "memory"); ack &= v; }
        if (__any_sync(0xffffffffu, ack != SENT)) __trap();
        if (lane == 0) st1(p.sc->ready + b, tag);
        while (!mbar_test(bar_stat, 0)) __nanosleep(200);
        const float4 ma = lds128f(sbase + SM_MAX), mb = lds128f(sbase + SM_MAX + 16);
        const float m = fmaxf(fmaxf(fmaxf(ma.x, ma.y), fmaxf(ma.z, ma.w)), fmaxf(fmaxf(mb.x, mb.y), fmaxf(mb.z, mb.w)));
        pkt_st2(mdst, m, sum8(sbase + SM_SUM), tag);
        int vote = 0;
#pragma unroll 1
        for (int r = 0; r < 9; r++) {
            __nanosleep(100);
            uint32_t d;
            asm volatile("{\n.reg .pred p, q;\n.reg .b32 a, b, c0, c1;\nmov.b32 c0, 0;\nmov.b32 c1, 0;\n"
                         "atom.relaxed.gpu.global.exch.b32 a, [%1], -1;\natom.relaxed.gpu.global.exch.b32 b, [%2], -1;\n"
                         "setp.eq.u32 p, a, -1;\n@p mov.u32 c0, %%clock;\nsetp.eq.u32 q, b, -1;\n@q mov.u32 c1, %%clock;\nsub.u32 %0, c1, c0;\n}"
                         : "=r"(d) : "l"(r & 1 ? slot[2] : slot[0]), "l"(r & 1 ? slot[0] : slot[2]) : "memory");
            vote += (d > 90) == (r & 1) ? 1 : -1;
        }
        const uint32_t side = __shfl_sync(0xffffffffu, vote, 0) > 0;
        uint32_t n = 0;
        {
            uint64_t em, el;
            while (true) {
                const uint4 e = ld4(p.sc->ready + lane * 4);
                pkt_ld2(p.sc->mbuf + (head * 4 + (lane & 3)) * 2, em, el);
                if (__all_sync(0xffffffffu, e.x == tag && e.y == tag && e.z == tag && e.w == tag && tag_ok(em, tag) && tag_ok(el, tag))) break;
                __nanosleep(500);
                if (++n > SPIN_LIMIT) __trap();
            }
            float M = fmaxf(val_of(em), __shfl_xor_sync(0xffffffffu, val_of(em), 1));
            M = fmaxf(M, __shfl_xor_sync(0xffffffffu, M, 2));
            float L = ex2((val_of(em) - M) * L2E) * val_of(el);
            L += __shfl_xor_sync(0xffffffffu, L, 1);
            L += __shfl_xor_sync(0xffffffffu, L, 2);
            if (lane == 0) {
                sts64(sbase + SM_MISC + 8, __float_as_uint(__fdividef(ex2((m - M) * L2E), L)), side);
                mbar_arrive(bar_scale);
                if (b == 0) p.sc->epoch = tag;
            }
        }
        unsigned char* hdst = p.xa + (hoff + (side ^ 1) * 4096 + lane * 4);
        unsigned char* hdst2 = p.xa + (hoff + side * 4096 + lane * 4);
        unsigned char* adst = p.xa + (aoff + (lane >> 4) * 4096 + (lane & 15) * 2);
        __nv_bfloat16* odst = p.out + u2 * 16 + (lane & 15);
        uint32_t r0 = sbase + SM_RED + lane * 48, r1 = sbase + SM_RED + (lane & 15) * 48;
        uint32_t res;
        asm volatile("ld.global.nc.u16 %0, [%1];" : "=r"(res) : "l"(p.x + u2 * 16 + (lane & 15)));
        pin(hdst); pin(hdst2); pin(adst); pin(odst); pin(r0); pin(r1);
        if (has_wo) {
            fin_sync<3>();
            const uint32_t v = in_word(sum8(r0));
            st1(hdst, v); st1(hdst2, v);
            STAMP(4);
        }
        if (has_f1) {
            fin_sync<4>();
            float mean_b, inv_den;
            ln_finish(sum8(sbase + SM_LN), sum8(sbase + SM_LN + 32), mean_b, inv_den);
            const float gr = fmaf(-mean_b, sum8(r1 + 48 * 48), sum8(r1 + 32 * 48)) * inv_den;
            mbar_wait_after(bar_up, r0, gr);
            const float gs = bfr(gr);
            const float up = bfr(fmaf(-mean_b, sum8(r1 + 80 * 48), sum8(r1 + 64 * 48)) * inv_den);
            asm volatile("st.relaxed.gpu.global.u16 [%0], %1;" ::"l"(adst), "h"((unsigned short)pack_bf(0.f, silu_b(gs) * up)) : "memory");
            STAMP(8);
        }
        if (has_f2) {
            mbar_wait(bar_tail + 8 * (NWP + NF1 + p.hgate), 0);
            const unsigned char* hsrc = p.xa + ((lane >> 4) * (1 << 14) + side * 4096 + u2 * 64 + (lane & 15) * 4);
            uint32_t e[3];
            do {
#pragma unroll
                for (int i = 0; i < 3; i++) e[i] = ld1(hsrc + xa_h(2 * i));
                if (++n > SPIN_LIMIT) __trap();
            } while (__any_sync(0xffffffffu, max(max(e[0], e[1]), e[2]) == SENT));
            float f[3];
#pragma unroll
            for (int i = 0; i < 3; i++) f[i] = __uint_as_float(e[i]) + __uint_as_float(__shfl_xor_sync(0xffffffffu, e[i], 16));
            res = add_bf2(res, pack_bf(0.f, (f[0] + f[1]) + f[2]));
            pin(res);
            fin_sync<6>();
            asm volatile("st.global.u16 [%0], %1;" ::"l"(odst), "h"((unsigned short)add_bf2(res, pack_bf(0.f, sum8(r1 + 96 * 48)))) : "memory");
            STAMP(11);
        }
    } else {
        const int g = lane >> 2, t = lane & 3;
        uint2 xres;
        {
            uint32_t xr;
            uint2 xu[5];
            const char* xb = reinterpret_cast<const char*>(p.x);
            asm volatile("ld.global.nc.u16 %0, [%1];" : "=r"(xr) : "l"(xb + (sp * 160 + min(tid, 159)) * 2));
#pragma unroll
            for (int i = 0; i < 5; i++) asm volatile("ld.global.nc.v2.u32 {%0, %1}, [%2];" : "=r"(xu[i].x), "=r"(xu[i].y) : "l"(xb + i * 256 + lane * 8));
            asm volatile("ld.global.nc.v2.u32 {%0, %1}, [%2];" : "=r"(xres.x), "=r"(xres.y) : "l"(xb + warp * 160 + min(lane, 19) * 8));
            if (lane >= 20) xres.x = xres.y = 0;
            float s1 = 0.f, s2 = 0.f, mean_b, inv_den;
#pragma unroll
            for (int i = 0; i < 5; i++) { ln_acc(xu[i].x, s1, s2); ln_acc(xu[i].y, s1, s2); }
            ln_finish(warp_sum(s1), warp_sum(s2), mean_b, inv_den);
            sts16(sbase + SM_P + warp * 64 + ((lane >> 1 & 3) * 8 + (lane >> 3) * 2 + (lane & 1)) * 2, ln_apply2(xr, mean_b, inv_den));
            asm volatile("cp.async.wait_all;" ::: "memory");
            asm volatile("bar.sync 2, 320;" ::: "memory");
        }
        STAMP(0);
        uint32_t va[3];
#pragma unroll
        for (int i = 0; i < 3; i++) {
            const int cc = 3 * warp + i, row = 3 * lane + (cc >> 3);
            va[i] = sbase + row * 128 + (((cc ^ row) & 7) << 4);
        }
        const int gi = g >= 3 ? g - 3 : g;
        unsigned char* odst = p.xa + ((xa_o(head) ^ (g >= 3 ? 4096 : 0)) + sp * (DH * 4) + (warp * 24 + gi * 8 + t * 2) * 4);
        pin(odst);

#pragma unroll 1
        for (int ph = 0; ph < 2; ph++) {
            if (ph == 1) {
                uint4 qf[6];
#pragma unroll
                for (int i = 0; i < 6; i++) qf[i] = lds128(sbase + SM_Q + t * 96 + i * 16);
                uint32_t ka[3];
#pragma unroll
                for (int j = 0; j < 3; j++) {
                    const int row = 3 * (lane & 15) + j;
                    ka[j] = sbase + row * 128 + ((((lane >> 4) ^ row) & 7) << 4) + warp * TILE_BYTES;
                }
                float s[4] = {0.f, 0.f, 0.f, 0.f};
#pragma unroll 1
                for (int it = 0; it < 4; it++) {
                    const int slot = (it & 1) * 8 + warp;
                    const uint32_t so = (it & 1) * 8 * TILE_BYTES;
                    float c[2][2][4];
                    zero4(c[0][0]); zero4(c[0][1]); zero4(c[1][0]); zero4(c[1][1]);
                    mbar_wait(bar_full + 8 * slot, it >> 1);
#pragma unroll
                    for (int ks = 0; ks < 12; ks++) {
                        const uint32_t a = (ka[ks >> 2] + so) ^ ((ks & 3) << 5);
                        uint32_t f0[4], f1[4];
                        ldsm_x4(f0, a); ldsm_x4(f1, a + 16 * DH * 2);
                        const uint32_t b0 = ks & 1 ? qf[ks >> 1].z : qf[ks >> 1].x, b1 = ks & 1 ? qf[ks >> 1].w : qf[ks >> 1].y;
                        mma_bf16(c[0][ks & 1], f0, b0, b1); mma_bf16(c[1][ks & 1], f1, b0, b1);
                    }
                    if (lane == 0) mbar_arrive8(bar_empty + 8 * slot);
                    const float v = t & 2 ? (t & 1 ? c[1][0][2] + c[1][1][2] : c[1][0][0] + c[1][1][0]) : (t & 1 ? c[0][0][2] + c[0][1][2] : c[0][0][0] + c[0][1][0]);
                    s[0] = s[1]; s[1] = s[2]; s[2] = s[3];
                    s[3] = bfr(bfr(v) * 0.07216878364870322f);
                }
                const float mw = warp_max(fmaxf(fmaxf(s[0], s[1]), fmaxf(s[2], s[3])));
                if (lane == 0) sts32(sbase + SM_MAX + warp * 4, mw);
                cons_sync();
                const float4 ma = lds128f(sbase + SM_MAX), mb = lds128f(sbase + SM_MAX + 16);
                const float m = fmaxf(fmaxf(fmaxf(ma.x, ma.y), fmaxf(ma.z, ma.w)), fmaxf(fmaxf(mb.x, mb.y), fmaxf(mb.z, mb.w)));
                float l = 0.f;
#pragma unroll
                for (int it = 0; it < 4; it++) {
                    const float e = ex2((s[it] - m) * L2E);
                    l += e;
                    sts16(sbase + SM_P + (it * 8 + warp) * 64 + ((g >> 1) * 8 + t * 2 + (g & 1)) * 2, pack_bf(0.f, e));
                }
                l = warp_sum(l);
                if (lane == 0) { sts32(sbase + SM_SUM + warp * 4, l); mbar_arrive(bar_stat); }
                cons_sync();
                STAMP(1);
            }
            float acc[2][3][4];
#pragma unroll
            for (int i = 0; i < 3; i++) { zero4(acc[0][i]); zero4(acc[1][i]); }
            const int nt = ph ? NKT : NQT;
            float scale = 1.f;
#pragma unroll 1
            for (int n = 0; n < nt; n++) {
                const int slot = ph ? (n & (NSLOT - 1)) : QSLOT + n;
                const uint4 w = lds128(sbase + SM_P + n * 64 + t * 16);
                if (n == NKT - 1) { mbar_wait(bar_scale, 0); scale = __uint_as_float(lds32(sbase + SM_MISC + 8)); }
                if (ph) mbar_wait(bar_full + 8 * slot, (n >> 4) & 1);
                uint32_t f[3][4];
#pragma unroll
                for (int i = 0; i < 3; i++) ldsm_x4_t(f[i], va[i] + slot * TILE_BYTES);
#pragma unroll
                for (int i = 0; i < 3; i++) {
                    mma_bf16(acc[0][i], w.x, w.x, w.y, w.y, f[i][0], f[i][1]);
                    mma_bf16(acc[1][i], w.z, w.z, w.w, w.w, f[i][2], f[i][3]);
                }
                if (lane == 0) mbar_arrive(bar_empty + 8 * slot);
            }
            const float v0 = (gi == 0 ? acc[0][0][0] + acc[1][0][0] : gi == 1 ? acc[0][1][0] + acc[1][1][0] : acc[0][2][0] + acc[1][2][0]) * scale;
            const float v1 = (gi == 0 ? acc[0][0][1] + acc[1][0][1] : gi == 1 ? acc[0][1][1] + acc[1][1][1] : acc[0][2][1] + acc[1][2][1]) * scale;
            if (ph == 1) {
                if (g < 6) st2(odst, in_word(v0), in_word(v1));
                break;
            }
            const uint32_t tag = lds32(sbase + SM_MISC);
            if (g < 3) pkt_st2(p.sc->qbuf + b * 96 + warp * 12 + lane, v0, v1, tag);
            if (warp < 3) {
                const uint4* src = p.sc->qbuf + head * 4 * 96 + tid;
                uint64_t e[4][2];
                uint32_t n = 0;
                bool ok;
#pragma unroll 1
                do {
                    __nanosleep(p.t_q);
                    ok = true;
#pragma unroll
                    for (int i = 0; i < 4; i++) { pkt_ld2(src + i * 96, e[i][0], e[i][1]); }
#pragma unroll
                    for (int i = 0; i < 4; i++) ok = ok && tag_ok(e[i][0], tag) && tag_ok(e[i][1], tag);
                    if (++n > SPIN_LIMIT) __trap();
                } while (!__all_sync(0xffffffffu, ok));
                sts32(sbase + SM_Q + (t * 24 + (tid >> 2)) * 4,
                      pack_bf((val_of(e[0][1]) + val_of(e[1][1])) + (val_of(e[2][1]) + val_of(e[3][1])), (val_of(e[0][0]) + val_of(e[1][0])) + (val_of(e[2][0]) + val_of(e[3][0]))));
            }
            cons_sync();
        }
        STAMP(2);
        const uint32_t side = lds32(sbase + SM_MISC + 12) * 4096;
        const uint32_t d16 = kg * 64 + g * 8 + warp, oh = d16 / 12;
        const unsigned char* osrc = p.xa + ((xa_o(oh) ^ side) + (d16 - oh * 12) * 64 + t * 16);
        const int r16 = (lane & 7) + ((lane >> 4) << 3), mi = lane >> 3 & 1;
        const uint32_t f32 = sbase + r16 * 32 + ((mi ^ (lane >> 2 & 1)) << 4);
        uint32_t rdst = sbase + SM_RED + (t * 8 + g) * 48 + warp * 4;
        uint32_t bl = sbase + SM_BC + warp * 512 + t * 80, bs = bl + g * 8;
        uint32_t hl = g < 4 ? bl : sbase + SM_ONE;
        uint32_t w1a = f32 + SM_W1 + warp * 2560, w2a = f32 + SM_W2 + warp * 1024;
        uint32_t gate = bar_tail + 8 * (NWP + (warp >> 2));
        uint32_t lnd = lane < 2 ? sbase + SM_LN + lane * 32 + warp * 4 : sbase + SM_BC + warp * 512 + 384 + lane * 4;
        const unsigned char* hs = p.xa + (side + warp * 320 + lane * 16);
        const unsigned char* as = p.xa + (XA_A + side + warp * 384 + min(lane, 23) * 16);
        uint32_t al = sbase + SM_BC + warp * 512 + t * 16, at = sbase + SM_BC + warp * 512 + lane * 16;
        uint32_t fl = role, ln = lane;
        pin_u(fl); pin(ln);
        const bool f1 = fl & 2, f2 = fl & 4, odd = ln & 1, first = ln == 0;
        constexpr uint32_t b2 = bar_tail + 8 * (NWP + NF1);
        pin(rdst); pin(bs); pin(hl); pin(w1a); pin(w2a); pin_u(gate); pin(lnd); pin(hs); pin(as); pin(al); pin(at);
#define F_(i, c) __uint_as_float(e[i].c)
        if (has_wo) {
            uint4 e[4];
#pragma unroll
            for (int i = 0; i < 4; i++) e[i].x = e[i].y = e[i].z = e[i].w = SENT;
            uint32_t n = 0;
            mbar_wait(bar_tail + 8 * p.ogate, 0);
#pragma unroll 1
            do {
                if (n) __nanosleep(100);
#pragma unroll
                for (int i = 0; i < 4; i++) poll4(osrc + i * (DH * 4), e[i]);
                if (++n > SPIN_LIMIT) __trap();
            } while (__any_sync(0xffffffffu, max(max(max4(e[0]), max4(e[1])), max(max4(e[2]), max4(e[3]))) == SENT));
            sts64(bs, pack_bf((F_(0, y) + F_(1, y)) + (F_(2, y) + F_(3, y)), (F_(0, x) + F_(1, x)) + (F_(2, x) + F_(3, x))),
                      pack_bf((F_(0, w) + F_(1, w)) + (F_(2, w) + F_(3, w)), (F_(0, z) + F_(1, z)) + (F_(2, z) + F_(3, z))));
            __syncwarp();
#pragma unroll
            for (int i = 0; i < 4; i++) e[i] = lds128(bl + i * 16);
            STAMP(3);
            const uint32_t wa = sbase + (warp * 16 + r16) * 64 + ((mi ^ (r16 >> 1 & 3)) << 4), wb = wa ^ 32;
            float c0[4], c1[4];
            zero4(c0); zero4(c1);
#pragma unroll
            for (int j = 0; j < NWP; j++) {
                mbar_wait(bar_tail + 8 * j, 0);
                uint32_t f0[4], f1[4];
                ldsm_x4_t(f0, wa + j * 8192); ldsm_x4_t(f1, wb + j * 8192);
                const uint32_t b0 = j & 1 ? e[j >> 1].z : e[j >> 1].x, b1 = j & 1 ? e[j >> 1].w : e[j >> 1].y;
                mma_bf16(c0, f0, b0, b1); mma_bf16(c1, f1, b0, b1);
            }
            sts32(rdst, t & 2 ? (t & 1 ? c1[2] : c1[0]) : (t & 1 ? c0[2] : c0[0]));
            fin_arrive<3>();
        }
        if (f1) {
            uint32_t a1[5][4], a3[5][4];
            uint4 e[NG];
#pragma unroll
            for (int i = 0; i < NG; i++) e[i].x = e[i].y = e[i].z = e[i].w = 0;
            uint32_t got3 = 0, n = 0;
#pragma unroll
            for (int i = 0; i < 5; i++) a3[i][0] = a3[i][1] = a3[i][2] = a3[i][3] = 0;
            if (!(fl & 1) || p.hdelay < 0) mbar_wait(b2 - 8 * NF1, 0);
            if (p.hdelay > 0) { const uint32_t c0 = (uint32_t)clock(); while ((uint32_t)clock() - c0 < p.hdelay) {} }
#pragma unroll
            for (int i = 0; i < NG; i++) ld4p(hs + xa_h(i), e[i], lane < 20);
            mbar_wait(gate, 0);
#pragma unroll
            for (int i = 0; i < 5; i++) ldsm_x4_t(a1[i], w1a + i * 512);
            ldsm5_if(a3, w1a + (SM_W3 - SM_W1), gate + 16, got3);
            uint4 hb0, hb1;
            uint2 hb2;
            float sv[4];
#pragma unroll 1
            while (true) {
#define S_(c) (((F_(0, c) + F_(1, c)) + (F_(2, c) + F_(3, c))) + (F_(4, c) + F_(5, c)))
                const float sx = S_(x), sy = S_(y), sz = S_(z), sw = S_(w), sa = (sx + sy) + (sz + sw);
#undef S_
                const uint32_t h0 = add_bf2(xres.x, pack_bf(sy, sx)), h1 = add_bf2(xres.y, pack_bf(sw, sz));
                sts64(bs, h0, h1);
                __syncwarp();
                hb0 = lds128(hl); hb1 = lds128(hl + 16); hb2 = lds64(hl + 32);
                const float a = bf_lo(h0), b = bf_hi(h0), c = bf_lo(h1), d = bf_hi(h1);
                const float s1 = (a + b) + (c + d), s2 = fmaf(a, a, b * b) + fmaf(c, c, d * d);
                sv[0] = odd ? s2 : s1;
                sv[1] = __shfl_xor_sync(0xffffffffu, odd ? s1 : s2, 1);
                sv[2] = __shfl_xor_sync(0xffffffffu, sv[0], 2);
                sv[3] = __shfl_xor_sync(0xffffffffu, odd ? s1 : s2, 3);
                bool miss = __any_sync(0xffffffffu, sa != sa);
                if (n == 0) STAMP(12);
                if (miss) {
                    miss = false;
#pragma unroll
                    for (int i = 0; i < NG; i++) {
                        const bool m = max4(e[i]) == SENT;
                        ld4p(hs + xa_h(i), e[i], m);
                        miss = miss || m;
                    }
                    ldsm5_if(a3, w1a + (SM_W3 - SM_W1), gate + 16, got3);
                    if (++n > SPIN_LIMIT) __trap();
                    miss = __any_sync(0xffffffffu, miss);
                }
                if (!miss) break;
            }
            STAMP(5);
            float cg[3][4], cu[3][4];
#pragma unroll
            for (int i = 0; i < 3; i++) { zero4(cg[i]); zero4(cu[i]); }
            const float st = (sv[0] + sv[1]) + (sv[2] + sv[3]);
#pragma unroll
            for (int i = 0; i < 4; i++) sv[i] = __shfl_down_sync(0xffffffffu, st, 4 * i + 4);
            mma_bf16(cg[0], a1[0], hb0.x, hb0.y); mma_bf16(cg[1], a1[1], hb0.z, hb0.w); mma_bf16(cg[2], a1[2], hb1.x, hb1.y);
            sts32(lnd, ((st + sv[0]) + sv[1]) + (sv[2] + sv[3]));
            mma_bf16(cg[0], a1[3], hb1.z, hb1.w); mma_bf16(cg[1], a1[4], hb2.x, hb2.y);
            mma_bf16(cu[0], a3[0], hb0.x, hb0.y); mma_bf16(cu[1], a3[1], hb0.z, hb0.w); mma_bf16(cu[2], a3[2], hb1.x, hb1.y);
            sts32(rdst + 32 * 48, odd ? (cg[0][2] + cg[2][2]) + cg[1][2] : (cg[0][0] + cg[2][0]) + cg[1][0]);
            fin_arrive<4>();
            STAMP(6);
            if (__any_sync(0xffffffffu, !got3)) {
                mbar_wait(gate + 16, 0);
#pragma unroll
                for (int i = 0; i < 5; i++) ldsm_x4_t(a3[i], w1a + (SM_W3 - SM_W1) + i * 512);
                mma_bf16(cu[0], a3[0], hb0.x, hb0.y); mma_bf16(cu[1], a3[1], hb0.z, hb0.w); mma_bf16(cu[2], a3[2], hb1.x, hb1.y);
            }
            mma_bf16(cu[0], a3[3], hb1.z, hb1.w); mma_bf16(cu[1], a3[4], hb2.x, hb2.y);
            sts32(rdst + 64 * 48, odd ? (cu[0][2] + cu[2][2]) + cu[1][2] : (cu[0][0] + cu[2][0]) + cu[1][0]);
            __syncwarp();
            if (first) mbar_arrive(bar_up);
        }
        if (f2) {
            uint32_t a2[NF2][2][4];
#pragma unroll
            for (int i = 0; i < 4; i++) a2[NF2 - 1][0][i] = a2[NF2 - 1][1][i] = 0;
#pragma unroll
            for (int j = 0; j < NF2 - 1; j++) {
                mbar_wait(b2 + 8 * j, 0);
                ldsm_x4_t(a2[j][0], w2a + j * 8192); ldsm_x4_t(a2[j][1], w2a + j * 8192 + 512);
            }
            STAMP(9);
            uint32_t n = 0, got = 0;
            uint4 e[NF2];
#pragma unroll 1
            while (true) {
                const uint4 pa = ld4(as);
                asm volatile("{\n.reg .pred p, q;\nsetp.eq.u32 q, %8, 0;\nmbarrier.test_wait.parity.shared::cta.b64 p, [%10], 0;\nand.pred p, p, q;\n"
                             "@p ldmatrix.sync.aligned.m8n8.x4.trans.shared.b16 {%0,%1,%2,%3}, [%9];\n"
                             "@p ldmatrix.sync.aligned.m8n8.x4.trans.shared.b16 {%4,%5,%6,%7}, [%9+512];\n@p mov.u32 %8, 1;\n}"
                             : "+r"(a2[5][0][0]), "+r"(a2[5][0][1]), "+r"(a2[5][0][2]), "+r"(a2[5][0][3]),
                               "+r"(a2[5][1][0]), "+r"(a2[5][1][1]), "+r"(a2[5][1][2]), "+r"(a2[5][1][3]), "+r"(got)
                             : "r"(w2a + (NF2 - 1) * 8192), "r"(b2 + 8 * (NF2 - 1)) : "memory");
                if (++n > SPIN_LIMIT) __trap();
                sts128(at, pa);
                __syncwarp();
#pragma unroll
                for (int j = 0; j < NF2; j++) e[j] = lds128v(al + j * 64);
                if (__all_sync(0xffffffffu, ok8(pa))) break;
            }
            STAMP(10);
            float c[4][4];
            zero4(c[0]); zero4(c[1]); zero4(c[2]); zero4(c[3]);
#pragma unroll
            for (int j = 0; j < NF2; j++) { mma_bf16(c[(j & 1) * 2], a2[j][0], e[j].x, e[j].y); mma_bf16(c[(j & 1) * 2 + 1], a2[j][1], e[j].z, e[j].w); }
            if (__any_sync(0xffffffffu, !got)) {
                constexpr int j = NF2 - 1;
                mbar_wait(b2 + 8 * j, 0);
                ldsm_x4_t(a2[j][0], w2a + j * 8192); ldsm_x4_t(a2[j][1], w2a + j * 8192 + 512);
                mma_bf16(c[0], a2[j][0], e[j].x, e[j].y); mma_bf16(c[1], a2[j][1], e[j].z, e[j].w);
            }
            sts32(rdst + 96 * 48, odd ? (c[0][2] + c[1][2]) + (c[2][2] + c[3][2]) : (c[0][0] + c[1][0]) + (c[2][0] + c[3][0]));
            fin_arrive<6>();
        }
#undef F_
    }
}

typedef CUresult (*EncodeTiledFn)(CUtensorMap*, CUtensorMapDataType, cuuint32_t, void*, const cuuint64_t*, const cuuint64_t*,
                                  const cuuint32_t*, const cuuint32_t*, CUtensorMapInterleave, CUtensorMapSwizzle,
                                  CUtensorMapL2promotion, CUtensorMapFloatOOBfill);

void make_map(EncodeTiledFn fn, CUtensorMap* tm, const void* w, const int (&d)[5], const int (&st)[4], const int (&bx)[5],
              CUtensorMapSwizzle sw, int promo) {
    cuuint64_t dims[5], strides[4];
    cuuint32_t box[5], estr[5];
    for (int i = 0; i < 5; i++) { dims[i] = (cuuint64_t)d[i]; box[i] = (cuuint32_t)bx[i]; estr[i] = 1; }
    for (int i = 0; i < 4; i++) strides[i] = (cuuint64_t)st[i];
    fn(tm, CU_TENSOR_MAP_DATA_TYPE_BFLOAT16, 5, const_cast<void*>(w), dims, strides, box, estr, CU_TENSOR_MAP_INTERLEAVE_NONE, sw,
       (CUtensorMapL2promotion)promo, CU_TENSOR_MAP_FLOAT_OOB_FILL_NONE);
}

enum { T_PER, T_LEAD, T_STAG, T_TD, T_PERO, T_F1D, T_PERF, T_F2, T_PER2, T_Q, T_PWO, T_PW13, T_PW2, T_PRE, T_PERP, T_OG, T_HG, T_TG, T_HD, T_N };
#define TUNE_NAMES {"per", "lead", "stag", "td", "pero", "f1d", "perf", "f2", "per2", "q", "pwo", "pw13", "pw2", "pre", "perp", "og", "hg", "tg", "hd"}
int g_tune[T_N] = {478, 1200, 120, 120, 299, 150, 299, 1300, 130, 1600, 1, 2, 2, 0, 299, 1, 1, 1720, -1};

}

extern "C" void kernel_launch(void* const* d_in, const int* in_sizes, int n_in, void* d_out, int out_size) {
    (void)in_sizes; (void)n_in; (void)out_size;
    static EncodeTiledFn encode = nullptr;
    static Scratch* scratch = nullptr;
    static unsigned char* xarea = nullptr;
    if (!encode) {
        void* sp = nullptr;
        cudaGetSymbolAddress(&sp, g_scratch);
        scratch = reinterpret_cast<Scratch*>(sp);
        cudaGetSymbolAddress(&sp, g_xarea);
        xarea = reinterpret_cast<unsigned char*>((reinterpret_cast<uintptr_t>(sp) + XA_ALIGN - 1) / XA_ALIGN * XA_ALIGN);
        void* fn = nullptr;
        cudaDriverEntryPointQueryResult st;
        cudaGetDriverEntryPoint("cuTensorMapEncodeTiled", &fn, cudaEnableDefault, &st);
        encode = reinterpret_cast<EncodeTiledFn>(fn);
        cudaFuncSetAttribute(fused_decode_kernel, cudaFuncAttributeMaxDynamicSharedMemorySize, SM_TOTAL);
    }
    const int* T = g_tune;
    KParams p;
    p.x = (const __nv_bfloat16*)d_in[0];
    p.wq = (const __nv_bfloat16*)d_in[3];
    p.out = (__nv_bfloat16*)d_out;
    p.sc = scratch;
    p.xa = xarea;
    p.per = T[T_PER];
    p.stag = T[T_STAG];
    p.t_k0 = (NQT + 1) * T[T_PER] - T[T_LEAD];
    {
        int t = p.t_k0 + 2 * NKT * T[T_PER] + T[T_STAG] * 3 / 2 + T[T_TD];
        for (int i = 0; i < T[T_PRE]; i++, t += T[T_PERP]) p.item[NWP + i] = t;
        for (int i = 0; i < NWP; i++, t += T[T_PERO]) p.item[i] = t;
        for (int i = T[T_PRE], t1 = t + T[T_F1D]; i < NF1; i++, t1 += T[T_PERF]) p.item[NWP + i] = t1;
        for (int i = 0, t2 = t + T[T_F2]; i < NF2; i++, t2 += T[T_PER2]) p.item[NWP + NF1 + i] = t2;
    }
    p.ogate = T[T_OG]; p.hgate = T[T_HG]; p.target = T[T_TG]; p.hdelay = T[T_HD]; p.t_q = T[T_Q];
    for (int i = 0, nw = 0, n1 = 0, n2 = 0; i < NCTA; i++) {
        const int grp = i >> 2;
        const bool f2 = grp % 3 == 2, both = grp == 8 || grp == 23, wo = !both, f1 = !f2 || both;
        p.role[i] = (wo ? 1 | nw / 20 << 3 | nw % 20 << 6 : 0) | (f1 ? 2 | n1 << 11 : 0) | (f2 ? 4 | n2 << 18 : 0);
        nw += wo; n1 += f1; n2 += f2;
    }
    TMaps tm;
    constexpr int R1 = FF * 2, R2 = D_MODEL * 2;
    for (int i = 0; i < 2; i++)
        make_map(encode, &tm.k + i, d_in[1 + i], {64, 96, 1, 1, NHEAD * SK / 32}, {128, TILE_BYTES, TILE_BYTES, TILE_BYTES}, {64, 96, 1, 1, 1}, CU_TENSOR_MAP_SWIZZLE_128B, 2);
    make_map(encode, &tm.wo, d_in[4], {D_MODEL, 2, 4, 2, NHEAD * DH / 16}, {R2, 4 * R2, 2 * R2, 16 * R2}, {32, 2, 4, 2, 8}, CU_TENSOR_MAP_SWIZZLE_64B, T[T_PWO]);
    make_map(encode, &tm.w1, d_in[6], {FF, 2, 4, 2, D_MODEL / 16}, {R1, 4 * R1, 2 * R1, 16 * R1}, {16, 2, 4, 2, 20}, CU_TENSOR_MAP_SWIZZLE_32B, T[T_PW13]);
    make_map(encode, &tm.w3, d_in[7], {FF, 2, 4, 2, D_MODEL / 16}, {R1, 4 * R1, 2 * R1, 16 * R1}, {16, 2, 4, 2, 20}, CU_TENSOR_MAP_SWIZZLE_32B, T[T_PW13]);
    make_map(encode, &tm.w2, d_in[8], {D_MODEL, 2, 4, 4, FF / 32}, {R2, 8 * R2, 2 * R2, 32 * R2}, {16, 2, 4, 4, 8}, CU_TENSOR_MAP_SWIZZLE_32B, T[T_PW2]);
    fused_decode_kernel<<<NCTA, NTHREADS, SM_TOTAL, cudaStreamPerThread>>>(p, tm);
}
```

```cpp
#include <cuda_runtime.h>
#include <cuda_bf16.h>
#include <cuda.h>
#include <stdint.h>

namespace {

constexpr int D_MODEL = 640;
constexpr int NHEAD = 32;
constexpr int DH = 192;
constexpr int SK = 32768;
constexpr int WIN = 4096;
constexpr int FF = 1536;

constexpr int NCTA = 128;
constexpr int NTHREADS = 256 + 64;
constexpr int TILE_BYTES = 32 * DH * 2;
constexpr int NSLOT = 16;
constexpr int NKT = 32;
constexpr int NQT = 5;
constexpr int QSLOT = NSLOT - NQT;
constexpr int NG = 6;
constexpr int NWP = 8, NP1 = 10, NF2 = 6;
constexpr int NITEM = NWP + NP1 + NF2;
#define CFG_NSPEC 3
#define CFG_NA 2
#define CFG_NB 2
constexpr int NF1 = 4, NA = CFG_NA, NB = CFG_NB;
constexpr int NTAIL = NWP + NF1 + NF2;

constexpr int INFLIGHT = 7;

constexpr uint32_t sbase = 1024;
constexpr int SM_W1 = NWP * 8192, SM_W3 = SM_W1 + 20480, SM_W2 = SM_W3 + 20480;
constexpr int SM_P = NSLOT * TILE_BYTES;
constexpr int SM_Q = SM_P + 2048;
constexpr int SM_RED = SM_Q + 384;
constexpr int SM_BC = SM_RED + 128 * 48;
constexpr int SM_ONE = SM_BC + 4096;
constexpr int SM_MAX = SM_ONE + 64;
constexpr int SM_SUM = SM_MAX + 32;
constexpr int SM_LN = SM_SUM + 32;
constexpr int SM_MISC = SM_LN + 64;
constexpr int SM_LATE = SM_MISC + 32;
constexpr int SM_BAR = SM_LATE + 32;
constexpr int SM_TOTAL = SM_BAR + 512;
static_assert(SM_TOTAL <= 232448, "shared memory");

struct __align__(128) Scratch {
    uint4 qbuf[NCTA * 96];
    uint4 mbuf[NCTA * 2];
    uint32_t ready[NCTA];
    uint32_t late[32];
    uint32_t epoch;
};
__device__ Scratch g_scratch;
constexpr int XA_ALIGN = 1 << 20;
constexpr uint32_t SENT = 0xffffffffu;
__device__ unsigned char g_xarea[2 * XA_ALIGN];
__host__ __device__ constexpr uint32_t xa_o(uint32_t h) { return (2 * h + ((h ^ (h >> 3) ^ (h >> 4)) & 1)) * 4096; }
__host__ __device__ constexpr uint32_t xa_h(uint32_t i) { return (1 << 18) + (i >> 2) * (3 << 16) + (i & 3) * (1 << 14); }
constexpr uint32_t XA_A = xa_h(NG);

constexpr uint32_t SPIN_LIMIT = 1u << 22;

__device__ __forceinline__ uint32_t smem_u32(const void* p) { return (uint32_t)__cvta_generic_to_shared(p); }
__device__ __forceinline__ uint32_t now_ns() { uint64_t t; asm volatile("mov.u64 %0, %globaltimer;" : "=l"(t)); return (uint32_t)t; }
__device__ __forceinline__ void mbar_init(uint32_t bar, uint32_t cnt) {
    asm volatile("mbarrier.init.shared::cta.b64 [%0], %1;" ::"r"(bar), "r"(cnt) : "memory");
}
__device__ __forceinline__ void mbar_expect_tx(uint32_t bar, uint32_t bytes) {
    asm volatile("mbarrier.arrive.expect_tx.shared::cta.b64 _, [%0], %1;" ::"r"(bar), "r"(bytes) : "memory");
}
__device__ __forceinline__ void mbar_arrive(uint32_t bar) {
    asm volatile("mbarrier.arrive.shared::cta.b64 _, [%0];" ::"r"(bar) : "memory");
}
__device__ __forceinline__ void mbar_arrive8(uint32_t bar) {
    asm volatile("mbarrier.arrive.shared::cta.b64 _, [%0], 8;" ::"r"(bar) : "memory");
}
__device__ __forceinline__ bool mbar_test(uint32_t bar, uint32_t parity) {
    uint32_t ok;
    asm volatile("{\n.reg .pred p;\nmbarrier.test_wait.parity.shared::cta.b64 p, [%1], %2;\nselp.u32 %0, 1, 0, p;\n}"
                 : "=r"(ok) : "r"(bar), "r"(parity) : "memory");
    return ok;
}
__device__ __forceinline__ void mbar_wait(uint32_t bar, uint32_t parity) {
    asm volatile("{\n.reg .pred p;\nW_%=:\nmbarrier.try_wait.parity.shared::cta.b64 p, [%0], %1;\n@!p bra.uni W_%=;\n}" ::"r"(bar), "r"(parity) : "memory");
}
__device__ __forceinline__ void mbar_wait_after(uint32_t bar, uint32_t dump, float v) {
    uint32_t ok;
    asm volatile("{\n.reg .pred p;\nmbarrier.try_wait.parity.shared::cta.b64 p, [%1], 0;\nselp.u32 %0, 1, 0, p;\n}" : "=r"(ok) : "r"(bar) : "memory");
    asm volatile("st.volatile.shared.f32 [%0], %1;" ::"r"(dump), "f"(v) : "memory");
    if (__builtin_expect(!ok, 0)) mbar_wait(bar, 0);
}
__device__ __forceinline__ void tma_load(uint32_t dst, const CUtensorMap* tm, int c0, int c4, uint32_t bar, uint64_t pol) {
    asm volatile("cp.async.bulk.tensor.5d.shared::cluster.global.mbarrier::complete_tx::bytes.L2::cache_hint [%0], [%1, {%3, %5, %5, %5, %4}], [%2], %6;"
                 ::"r"(dst), "l"(reinterpret_cast<uint64_t>(tm)), "r"(bar), "r"(c0), "r"(c4), "r"(0), "l"(pol) : "memory");
}
__device__ __forceinline__ void pin(uint32_t& v) { asm volatile("shfl.sync.bfly.b32 %0, %0, 0, 31, -1;" : "+r"(v) :: "memory"); }
__device__ __forceinline__ void pin_u(uint32_t& v) { asm volatile("shfl.sync.idx.b32 %0, %0, 0, 31, -1;" : "+r"(v) :: "memory"); }
template <class T> __device__ __forceinline__ void pin(T*& v) {
    asm volatile("{\n.reg .b32 a, b;\nmov.b64 {a, b}, %0;\nshfl.sync.bfly.b32 a, a, 0, 31, -1;\nshfl.sync.bfly.b32 b, b, 0, 31, -1;\nmov.b64 %0, {a, b};\n}" : "+l"(v) :: "memory");
}
__device__ __forceinline__ void sts16(uint32_t a, uint32_t v) { asm volatile("st.shared.u16 [%0], %1;" ::"r"(a), "h"((unsigned short)v) : "memory"); }
__device__ __forceinline__ void sts32(uint32_t a, float v) { asm volatile("st.shared.f32 [%0], %1;" ::"r"(a), "f"(v) : "memory"); }
__device__ __forceinline__ void sts32(uint32_t a, uint32_t v) { asm volatile("st.shared.u32 [%0], %1;" ::"r"(a), "r"(v) : "memory"); }
__device__ __forceinline__ void sts64(uint32_t a, uint32_t x, uint32_t y) { asm volatile("st.shared.v2.u32 [%0], {%1, %2};" ::"r"(a), "r"(x), "r"(y) : "memory"); }
__device__ __forceinline__ void sts128(uint32_t a, const uint4& v) { asm volatile("st.shared.v4.u32 [%0], {%1, %2, %3, %4};" ::"r"(a), "r"(v.x), "r"(v.y), "r"(v.z), "r"(v.w) : "memory"); }
__device__ __forceinline__ void cons_sync() { asm volatile("bar.sync 1, 256;" ::: "memory"); }
template <int ID> __device__ __forceinline__ void fin_arrive() { asm volatile("bar.arrive %0, 288;" ::"n"(ID) : "memory"); }
template <int ID> __device__ __forceinline__ void fin_sync() { asm volatile("bar.sync %0, 288;" ::"n"(ID) : "memory"); }

__device__ __forceinline__ uint4 lds128(uint32_t a) {
    uint4 v;
    asm volatile("ld.shared.v4.u32 {%0,%1,%2,%3}, [%4];" : "=r"(v.x), "=r"(v.y), "=r"(v.z), "=r"(v.w) : "r"(a) : "memory");
    return v;
}
__device__ __forceinline__ uint4 lds128v(uint32_t a) {
    uint4 v;
    asm volatile("ld.volatile.shared.v4.u32 {%0,%1,%2,%3}, [%4];" : "=r"(v.x), "=r"(v.y), "=r"(v.z), "=r"(v.w) : "r"(a) : "memory");
    return v;
}
__device__ __forceinline__ float4 lds128f(uint32_t a) {
    float4 v;
    asm volatile("ld.shared.v4.f32 {%0,%1,%2,%3}, [%4];" : "=f"(v.x), "=f"(v.y), "=f"(v.z), "=f"(v.w) : "r"(a) : "memory");
    return v;
}
__device__ __forceinline__ uint2 lds64(uint32_t a) {
    uint2 v;
    asm volatile("ld.shared.v2.u32 {%0,%1}, [%2];" : "=r"(v.x), "=r"(v.y) : "r"(a) : "memory");
    return v;
}
__device__ __forceinline__ uint32_t lds32(uint32_t a) {
    uint32_t v;
    asm volatile("ld.shared.u32 %0, [%1];" : "=r"(v) : "r"(a) : "memory");
    return v;
}
__device__ __forceinline__ float sum8(uint32_t a) {
    const float4 x = lds128f(a), y = lds128f(a + 16);
    return ((x.x + x.y) + (x.z + x.w)) + ((y.x + y.y) + (y.z + y.w));
}
__device__ __forceinline__ void ldsm_x4(uint32_t* r, uint32_t a) {
    asm volatile("ldmatrix.sync.aligned.m8n8.x4.shared.b16 {%0,%1,%2,%3}, [%4];"
                 : "=r"(r[0]), "=r"(r[1]), "=r"(r[2]), "=r"(r[3]) : "r"(a) : "memory");
}
__device__ __forceinline__ void ldsm_x4_t(uint32_t* r, uint32_t a) {
    asm volatile("ldmatrix.sync.aligned.m8n8.x4.trans.shared.b16 {%0,%1,%2,%3}, [%4];"
                 : "=r"(r[0]), "=r"(r[1]), "=r"(r[2]), "=r"(r[3]) : "r"(a) : "memory");
}
template <int N, int STRIDE>
__device__ __forceinline__ void ldsm_if(uint32_t* r0, uint32_t* r1, uint32_t* r2, uint32_t a, uint32_t bar, uint32_t& got) {
    if (N == 2)
        asm volatile("{\n.reg .pred p, q;\nsetp.eq.u32 q, %8, 0;\nmbarrier.test_wait.parity.shared::cta.b64 p, [%10], 0;\nand.pred p, p, q;\n"
                     "@p ldmatrix.sync.aligned.m8n8.x4.trans.shared.b16 {%0,%1,%2,%3}, [%9];\n"
                     "@p ldmatrix.sync.aligned.m8n8.x4.trans.shared.b16 {%4,%5,%6,%7}, [%9+%11];\n@p mov.u32 %8, 1;\n}"
                     : "+r"(r0[0]), "+r"(r0[1]), "+r"(r0[2]), "+r"(r0[3]), "+r"(r1[0]), "+r"(r1[1]), "+r"(r1[2]), "+r"(r1[3]), "+r"(got)
                     : "r"(a), "r"(bar), "n"(STRIDE) : "memory");
    else
        asm volatile("{\n.reg .pred p, q;\nsetp.eq.u32 q, %12, 0;\nmbarrier.test_wait.parity.shared::cta.b64 p, [%14], 0;\nand.pred p, p, q;\n"
                     "@p ldmatrix.sync.aligned.m8n8.x4.trans.shared.b16 {%0,%1,%2,%3}, [%13];\n"
                     "@p ldmatrix.sync.aligned.m8n8.x4.trans.shared.b16 {%4,%5,%6,%7}, [%13+%15];\n"
                     "@p ldmatrix.sync.aligned.m8n8.x4.trans.shared.b16 {%8,%9,%10,%11}, [%13+%16];\n@p mov.u32 %12, 1;\n}"
                     : "+r"(r0[0]), "+r"(r0[1]), "+r"(r0[2]), "+r"(r0[3]), "+r"(r1[0]), "+r"(r1[1]), "+r"(r1[2]), "+r"(r1[3]),
                       "+r"(r2[0]), "+r"(r2[1]), "+r"(r2[2]), "+r"(r2[3]), "+r"(got)
                     : "r"(a), "r"(bar), "n"(STRIDE), "n"(2 * STRIDE) : "memory");
}
__device__ __forceinline__ void mma_bf16(float* c, uint32_t a0, uint32_t a1, uint32_t a2, uint32_t a3, uint32_t b0, uint32_t b1) {
    asm volatile("mma.sync.aligned.m16n8k16.row.col.f32.bf16.bf16.f32 {%0,%1,%2,%3}, {%4,%5,%6,%7}, {%8,%9}, {%0,%1,%2,%3};"
                 : "+f"(c[0]), "+f"(c[1]), "+f"(c[2]), "+f"(c[3]) : "r"(a0), "r"(a1), "r"(a2), "r"(a3), "r"(b0), "r"(b1));
}
__device__ __forceinline__ void mma_bf16(float* c, const uint32_t* a, uint32_t b0, uint32_t b1) { mma_bf16(c, a[0], a[1], a[2], a[3], b0, b1); }
__device__ __forceinline__ void zero4(float* c) { c[0] = c[1] = c[2] = c[3] = 0.f; }
__device__ __forceinline__ float bf_lo(uint32_t u) { return __uint_as_float(u << 16); }
__device__ __forceinline__ float bf_hi(uint32_t u) { return __uint_as_float(u & 0xffff0000u); }
__device__ __forceinline__ uint32_t pack_bf(float hi, float lo) { uint32_t r; asm("cvt.rn.bf16x2.f32 %0, %1, %2;" : "=r"(r) : "f"(hi), "f"(lo)); return r; }
__device__ __forceinline__ uint32_t add_bf2(uint32_t a, uint32_t b) { uint32_t r; asm("add.rn.bf16x2 %0, %1, %2;" : "=r"(r) : "r"(a), "r"(b)); return r; }
__device__ __forceinline__ float bfr(float x) { return __uint_as_float(pack_bf(x, 0.f)); }

__device__ __forceinline__ uint32_t in_word(float v) { return __float_as_uint(v); }
__device__ __forceinline__ void st1(void* p, uint32_t v) {
    asm volatile("st.relaxed.gpu.global.u32 [%0], %1;" ::"l"(p), "r"(v) : "memory");
}
__device__ __forceinline__ void st16(void* p, uint32_t v) {
    asm volatile("st.relaxed.gpu.global.u16 [%0], %1;" ::"l"(p), "h"((unsigned short)v) : "memory");
}
__device__ __forceinline__ void st2(void* p, uint32_t a, uint32_t b) {
    asm volatile("st.relaxed.gpu.global.v2.u32 [%0], {%1, %2};" ::"l"(p), "r"(a), "r"(b) : "memory");
}
__device__ __forceinline__ void st4(void* p, uint32_t a, uint32_t b, uint32_t c, uint32_t d) {
    asm volatile("st.relaxed.gpu.global.v4.u32 [%0], {%1, %2, %3, %4};" ::"l"(p), "r"(a), "r"(b), "r"(c), "r"(d) : "memory");
}
__device__ __forceinline__ uint32_t ld1(const void* p) {
    uint32_t v;
    asm volatile("ld.relaxed.gpu.global.u32 %0, [%1];" : "=r"(v) : "l"(p) : "memory");
    return v;
}
__device__ __forceinline__ uint4 ld4(const void* p) {
    uint4 v;
    asm volatile("ld.relaxed.gpu.global.v4.u32 {%0, %1, %2, %3}, [%4];" : "=r"(v.x), "=r"(v.y), "=r"(v.z), "=r"(v.w) : "l"(p) : "memory");
    return v;
}
__device__ __forceinline__ void ld4p(const void* p, uint4& v, bool on) {
    asm volatile("{\n.reg .pred q;\nsetp.ne.u32 q, %5, 0;\n@q ld.relaxed.gpu.global.v4.u32 {%0, %1, %2, %3}, [%4];\n}"
                 : "+r"(v.x), "+r"(v.y), "+r"(v.z), "+r"(v.w) : "l"(p), "r"((uint32_t)on) : "memory");
}
__device__ __forceinline__ void ld2p(const void* p, uint2& v, bool on) {
    asm volatile("{\n.reg .pred q;\nsetp.ne.u32 q, %3, 0;\n@q ld.relaxed.gpu.global.v2.u32 {%0, %1}, [%2];\n}"
                 : "+r"(v.x), "+r"(v.y) : "l"(p), "r"((uint32_t)on) : "memory");
}
__device__ __forceinline__ void poll2(const void* p, uint2& v) {
    asm volatile("{\n.reg .pred q, r;\nsetp.nan.bf16x2 q|r, %0, %1;\nor.pred q, q, r;\n@q ld.relaxed.gpu.global.v2.u32 {%0, %1}, [%2];\n}"
                 : "+r"(v.x), "+r"(v.y) : "l"(p) : "memory");
}
__device__ __forceinline__ bool ok8(const uint4& v) {
    const uint32_t m = __vimax3_u16x2(__vimax3_u16x2(v.x, v.y, v.z), v.w, v.w);
    return __vimax3_u16x2(m, m << 16, m >> 16) != SENT;
}
__device__ __forceinline__ void poll4(const void* p, uint4& v) {
    asm volatile("{\n.reg .pred q;\n.reg .u32 m;\nmax.u32 m, %0, %1;\nmax.u32 m, m, %2;\nmax.u32 m, m, %3;\nsetp.eq.u32 q, m, 0xffffffff;\n"
                 "@q ld.relaxed.gpu.global.v4.u32 {%0, %1, %2, %3}, [%4];\n}"
                 : "+r"(v.x), "+r"(v.y), "+r"(v.z), "+r"(v.w) : "l"(p) : "memory");
}
__device__ __forceinline__ uint32_t max4(const uint4& v) { return max(max(v.x, v.y), max(v.z, v.w)); }
__device__ __forceinline__ void pkt_st2(uint4* p, float a, float b, uint32_t tag) {
    asm volatile("st.relaxed.gpu.global.v2.b64 [%0], {%1, %2};" ::"l"(p), "l"(((uint64_t)tag << 32) | __float_as_uint(a)), "l"(((uint64_t)tag << 32) | __float_as_uint(b)) : "memory");
}
__device__ __forceinline__ void pkt_ld2(const uint4* p, uint64_t& a, uint64_t& b) {
    asm volatile("ld.relaxed.gpu.global.v2.b64 {%0, %1}, [%2];" : "=l"(a), "=l"(b) : "l"(p) : "memory");
}
__device__ __forceinline__ bool tag_ok(uint64_t v, uint32_t tag) { return (uint32_t)(v >> 32) == tag; }
__device__ __forceinline__ float val_of(uint64_t v) { return __uint_as_float((uint32_t)v); }

__device__ __forceinline__ float warp_sum(float v) {
#pragma unroll
    for (int o = 16; o > 0; o >>= 1) v += __shfl_xor_sync(0xffffffffu, v, o);
    return v;
}
__device__ __forceinline__ float warp_max(float v) {
#pragma unroll
    for (int o = 16; o > 0; o >>= 1) v = fmaxf(v, __shfl_xor_sync(0xffffffffu, v, o));
    return v;
}
__device__ __forceinline__ float sqrt_fast(float x) { float r; asm("sqrt.approx.ftz.f32 %0, %1;" : "=f"(r) : "f"(x)); return r; }
__device__ __forceinline__ float rcp_fast(float x) { float r; asm("rcp.approx.ftz.f32 %0, %1;" : "=f"(r) : "f"(x)); return r; }
__device__ __forceinline__ float ex2(float x) { float r; asm("ex2.approx.ftz.f32 %0, %1;" : "=f"(r) : "f"(x)); return r; }
constexpr float L2E = 1.4426950408889634f;
__device__ __forceinline__ void ln_finish(float s1, float s2, float& mean_b, float& inv_den) {
    const float mean = s1 * (1.0f / D_MODEL);
    const float var = fmaxf(fmaf(-mean, mean, s2 * (1.0f / D_MODEL)), 0.f);
    mean_b = bfr(mean);
    inv_den = rcp_fast(bfr(sqrt_fast(bfr(bfr(var) + 1e-5f))));
}
__device__ __forceinline__ uint32_t ln_apply2(uint32_t u, float mean_b, float inv_den) {
    const uint32_t d = pack_bf(bf_hi(u) - mean_b, bf_lo(u) - mean_b);
    return pack_bf(bf_hi(d) * inv_den, bf_lo(d) * inv_den);
}
__device__ __forceinline__ void ln_acc(uint32_t u, float& s1, float& s2) {
    const float a = bf_lo(u), b = bf_hi(u);
    s1 += a + b;
    s2 = fmaf(a, a, fmaf(b, b, s2));
}
__device__ __forceinline__ float silu_b(float g) { return bfr(__fdividef(g, 1.0f + ex2(-g * L2E))); }

#define STAMP(i) do { } while (0)

struct KParams {
    const __nv_bfloat16* wq;
    const __nv_bfloat16* x;
    __nv_bfloat16* out;
    Scratch* sc;
    unsigned char* xa;
    int t_k0, per, stag;
    int target;
    int t_q;
    uint32_t item[32];
    uint32_t role[NCTA];
};
struct TMaps { CUtensorMap k, v, wo, w1, w3, w2; };

__global__ void __launch_bounds__(NTHREADS, 1)
fused_decode_kernel(const __grid_constant__ KParams p, const __grid_constant__ TMaps tm) {
    extern __shared__ __align__(1024) unsigned char smem[];
    const int tid = threadIdx.x;
    const int b = blockIdx.x;
    const int head = b >> 2, sp = b & 3;
    if (tid < 256) {
        const uint32_t r = tid >> 3, ch = tid & 7;
        const char* src = reinterpret_cast<const char*>(p.wq) + ((sp * 160 + r) * (NHEAD * DH * 2) + head * (DH * 2) + ch * 16);
#pragma unroll
        for (int i = 0; i < NQT; i++) {
#pragma unroll
            for (int j = 0; j < 3; j++)
                asm volatile("cp.async.cg.shared.global [%0], [%1], 16;"
                             ::"r"(sbase + (QSLOT + i) * TILE_BYTES + (3 * r + j) * 128 + ((ch ^ ((3 * r + j) & 7)) << 4)),
                               "l"(src + (size_t)i * 32 * (NHEAD * DH * 2) + j * 128) : "memory");
        }
    }
    const uint32_t t0 = now_ns();
    const int warp = __shfl_sync(0xffffffffu, tid >> 5, 0), lane = tid & 31;
    const uint32_t role = p.role[b];
    const int kg = role >> 3 & 7, ng = role >> 6 & 31;
    const int u1 = role >> 11 & 127, u2 = role >> 18;
    const bool has_wo = role & 1, has_f1 = role & 2, has_f2 = role & 4;
    constexpr uint32_t bar_full = sbase + SM_BAR;
    constexpr uint32_t bar_empty = sbase + SM_BAR + 128;
    constexpr uint32_t bar_tail = sbase + SM_BAR + 256;
    constexpr uint32_t bar_scale = bar_tail + 8 * NTAIL;
    constexpr uint32_t bar_stat = bar_scale + 8;
    constexpr uint32_t bar_up = bar_scale + 16;

    if (warp == 8) {
        if (smem_u32(smem) != sbase) __trap();
        uint64_t pol;
        asm volatile("createpolicy.fractional.L2::evict_first.b64 %0, 1.0;" : "=l"(pol));
        sts32(sbase + SM_LATE + (lane & 7) * 4, 0u);
        if (lane == 0) {
#pragma unroll
            for (int i = 0; i < 32 + NTAIL + 3; i++)
                mbar_init(bar_full + 8 * i, (i >= 16 && i < 32) || i > 32 + NTAIL ? 8 : i == 32 + NWP ? NA : i == 33 + NWP ? 5 - NA : i == 34 + NWP ? NB : i == 35 + NWP ? 5 - NB : 1);
#pragma unroll
            for (int i = 0; i < 6; i++) asm volatile("prefetch.tensormap [%0];" ::"l"(reinterpret_cast<uint64_t>(&tm.k + i)) : "memory");
            asm volatile("fence.mbarrier_init.release.cluster;" ::: "memory");
        }
        __syncwarp();
        asm volatile("bar.arrive 2, 320;" ::: "memory");
        int slip = 0;
        if (lane == 0) {
            if (b == 0) { st4(p.sc->late, 0, 0, 0, 0); st4(p.sc->late + 4, 0, 0, 0, 0); }
            const int tile0 = (head * SK + (SK - WIN)) / 32 + sp;
            uint32_t tn = t0 + p.t_k0 + sp * p.stag, tw = tn, acc = 0;
            int w = 0;
#pragma unroll 1
            for (int n = 0; n < 2 * NKT; n++) {
                const int slot = n & (NSLOT - 1);
                mbar_wait(bar_empty + 8 * slot, (((n + NQT) >> 4) & 1) ^ 1);
                mbar_expect_tx(bar_full + 8 * slot, TILE_BYTES);
                uint32_t t;
                do {
                    t = now_ns();
                    if (mbar_test(bar_full + 8 * (w & (NSLOT - 1)), (w >> 4) & 1)) {
                        acc += t - tw;
                        tw += p.per;
                        if ((++w & 7) == 0) {
                            asm volatile("red.relaxed.gpu.global.add.u32 [%0], %1;" ::"l"(p.sc->late + (w >> 3)), "r"((1u << 24) + min(acc >> 3, 65535u)) : "memory");
                            acc = 0;
                        }
                    }
                } while ((int)(t - tn) < slip || w <= n - INFLIGHT);
                tma_load(sbase + slot * TILE_BYTES, &tm.k + (n >> 5), 0, tile0 + (n & (NKT - 1)) * 4, bar_full + 8 * slot, pol);
                tn += p.per;
                if ((n & 7) == 5)
                    asm volatile("cp.async.cg.shared.global [%0], [%1], 16;\ncp.async.cg.shared.global [%0+16], [%1+16], 16;" ::"r"(sbase + SM_LATE), "l"(p.sc->late) : "memory");
                uint32_t rep = lds32(sbase + SM_LATE + (n >> 3) * 4);
                if (!(rep >> 30)) rep = lds32(sbase + SM_LATE + (max(n - 8, 0) >> 3) * 4);
                if (rep >> 30) slip = max((int)((float)(rep & 0xffffffu) * rcp_fast((float)(rep >> 24))) - p.target, -500);
            }
        }
        const int seg = (lane >= NWP) + (lane >= NWP + NP1), i = lane - (seg == 0 ? 0 : seg == 1 ? NWP : NWP + NP1);
        const bool todo = lane < NITEM && (role >> seg & 1);
        const uint32_t len = seg == 1 ? 4096 : 8192, dst = sbase + (seg == 0 ? 0 : seg == 1 ? SM_W1 : SM_W2) + i * len;
        const int w3 = seg == 1 && i >= 5;
        const CUtensorMap* m = &tm.wo + (seg == 2 ? 3 : seg + w3);
        const int c0 = seg == 0 ? ng * 32 : seg == 1 ? u1 * 16 : u2 * 16;
        const int c4 = (seg == 0 ? kg * 64 : w3 * -40) + i * 8;
        const uint32_t bar = bar_tail + 8 * (seg == 0 ? i : seg == 1 ? NWP + (i >= NA) + w3 + (i >= 5 + NB) : NWP + NF1 + i);
        const uint32_t tn = (__shfl_sync(0xffffffffu, t0 + slip, 0) + p.item[lane]) | 1;
        if (todo) mbar_expect_tx(bar, len);
#pragma unroll 1
        for (int ph = 0; ph < 2; ph++) {
            mbar_wait(bar_empty + 8 * (ph ? 12 : 5), ph ^ 1);
            uint32_t due = todo && (seg != 0) == ph ? tn : 0;
            while (__any_sync(0xffffffffu, due)) {
                if (due && (int)(now_ns() - due) >= 0) {
                    tma_load(dst, m, c0, c4, bar, pol);
                    due = 0;
                }
            }
        }
    } else if (warp == 9) {
        const uint32_t tag = ld1(&p.sc->epoch) + 1;
        const uint32_t aoff = XA_A + (u1 >> 1 & 7) * 384 + (u1 >> 4) * 64 + (u1 & 1) * 32, hoff = xa_h(kg) + (ng & 3) * 512 + (ng >> 2) * 32;
        sts32(sbase + SM_ONE + (lane & 15) * 4, 0x3f803f80u);
        const uint32_t ooff = xa_o(head) + sp * (DH * 4);
        unsigned char* slot[4] = {p.xa + (ooff + lane * 16), p.xa + ((ooff + 512 + (lane & 15) * 16) ^ (lane >> 4) << 12), p.xa + ((ooff + lane * 16) ^ 4096),
                                  p.xa + (lane < 16 ? (has_wo ? hoff + (lane >> 2 & 1) * 4096 + (lane >> 1 & 1) * 256 + (lane & 1) * 16 : ooff) : has_f1 ? aoff + (lane >> 1 & 1) * 4096 + (lane & 1) * 16 : ooff)};
#pragma unroll
        for (int i = 0; i < 4; i++) st4(slot[i], SENT, SENT, SENT, SENT);
#pragma unroll
        for (int i = 0; i < 3; i++) st4(p.sc->qbuf + b * 96 + i * 32 + lane, 0, 0, 0, 0);
        uint4* mdst = p.sc->mbuf + b * 2 + (lane & 1);
        st4(mdst, 0, 0, 0, 0);
        sts32(sbase + SM_MISC, tag);
        asm volatile("bar.sync 2, 320;" ::: "memory");
        __nanosleep(3000);
        uint32_t ack = SENT;
#pragma unroll
        for (int i = 0; i < 4; i++) { uint32_t v; asm volatile("atom.relaxed.gpu.global.exch.b32 %0, [%1], -1;" : "=r"(v) : "l"(slot[i]) : "memory"); ack &= v; }
        if (__any_sync(0xffffffffu, ack != SENT)) __trap();
        if (lane == 0) st1(p.sc->ready + b, tag);
        while (!mbar_test(bar_stat, 0)) __nanosleep(200);
        const float4 ma = lds128f(sbase + SM_MAX), mb = lds128f(sbase + SM_MAX + 16);
        const float m = fmaxf(fmaxf(fmaxf(ma.x, ma.y), fmaxf(ma.z, ma.w)), fmaxf(fmaxf(mb.x, mb.y), fmaxf(mb.z, mb.w)));
        pkt_st2(mdst, m, sum8(sbase + SM_SUM), tag);
        int vote = 0;
#pragma unroll 1
        for (int r = 0; r < 9; r++) {
            __nanosleep(100);
            uint32_t d;
            asm volatile("{\n.reg .pred p, q;\n.reg .b32 a, b, c0, c1;\nmov.b32 c0, 0;\nmov.b32 c1, 0;\n"
                         "atom.relaxed.gpu.global.exch.b32 a, [%1], -1;\natom.relaxed.gpu.global.exch.b32 b, [%2], -1;\n"
                         "setp.eq.u32 p, a, -1;\n@p mov.u32 c0, %%clock;\nsetp.eq.u32 q, b, -1;\n@q mov.u32 c1, %%clock;\nsub.u32 %0, c1, c0;\n}"
                         : "=r"(d) : "l"(r & 1 ? slot[2] : slot[0]), "l"(r & 1 ? slot[0] : slot[2]) : "memory");
            vote += (d > 90) == (r & 1) ? 1 : -1;
        }
        const uint32_t side = __shfl_sync(0xffffffffu, vote, 0) > 0;
        uint32_t n = 0;
        {
            uint64_t em, el;
            while (true) {
                const uint4 e = ld4(p.sc->ready + lane * 4);
                pkt_ld2(p.sc->mbuf + (head * 4 + (lane & 3)) * 2, em, el);
                if (__all_sync(0xffffffffu, e.x == tag && e.y == tag && e.z == tag && e.w == tag && tag_ok(em, tag) && tag_ok(el, tag))) break;
                __nanosleep(500);
                if (++n > SPIN_LIMIT) __trap();
            }
            float M = fmaxf(val_of(em), __shfl_xor_sync(0xffffffffu, val_of(em), 1));
            M = fmaxf(M, __shfl_xor_sync(0xffffffffu, M, 2));
            float L = ex2((val_of(em) - M) * L2E) * val_of(el);
            L += __shfl_xor_sync(0xffffffffu, L, 1);
            L += __shfl_xor_sync(0xffffffffu, L, 2);
            if (lane == 0) {
                sts64(sbase + SM_MISC + 8, __float_as_uint(__fdividef(ex2((m - M) * L2E), L)), side);
                mbar_arrive(bar_scale);
                if (b == 0) p.sc->epoch = tag;
            }
        }
        unsigned char* hdst = p.xa + (hoff + (side ^ 1) * 4096 + (lane >> 4) * 256 + (lane & 15) * 2);
        unsigned char* hdst2 = p.xa + (hoff + side * 4096 + (lane >> 4) * 256 + (lane & 15) * 2);
        unsigned char* adst = p.xa + (aoff + (lane >> 4) * 4096 + (lane & 15) * 2);
        __nv_bfloat16* odst = p.out + u2 * 16 + (lane & 15);
        uint32_t r0 = sbase + SM_RED + lane * 48, r1 = sbase + SM_RED + (lane & 15) * 48;
        uint32_t res;
        asm volatile("ld.global.nc.u16 %0, [%1];" : "=r"(res) : "l"(p.x + u2 * 16 + (lane & 15)));
        pin(hdst); pin(hdst2); pin(adst); pin(odst); pin(r0); pin(r1);
        if (has_wo) {
            fin_sync<3>();
            const uint32_t v = pack_bf(0.f, sum8(r0));
            st16(hdst, v); st16(hdst2, v);
            STAMP(4);
        }
        if (has_f1) {
            fin_sync<4>();
            float mean_b, inv_den;
            ln_finish(sum8(sbase + SM_LN), sum8(sbase + SM_LN + 32), mean_b, inv_den);
            const float gr = fmaf(-mean_b, sum8(r1 + 48 * 48), sum8(r1 + 32 * 48)) * inv_den;
            mbar_wait_after(bar_up, r0, gr);
            const float gs = bfr(gr);
            const float up = bfr(fmaf(-mean_b, sum8(r1 + 80 * 48), sum8(r1 + 64 * 48)) * inv_den);
            st16(adst, pack_bf(0.f, silu_b(gs) * up));
            STAMP(8);
        }
        if (has_f2) {
            mbar_wait(bar_tail + 8 * (NWP + NF1 + 1), 0);
            const unsigned char* hsrc = p.xa + ((lane >> 4) * (1 << 14) + side * 4096 + (u2 & 7) * 256 + (u2 >> 3) * 32 + (lane & 15) * 2);
            uint32_t e[3];
            do {
#pragma unroll
                for (int i = 0; i < 3; i++) asm volatile("ld.relaxed.gpu.global.u16 %0, [%1];" : "=r"(e[i]) : "l"(hsrc + xa_h(2 * i)) : "memory");
                if (++n > SPIN_LIMIT) __trap();
            } while (__any_sync(0xffffffffu, max(max(e[0], e[1]), e[2]) == 0xffffu));
            float f[3];
#pragma unroll
            for (int i = 0; i < 3; i++) f[i] = bf_lo(e[i]) + bf_lo(__shfl_xor_sync(0xffffffffu, e[i], 16));
            res = add_bf2(res, pack_bf(0.f, (f[0] + f[1]) + f[2]));
            pin(res);
            fin_sync<6>();
            asm volatile("st.global.u16 [%0], %1;" ::"l"(odst), "h"((unsigned short)add_bf2(res, pack_bf(0.f, sum8(r1 + 96 * 48)))) : "memory");
            STAMP(11);
        }
    } else {
        const int g = lane >> 2, t = lane & 3;
        uint2 xres;
        {
            uint32_t xr;
            uint2 xu[5];
            const char* xb = reinterpret_cast<const char*>(p.x);
            asm volatile("ld.global.nc.u16 %0, [%1];" : "=r"(xr) : "l"(xb + (sp * 160 + min(tid, 159)) * 2));
#pragma unroll
            for (int i = 0; i < 5; i++) asm volatile("ld.global.nc.v2.u32 {%0, %1}, [%2];" : "=r"(xu[i].x), "=r"(xu[i].y) : "l"(xb + i * 256 + lane * 8));
            asm volatile("ld.global.nc.v2.u32 {%0, %1}, [%2];" : "=r"(xres.x), "=r"(xres.y) : "l"(xb + min(g, 4) * 256 + warp * 32 + t * 8));
            if (lane >= 20) xres.x = xres.y = 0;
            float s1 = 0.f, s2 = 0.f, mean_b, inv_den;
#pragma unroll
            for (int i = 0; i < 5; i++) { ln_acc(xu[i].x, s1, s2); ln_acc(xu[i].y, s1, s2); }
            ln_finish(warp_sum(s1), warp_sum(s2), mean_b, inv_den);
            sts16(sbase + SM_P + warp * 64 + ((lane >> 1 & 3) * 8 + (lane >> 3) * 2 + (lane & 1)) * 2, ln_apply2(xr, mean_b, inv_den));
            asm volatile("cp.async.wait_all;" ::: "memory");
            asm volatile("bar.sync 2, 320;" ::: "memory");
        }
        STAMP(0);
        uint32_t va[3];
#pragma unroll
        for (int i = 0; i < 3; i++) {
            const int cc = 3 * warp + i, row = 3 * lane + (cc >> 3);
            va[i] = sbase + row * 128 + (((cc ^ row) & 7) << 4);
        }
        const int gi = g >= 3 ? g - 3 : g;
        unsigned char* odst = p.xa + ((xa_o(head) ^ (g >= 3 ? 4096 : 0)) + sp * (DH * 4) + (warp * 24 + gi * 8 + t * 2) * 4);
        pin(odst);

#pragma unroll 1
        for (int ph = 0; ph < 2; ph++) {
            if (ph == 1) {
                uint4 qf[6];
#pragma unroll
                for (int i = 0; i < 6; i++) qf[i] = lds128(sbase + SM_Q + t * 96 + i * 16);
                uint32_t ka[3];
#pragma unroll
                for (int j = 0; j < 3; j++) {
                    const int row = 3 * (lane & 15) + j;
                    ka[j] = sbase + row * 128 + ((((lane >> 4) ^ row) & 7) << 4) + warp * TILE_BYTES;
                }
                float s[4] = {0.f, 0.f, 0.f, 0.f};
#pragma unroll 1
                for (int it = 0; it < 4; it++) {
                    const int slot = (it & 1) * 8 + warp;
                    const uint32_t so = (it & 1) * 8 * TILE_BYTES;
                    float c[2][2][4];
                    zero4(c[0][0]); zero4(c[0][1]); zero4(c[1][0]); zero4(c[1][1]);
                    mbar_wait(bar_full + 8 * slot, it >> 1);
#pragma unroll
                    for (int ks = 0; ks < 12; ks++) {
                        const uint32_t a = (ka[ks >> 2] + so) ^ ((ks & 3) << 5);
                        uint32_t f0[4], f1[4];
                        ldsm_x4(f0, a); ldsm_x4(f1, a + 16 * DH * 2);
                        const uint32_t b0 = ks & 1 ? qf[ks >> 1].z : qf[ks >> 1].x, b1 = ks & 1 ? qf[ks >> 1].w : qf[ks >> 1].y;
                        mma_bf16(c[0][ks & 1], f0, b0, b1); mma_bf16(c[1][ks & 1], f1, b0, b1);
                    }
                    if (lane == 0) mbar_arrive8(bar_empty + 8 * slot);
                    const float v = t & 2 ? (t & 1 ? c[1][0][2] + c[1][1][2] : c[1][0][0] + c[1][1][0]) : (t & 1 ? c[0][0][2] + c[0][1][2] : c[0][0][0] + c[0][1][0]);
                    s[0] = s[1]; s[1] = s[2]; s[2] = s[3];
                    s[3] = bfr(bfr(v) * 0.07216878364870322f);
                }
                const float mw = warp_max(fmaxf(fmaxf(s[0], s[1]), fmaxf(s[2], s[3])));
                if (lane == 0) sts32(sbase + SM_MAX + warp * 4, mw);
                cons_sync();
                const float4 ma = lds128f(sbase + SM_MAX), mb = lds128f(sbase + SM_MAX + 16);
                const float m = fmaxf(fmaxf(fmaxf(ma.x, ma.y), fmaxf(ma.z, ma.w)), fmaxf(fmaxf(mb.x, mb.y), fmaxf(mb.z, mb.w)));
                float l = 0.f;
#pragma unroll
                for (int it = 0; it < 4; it++) {
                    const float e = ex2((s[it] - m) * L2E);
                    l += e;
                    sts16(sbase + SM_P + (it * 8 + warp) * 64 + ((g >> 1) * 8 + t * 2 + (g & 1)) * 2, pack_bf(0.f, e));
                }
                l = warp_sum(l);
                if (lane == 0) { sts32(sbase + SM_SUM + warp * 4, l); mbar_arrive(bar_stat); }
                cons_sync();
                STAMP(1);
            }
            float acc[2][3][4];
#pragma unroll
            for (int i = 0; i < 3; i++) { zero4(acc[0][i]); zero4(acc[1][i]); }
            const int nt = ph ? NKT : NQT;
            float scale = 1.f;
#pragma unroll 1
            for (int n = 0; n < nt; n++) {
                const int slot = ph ? (n & (NSLOT - 1)) : QSLOT + n;
                const uint4 w = lds128(sbase + SM_P + n * 64 + t * 16);
                if (n == NKT - 1) { mbar_wait(bar_scale, 0); scale = __uint_as_float(lds32(sbase + SM_MISC + 8)); }
                if (ph) mbar_wait(bar_full + 8 * slot, (n >> 4) & 1);
                uint32_t f[3][4];
#pragma unroll
                for (int i = 0; i < 3; i++) ldsm_x4_t(f[i], va[i] + slot * TILE_BYTES);
#pragma unroll
                for (int i = 0; i < 3; i++) {
                    mma_bf16(acc[0][i], w.x, w.x, w.y, w.y, f[i][0], f[i][1]);
                    mma_bf16(acc[1][i], w.z, w.z, w.w, w.w, f[i][2], f[i][3]);
                }
                if (lane == 0) mbar_arrive(bar_empty + 8 * slot);
            }
            const float v0 = (gi == 0 ? acc[0][0][0] + acc[1][0][0] : gi == 1 ? acc[0][1][0] + acc[1][1][0] : acc[0][2][0] + acc[1][2][0]) * scale;
            const float v1 = (gi == 0 ? acc[0][0][1] + acc[1][0][1] : gi == 1 ? acc[0][1][1] + acc[1][1][1] : acc[0][2][1] + acc[1][2][1]) * scale;
            if (ph == 1) {
                if (g < 6) st2(odst, in_word(v0), in_word(v1));
                break;
            }
            const uint32_t tag = lds32(sbase + SM_MISC);
            if (g < 3) pkt_st2(p.sc->qbuf + b * 96 + warp * 12 + lane, v0, v1, tag);
            if (warp < 3) {
                const uint4* src = p.sc->qbuf + head * 4 * 96 + tid;
                uint64_t e[4][2];
                uint32_t n = 0;
                bool ok;
#pragma unroll 1
                do {
                    __nanosleep(p.t_q);
                    ok = true;
#pragma unroll
                    for (int i = 0; i < 4; i++) { pkt_ld2(src + i * 96, e[i][0], e[i][1]); }
#pragma unroll
                    for (int i = 0; i < 4; i++) ok = ok && tag_ok(e[i][0], tag) && tag_ok(e[i][1], tag);
                    if (++n > SPIN_LIMIT) __trap();
                } while (!__all_sync(0xffffffffu, ok));
                sts32(sbase + SM_Q + (t * 24 + (tid >> 2)) * 4,
                      pack_bf((val_of(e[0][1]) + val_of(e[1][1])) + (val_of(e[2][1]) + val_of(e[3][1])), (val_of(e[0][0]) + val_of(e[1][0])) + (val_of(e[2][0]) + val_of(e[3][0]))));
            }
            cons_sync();
        }
        STAMP(2);
        const uint32_t side = lds32(sbase + SM_MISC + 12) * 4096;
        const uint32_t d16 = kg * 64 + g * 8 + warp, oh = d16 / 12;
        const unsigned char* osrc = p.xa + ((xa_o(oh) ^ side) + (d16 - oh * 12) * 64 + t * 16);
        const int r16 = (lane & 7) + ((lane >> 4) << 3), mi = lane >> 3 & 1;
        const uint32_t f32 = sbase + r16 * 32 + ((mi ^ (lane >> 2 & 1)) << 4);
        uint32_t rdst = sbase + SM_RED + (t * 8 + g) * 48 + warp * 4;
        uint32_t bl = sbase + SM_BC + warp * 512 + t * 80, bs = bl + g * 8;
        uint32_t hl = g < 4 ? bl : sbase + SM_ONE;
        uint32_t w1a = f32 + SM_W1 + warp * 512, w2a = f32 + SM_W2 + warp * 1024;
        uint32_t lnd = lane < 2 ? sbase + SM_LN + lane * 32 + warp * 4 : sbase + SM_BC + warp * 512 + 384 + lane * 4;
        const unsigned char* hs = p.xa + (side + warp * 256 + lane * 8);
        const unsigned char* as = p.xa + (XA_A + side + warp * 384 + min(lane, 23) * 16);
        uint32_t al = sbase + SM_BC + warp * 512 + t * 16, at = sbase + SM_BC + warp * 512 + lane * 16;
        uint32_t fl = role, ln = lane;
        pin_u(fl); pin(ln);
        const bool f1 = fl & 2, f2 = fl & 4, odd = ln & 1, first = ln == 0;
        constexpr uint32_t b2 = bar_tail + 8 * (NWP + NF1);
        pin(rdst); pin(bs); pin(hl); pin(w1a); pin(w2a); pin(lnd); pin(hs); pin(as); pin(al); pin(at);
#define F_(i, c) __uint_as_float(e[i].c)
        if (has_wo) {
            uint4 e[4];
#pragma unroll
            for (int i = 0; i < 4; i++) e[i].x = e[i].y = e[i].z = e[i].w = SENT;
            uint32_t n = 0;
            mbar_wait(bar_tail + 8, 0);
#pragma unroll 1
            do {
                if (n) __nanosleep(100);
#pragma unroll
                for (int i = 0; i < 4; i++) poll4(osrc + i * (DH * 4), e[i]);
                if (++n > SPIN_LIMIT) __trap();
            } while (__any_sync(0xffffffffu, max(max(max4(e[0]), max4(e[1])), max(max4(e[2]), max4(e[3]))) == SENT));
            sts64(bs, pack_bf((F_(0, y) + F_(1, y)) + (F_(2, y) + F_(3, y)), (F_(0, x) + F_(1, x)) + (F_(2, x) + F_(3, x))),
                      pack_bf((F_(0, w) + F_(1, w)) + (F_(2, w) + F_(3, w)), (F_(0, z) + F_(1, z)) + (F_(2, z) + F_(3, z))));
            __syncwarp();
#pragma unroll
            for (int i = 0; i < 4; i++) e[i] = lds128(bl + i * 16);
            STAMP(3);
            const uint32_t wa = sbase + (warp * 16 + r16) * 64 + ((mi ^ (r16 >> 1 & 3)) << 4), wb = wa ^ 32;
            float c0[4], c1[4];
            zero4(c0); zero4(c1);
#pragma unroll
            for (int j = 0; j < NWP; j++) {
                mbar_wait(bar_tail + 8 * j, 0);
                uint32_t f0[4], f1[4];
                ldsm_x4_t(f0, wa + j * 8192); ldsm_x4_t(f1, wb + j * 8192);
                const uint32_t b0 = j & 1 ? e[j >> 1].z : e[j >> 1].x, b1 = j & 1 ? e[j >> 1].w : e[j >> 1].y;
                mma_bf16(c0, f0, b0, b1); mma_bf16(c1, f1, b0, b1);
            }
            sts32(rdst, t & 2 ? (t & 1 ? c1[2] : c1[0]) : (t & 1 ? c0[2] : c0[0]));
            fin_arrive<3>();
        }
        if (f1) {
            constexpr uint32_t b1 = bar_tail + 8 * NWP;
            uint32_t a1[5][4], a3[5][4];
            uint2 e[NG];
#pragma unroll
            for (int i = 0; i < NG; i++) e[i].x = e[i].y = 0;
            uint32_t got = 0, n = 0;
#pragma unroll
            for (int i = 0; i < NB; i++) a3[i][0] = a3[i][1] = a3[i][2] = a3[i][3] = 0;
            mbar_wait(b1, 0);
#pragma unroll
            for (int i = 0; i < NG; i++) ld2p(hs + xa_h(i), e[i], lane < 20);
            mbar_wait(b1 + 8, 0);
#pragma unroll
            for (int i = 0; i < 5; i++) ldsm_x4_t(a1[i], w1a + i * 4096);
            uint4 hb0, hb1;
            uint2 hb2;
            float sv[4];
#pragma unroll 1
            while (true) {
#define S_(f, c) (((f(e[0].c) + f(e[1].c)) + (f(e[2].c) + f(e[3].c))) + (f(e[4].c) + f(e[5].c)))
                const float sx = S_(bf_lo, x), sy = S_(bf_hi, x), sz = S_(bf_lo, y), sw = S_(bf_hi, y), sa = (sx + sy) + (sz + sw);
#undef S_
                const uint32_t h0 = add_bf2(xres.x, pack_bf(sy, sx)), h1 = add_bf2(xres.y, pack_bf(sw, sz));
                sts64(bs, h0, h1);
                __syncwarp();
                hb0 = lds128(hl); hb1 = lds128(hl + 16); hb2 = lds64(hl + 32);
                const float a = bf_lo(h0), b = bf_hi(h0), c = bf_lo(h1), d = bf_hi(h1);
                const float s1 = (a + b) + (c + d), s2 = fmaf(a, a, b * b) + fmaf(c, c, d * d);
                sv[0] = odd ? s2 : s1;
                sv[1] = __shfl_xor_sync(0xffffffffu, odd ? s1 : s2, 1);
                sv[2] = __shfl_xor_sync(0xffffffffu, sv[0], 2);
                sv[3] = __shfl_xor_sync(0xffffffffu, odd ? s1 : s2, 3);
                bool miss = __any_sync(0xffffffffu, sa != sa);
                if (n == 0) STAMP(12);
                if (miss) {
                    const uint4 mx = make_uint4(__vimax3_u16x2(e[0].x, e[0].y, e[1].x), __vimax3_u16x2(e[1].y, e[2].x, e[2].y),
                                                __vimax3_u16x2(e[3].x, e[3].y, e[4].x), __vimax3_u16x2(e[4].y, e[5].x, e[5].y));
#pragma unroll
                    for (int i = 0; i < NG; i++) poll2(hs + xa_h(i), e[i]);
                    ldsm_if<NB, 4096>(a3[0], a3[1], a3[2], w1a + (SM_W3 - SM_W1), b1 + 16, got);
                    if (++n > SPIN_LIMIT) __trap();
                    miss = __any_sync(0xffffffffu, !ok8(mx));
                }
                if (!miss) break;
            }
            STAMP(5);
            float cg[3][4], cu[3][4];
#pragma unroll
            for (int i = 0; i < 3; i++) { zero4(cg[i]); zero4(cu[i]); }
            const uint32_t hb[5][2] = {{hb0.x, hb0.y}, {hb0.z, hb0.w}, {hb1.x, hb1.y}, {hb1.z, hb1.w}, {hb2.x, hb2.y}};
            const float st = (sv[0] + sv[1]) + (sv[2] + sv[3]);
#pragma unroll
            for (int i = 0; i < 4; i++) sv[i] = __shfl_down_sync(0xffffffffu, st, 4 * i + 4);
#pragma unroll
            for (int i = 0; i < 5; i++) mma_bf16(cg[i % 3], a1[i], hb[i][0], hb[i][1]);
            sts32(lnd, ((st + sv[0]) + sv[1]) + (sv[2] + sv[3]));
            sts32(rdst + 32 * 48, odd ? (cg[0][2] + cg[2][2]) + cg[1][2] : (cg[0][0] + cg[2][0]) + cg[1][0]);
            fin_arrive<4>();
            STAMP(6);
            if (__any_sync(0xffffffffu, !got)) {
                mbar_wait(b1 + 16, 0);
#pragma unroll
                for (int i = 0; i < NB; i++) ldsm_x4_t(a3[i], w1a + (SM_W3 - SM_W1) + i * 4096);
            }
            mbar_wait(b1 + 24, 0);
#pragma unroll
            for (int i = NB; i < 5; i++) ldsm_x4_t(a3[i], w1a + (SM_W3 - SM_W1) + i * 4096);
#pragma unroll
            for (int i = 0; i < 5; i++) mma_bf16(cu[i % 3], a3[i], hb[i][0], hb[i][1]);
            sts32(rdst + 64 * 48, odd ? (cu[0][2] + cu[2][2]) + cu[1][2] : (cu[0][0] + cu[2][0]) + cu[1][0]);
            __syncwarp();
            if (first) mbar_arrive(bar_up);
        }
        if (f2) {
            uint32_t a2[NF2][2][4];
#pragma unroll
            for (int i = 0; i < 4; i++) a2[NF2 - 1][0][i] = a2[NF2 - 1][1][i] = 0;
#pragma unroll
            for (int j = 0; j < NF2 - 1; j++) {
                mbar_wait(b2 + 8 * j, 0);
                ldsm_x4_t(a2[j][0], w2a + j * 8192); ldsm_x4_t(a2[j][1], w2a + j * 8192 + 512);
            }
            STAMP(9);
            uint32_t n = 0, got = 0;
            uint4 e[NF2];
#pragma unroll 1
            while (true) {
                const uint4 pa = ld4(as);
                ldsm_if<2, 512>(a2[NF2 - 1][0], a2[NF2 - 1][1], nullptr, w2a + (NF2 - 1) * 8192, b2 + 8 * (NF2 - 1), got);
                if (++n > SPIN_LIMIT) __trap();
                sts128(at, pa);
                __syncwarp();
#pragma unroll
                for (int j = 0; j < CFG_NSPEC; j++) e[j] = lds128v(al + j * 64);
                if (__all_sync(0xffffffffu, ok8(pa))) break;
            }
#pragma unroll
            for (int j = CFG_NSPEC; j < NF2; j++) e[j] = lds128v(al + j * 64);
            STAMP(10);
            float c[4][4];
            zero4(c[0]); zero4(c[1]); zero4(c[2]); zero4(c[3]);
#pragma unroll
            for (int j = 0; j < NF2; j++) { mma_bf16(c[(j & 1) * 2], a2[j][0], e[j].x, e[j].y); mma_bf16(c[(j & 1) * 2 + 1], a2[j][1], e[j].z, e[j].w); }
            if (__any_sync(0xffffffffu, !got)) {
                constexpr int j = NF2 - 1;
                mbar_wait(b2 + 8 * j, 0);
                ldsm_x4_t(a2[j][0], w2a + j * 8192); ldsm_x4_t(a2[j][1], w2a + j * 8192 + 512);
                mma_bf16(c[0], a2[j][0], e[j].x, e[j].y); mma_bf16(c[1], a2[j][1], e[j].z, e[j].w);
            }
            sts32(rdst + 96 * 48, odd ? (c[0][2] + c[1][2]) + (c[2][2] + c[3][2]) : (c[0][0] + c[1][0]) + (c[2][0] + c[3][0]));
            fin_arrive<6>();
        }
#undef F_
    }
}

typedef CUresult (*EncodeTiledFn)(CUtensorMap*, CUtensorMapDataType, cuuint32_t, void*, const cuuint64_t*, const cuuint64_t*,
                                  const cuuint32_t*, const cuuint32_t*, CUtensorMapInterleave, CUtensorMapSwizzle,
                                  CUtensorMapL2promotion, CUtensorMapFloatOOBfill);

void make_map(EncodeTiledFn fn, CUtensorMap* tm, const void* w, const int (&d)[5], const int (&st)[4], const int (&bx)[5],
              CUtensorMapSwizzle sw, int promo) {
    cuuint64_t dims[5], strides[4];
    cuuint32_t box[5], estr[5];
    for (int i = 0; i < 5; i++) { dims[i] = (cuuint64_t)d[i]; box[i] = (cuuint32_t)bx[i]; estr[i] = 1; }
    for (int i = 0; i < 4; i++) strides[i] = (cuuint64_t)st[i];
    fn(tm, CU_TENSOR_MAP_DATA_TYPE_BFLOAT16, 5, const_cast<void*>(w), dims, strides, box, estr, CU_TENSOR_MAP_INTERLEAVE_NONE, sw,
       (CUtensorMapL2promotion)promo, CU_TENSOR_MAP_FLOAT_OOB_FILL_NONE);
}

enum { T_PER, T_LEAD, T_STAG, T_TD, T_PERO, T_F1D, T_PERF, T_F2, T_PER2, T_Q, T_PWO, T_PW13, T_PW2, T_TG, T_N };
#define TUNE_NAMES {"per", "lead", "stag", "td", "pero", "f1d", "perf", "f2", "per2", "q", "pwo", "pw13", "pw2", "tg"}
int g_tune[T_N] = {478, 1200, 120, 120, 299, 100, 120, 1300, 130, 1600, 1, 2, 2, 1720};

}

extern "C" void kernel_launch(void* const* d_in, const int* in_sizes, int n_in, void* d_out, int out_size) {
    (void)in_sizes; (void)n_in; (void)out_size;
    static EncodeTiledFn encode = nullptr;
    static Scratch* scratch = nullptr;
    static unsigned char* xarea = nullptr;
    if (!encode) {
        void* sp = nullptr;
        cudaGetSymbolAddress(&sp, g_scratch);
        scratch = reinterpret_cast<Scratch*>(sp);
        cudaGetSymbolAddress(&sp, g_xarea);
        xarea = reinterpret_cast<unsigned char*>((reinterpret_cast<uintptr_t>(sp) + XA_ALIGN - 1) / XA_ALIGN * XA_ALIGN);
        void* fn = nullptr;
        cudaDriverEntryPointQueryResult st;
        cudaGetDriverEntryPoint("cuTensorMapEncodeTiled", &fn, cudaEnableDefault, &st);
        encode = reinterpret_cast<EncodeTiledFn>(fn);
        cudaFuncSetAttribute(fused_decode_kernel, cudaFuncAttributeMaxDynamicSharedMemorySize, SM_TOTAL);
    }
    const int* T = g_tune;
    KParams p;
    p.x = (const __nv_bfloat16*)d_in[0];
    p.wq = (const __nv_bfloat16*)d_in[3];
    p.out = (__nv_bfloat16*)d_out;
    p.sc = scratch;
    p.xa = xarea;
    p.per = T[T_PER];
    p.stag = T[T_STAG];
    p.t_k0 = (NQT + 1) * T[T_PER] - T[T_LEAD];
    {
        int t = p.t_k0 + 2 * NKT * T[T_PER] + T[T_STAG] * 3 / 2 + T[T_TD];
        for (int i = 0; i < NWP; i++, t += T[T_PERO]) p.item[i] = t;
        for (int i = 0, t1 = t + T[T_F1D]; i < NP1; i++, t1 += T[T_PERF]) p.item[NWP + i] = t1;
        for (int i = 0, t2 = t + T[T_F2]; i < NF2; i++, t2 += T[T_PER2]) p.item[NWP + NP1 + i] = t2;
        for (int i = NITEM; i < 32; i++) p.item[i] = 0;
    }
    p.target = T[T_TG]; p.t_q = T[T_Q];
    for (int i = 0, nw = 0, n1 = 0, n2 = 0; i < NCTA; i++) {
        const int grp = i >> 2;
        const bool f2 = grp % 3 == 2, both = grp == 8 || grp == 23, wo = !both, f1 = !f2 || both;
        p.role[i] = (wo ? 1 | nw / 20 << 3 | nw % 20 << 6 : 0) | (f1 ? 2 | n1 << 11 : 0) | (f2 ? 4 | n2 << 18 : 0);
        nw += wo; n1 += f1; n2 += f2;
    }
    TMaps tm;
    constexpr int R1 = FF * 2, R2 = D_MODEL * 2;
    for (int i = 0; i < 2; i++)
        make_map(encode, &tm.k + i, d_in[1 + i], {64, 96, 1, 1, NHEAD * SK / 32}, {128, TILE_BYTES, TILE_BYTES, TILE_BYTES}, {64, 96, 1, 1, 1}, CU_TENSOR_MAP_SWIZZLE_128B, 2);
    make_map(encode, &tm.wo, d_in[4], {D_MODEL, 2, 4, 2, NHEAD * DH / 16}, {R2, 4 * R2, 2 * R2, 16 * R2}, {32, 2, 4, 2, 8}, CU_TENSOR_MAP_SWIZZLE_64B, T[T_PWO]);
    make_map(encode, &tm.w1, d_in[6], {FF, 2, 4, 2, D_MODEL / 16}, {R1, 4 * R1, 2 * R1, 16 * R1}, {16, 2, 4, 2, 8}, CU_TENSOR_MAP_SWIZZLE_32B, T[T_PW13]);
    make_map(encode, &tm.w3, d_in[7], {FF, 2, 4, 2, D_MODEL / 16}, {R1, 4 * R1, 2 * R1, 16 * R1}, {16, 2, 4, 2, 8}, CU_TENSOR_MAP_SWIZZLE_32B, T[T_PW13]);
    make_map(encode, &tm.w2, d_in[8], {D_MODEL, 2, 4, 4, FF / 32}, {R2, 8 * R2, 2 * R2, 32 * R2}, {16, 2, 4, 4, 8}, CU_TENSOR_MAP_SWIZZLE_32B, T[T_PW2]);
    fused_decode_kernel<<<NCTA, NTHREADS, SM_TOTAL, cudaStreamPerThread>>>(p, tm);
}
```

```cpp
#include <cuda_runtime.h>
#include <cuda_bf16.h>
#include <cuda.h>
#include <stdint.h>

namespace {

constexpr int D_MODEL = 640;
constexpr int NHEAD = 32;
constexpr int DH = 192;
constexpr int SK = 32768;
constexpr int WIN = 4096;
constexpr int FF = 1536;

constexpr int NCTA = 128;
constexpr int NTHREADS = 256 + 64;
constexpr int TILE_BYTES = 32 * DH * 2;
constexpr int NSLOT = 16;
constexpr int NKT = 32;
constexpr int NQT = 5;
constexpr int QSLOT = NSLOT - NQT;
constexpr int NG = 6;
constexpr int NWP = 8, NP1 = 10, NF2 = 6;
constexpr int NITEM = NWP + NP1 + NF2;
#define CFG_NSPEC 3
#define CFG_NA 2
#define CFG_NB 2
constexpr int NF1 = 4, NA = CFG_NA, NB = CFG_NB;
constexpr int NTAIL = NWP + NF1 + NF2;

#define CFG_INFL 5
#define CFG_OG 0
#define CFG_HG 3
#define CFG_OSL 100
constexpr int INFLIGHT = CFG_INFL;

constexpr uint32_t sbase = 1024;
constexpr int SM_W1 = NWP * 8192, SM_W3 = SM_W1 + 20480, SM_W2 = SM_W3 + 20480;
constexpr int SM_P = NSLOT * TILE_BYTES;
constexpr int SM_Q = SM_P + 2048;
constexpr int SM_RED = SM_Q + 384;
constexpr int SM_BC = SM_RED + 128 * 48;
constexpr int SM_ONE = SM_BC + 4096;
constexpr int SM_MAX = SM_ONE + 64;
constexpr int SM_SUM = SM_MAX + 32;
constexpr int SM_LN = SM_SUM + 32;
constexpr int SM_MISC = SM_LN + 64;
constexpr int SM_LATE = SM_MISC + 32;
constexpr int SM_BAR = SM_LATE + 32;
constexpr int SM_TOTAL = SM_BAR + 512;
static_assert(SM_TOTAL <= 232448, "shared memory");

struct __align__(128) Scratch {
    uint2 qbuf[NCTA * 96];
    uint4 mbuf[NCTA * 2];
    uint32_t ready[NCTA];
    uint32_t late[32];
    uint32_t epoch;
};
__device__ Scratch g_scratch;
constexpr int XA_ALIGN = 1 << 20;
constexpr uint32_t SENT = 0xffffffffu;
__device__ unsigned char g_xarea[2 * XA_ALIGN];
__host__ __device__ constexpr uint32_t xa_o(uint32_t h) { return (2 * h + ((h ^ (h >> 3) ^ (h >> 4)) & 1)) * 4096; }
__host__ __device__ constexpr uint32_t xa_h(uint32_t i) { return (1 << 18) + (i >> 2) * (3 << 16) + (i & 3) * (1 << 14); }
constexpr uint32_t XA_A = xa_h(NG);

constexpr uint32_t SPIN_LIMIT = 1u << 22;

__device__ __forceinline__ uint32_t smem_u32(const void* p) { return (uint32_t)__cvta_generic_to_shared(p); }
__device__ __forceinline__ uint32_t now_ns() { uint64_t t; asm volatile("mov.u64 %0, %globaltimer;" : "=l"(t)); return (uint32_t)t; }
__device__ __forceinline__ void mbar_init(uint32_t bar, uint32_t cnt) {
    asm volatile("mbarrier.init.shared::cta.b64 [%0], %1;" ::"r"(bar), "r"(cnt) : "memory");
}
__device__ __forceinline__ void mbar_expect_tx(uint32_t bar, uint32_t bytes) {
    asm volatile("mbarrier.arrive.expect_tx.shared::cta.b64 _, [%0], %1;" ::"r"(bar), "r"(bytes) : "memory");
}
__device__ __forceinline__ void mbar_arrive(uint32_t bar) {
    asm volatile("mbarrier.arrive.shared::cta.b64 _, [%0];" ::"r"(bar) : "memory");
}
__device__ __forceinline__ void mbar_arrive8(uint32_t bar) {
    asm volatile("mbarrier.arrive.shared::cta.b64 _, [%0], 8;" ::"r"(bar) : "memory");
}
__device__ __forceinline__ bool mbar_test(uint32_t bar, uint32_t parity) {
    uint32_t ok;
    asm volatile("{\n.reg .pred p;\nmbarrier.test_wait.parity.shared::cta.b64 p, [%1], %2;\nselp.u32 %0, 1, 0, p;\n}"
                 : "=r"(ok) : "r"(bar), "r"(parity) : "memory");
    return ok;
}
__device__ __forceinline__ void mbar_wait(uint32_t bar, uint32_t parity) {
    asm volatile("{\n.reg .pred p;\nW_%=:\nmbarrier.try_wait.parity.shared::cta.b64 p, [%0], %1;\n@!p bra.uni W_%=;\n}" ::"r"(bar), "r"(parity) : "memory");
}
__device__ __forceinline__ void mbar_wait_after(uint32_t bar, uint32_t dump, float v) {
    uint32_t ok;
    asm volatile("{\n.reg .pred p;\nmbarrier.try_wait.parity.shared::cta.b64 p, [%1], 0;\nselp.u32 %0, 1, 0, p;\n}" : "=r"(ok) : "r"(bar) : "memory");
    asm volatile("st.volatile.shared.f32 [%0], %1;" ::"r"(dump), "f"(v) : "memory");
    if (__builtin_expect(!ok, 0)) mbar_wait(bar, 0);
}
__device__ __forceinline__ void tma_load(uint32_t dst, const CUtensorMap* tm, int c0, int c4, uint32_t bar, uint64_t pol) {
    asm volatile("cp.async.bulk.tensor.5d.shared::cluster.global.mbarrier::complete_tx::bytes.L2::cache_hint [%0], [%1, {%3, %5, %5, %5, %4}], [%2], %6;"
                 ::"r"(dst), "l"(reinterpret_cast<uint64_t>(tm)), "r"(bar), "r"(c0), "r"(c4), "r"(0), "l"(pol) : "memory");
}
__device__ __forceinline__ void pin(uint32_t& v) { asm volatile("shfl.sync.bfly.b32 %0, %0, 0, 31, -1;" : "+r"(v) :: "memory"); }
__device__ __forceinline__ void pin_u(uint32_t& v) { asm volatile("shfl.sync.idx.b32 %0, %0, 0, 31, -1;" : "+r"(v) :: "memory"); }
template <class T> __device__ __forceinline__ void pin(T*& v) {
    asm volatile("{\n.reg .b32 a, b;\nmov.b64 {a, b}, %0;\nshfl.sync.bfly.b32 a, a, 0, 31, -1;\nshfl.sync.bfly.b32 b, b, 0, 31, -1;\nmov.b64 %0, {a, b};\n}" : "+l"(v) :: "memory");
}
__device__ __forceinline__ void sts16(uint32_t a, uint32_t v) { asm volatile("st.shared.u16 [%0], %1;" ::"r"(a), "h"((unsigned short)v) : "memory"); }
__device__ __forceinline__ void sts32(uint32_t a, float v) { asm volatile("st.shared.f32 [%0], %1;" ::"r"(a), "f"(v) : "memory"); }
__device__ __forceinline__ void sts32(uint32_t a, uint32_t v) { asm volatile("st.shared.u32 [%0], %1;" ::"r"(a), "r"(v) : "memory"); }
__device__ __forceinline__ void sts64(uint32_t a, uint32_t x, uint32_t y) { asm volatile("st.shared.v2.u32 [%0], {%1, %2};" ::"r"(a), "r"(x), "r"(y) : "memory"); }
__device__ __forceinline__ void sts128(uint32_t a, const uint4& v) { asm volatile("st.shared.v4.u32 [%0], {%1, %2, %3, %4};" ::"r"(a), "r"(v.x), "r"(v.y), "r"(v.z), "r"(v.w) : "memory"); }
__device__ __forceinline__ void cons_sync() { asm volatile("bar.sync 1, 256;" ::: "memory"); }
template <int ID> __device__ __forceinline__ void fin_arrive() { asm volatile("bar.arrive %0, 288;" ::"n"(ID) : "memory"); }
template <int ID> __device__ __forceinline__ void fin_sync() { asm volatile("bar.sync %0, 288;" ::"n"(ID) : "memory"); }

__device__ __forceinline__ uint4 lds128(uint32_t a) {
    uint4 v;
    asm volatile("ld.shared.v4.u32 {%0,%1,%2,%3}, [%4];" : "=r"(v.x), "=r"(v.y), "=r"(v.z), "=r"(v.w) : "r"(a) : "memory");
    return v;
}
__device__ __forceinline__ uint4 lds128v(uint32_t a) {
    uint4 v;
    asm volatile("ld.volatile.shared.v4.u32 {%0,%1,%2,%3}, [%4];" : "=r"(v.x), "=r"(v.y), "=r"(v.z), "=r"(v.w) : "r"(a) : "memory");
    return v;
}
__device__ __forceinline__ float4 lds128f(uint32_t a) {
    float4 v;
    asm volatile("ld.shared.v4.f32 {%0,%1,%2,%3}, [%4];" : "=f"(v.x), "=f"(v.y), "=f"(v.z), "=f"(v.w) : "r"(a) : "memory");
    return v;
}
__device__ __forceinline__ uint2 lds64(uint32_t a) {
    uint2 v;
    asm volatile("ld.shared.v2.u32 {%0,%1}, [%2];" : "=r"(v.x), "=r"(v.y) : "r"(a) : "memory");
    return v;
}
__device__ __forceinline__ uint32_t lds32(uint32_t a) {
    uint32_t v;
    asm volatile("ld.shared.u32 %0, [%1];" : "=r"(v) : "r"(a) : "memory");
    return v;
}
__device__ __forceinline__ float sum8(uint32_t a) {
    const float4 x = lds128f(a), y = lds128f(a + 16);
    return ((x.x + x.y) + (x.z + x.w)) + ((y.x + y.y) + (y.z + y.w));
}
__device__ __forceinline__ void ldsm_x4(uint32_t* r, uint32_t a) {
    asm volatile("ldmatrix.sync.aligned.m8n8.x4.shared.b16 {%0,%1,%2,%3}, [%4];"
                 : "=r"(r[0]), "=r"(r[1]), "=r"(r[2]), "=r"(r[3]) : "r"(a) : "memory");
}
__device__ __forceinline__ void ldsm_x4_t(uint32_t* r, uint32_t a) {
    asm volatile("ldmatrix.sync.aligned.m8n8.x4.trans.shared.b16 {%0,%1,%2,%3}, [%4];"
                 : "=r"(r[0]), "=r"(r[1]), "=r"(r[2]), "=r"(r[3]) : "r"(a) : "memory");
}
template <int N, int STRIDE>
__device__ __forceinline__ void ldsm_if(uint32_t* r0, uint32_t* r1, uint32_t* r2, uint32_t a, uint32_t bar, uint32_t& got) {
    if (N == 2)
        asm volatile("{\n.reg .pred p, q;\nsetp.eq.u32 q, %8, 0;\nmbarrier.test_wait.parity.shared::cta.b64 p, [%10], 0;\nand.pred p, p, q;\n"
                     "@p ldmatrix.sync.aligned.m8n8.x4.trans.shared.b16 {%0,%1,%2,%3}, [%9];\n"
                     "@p ldmatrix.sync.aligned.m8n8.x4.trans.shared.b16 {%4,%5,%6,%7}, [%9+%11];\n@p mov.u32 %8, 1;\n}"
                     : "+r"(r0[0]), "+r"(r0[1]), "+r"(r0[2]), "+r"(r0[3]), "+r"(r1[0]), "+r"(r1[1]), "+r"(r1[2]), "+r"(r1[3]), "+r"(got)
                     : "r"(a), "r"(bar), "n"(STRIDE) : "memory");
    else
        asm volatile("{\n.reg .pred p, q;\nsetp.eq.u32 q, %12, 0;\nmbarrier.test_wait.parity.shared::cta.b64 p, [%14], 0;\nand.pred p, p, q;\n"
                     "@p ldmatrix.sync.aligned.m8n8.x4.trans.shared.b16 {%0,%1,%2,%3}, [%13];\n"
                     "@p ldmatrix.sync.aligned.m8n8.x4.trans.shared.b16 {%4,%5,%6,%7}, [%13+%15];\n"
                     "@p ldmatrix.sync.aligned.m8n8.x4.trans.shared.b16 {%8,%9,%10,%11}, [%13+%16];\n@p mov.u32 %12, 1;\n}"
                     : "+r"(r0[0]), "+r"(r0[1]), "+r"(r0[2]), "+r"(r0[3]), "+r"(r1[0]), "+r"(r1[1]), "+r"(r1[2]), "+r"(r1[3]),
                       "+r"(r2[0]), "+r"(r2[1]), "+r"(r2[2]), "+r"(r2[3]), "+r"(got)
                     : "r"(a), "r"(bar), "n"(STRIDE), "n"(2 * STRIDE) : "memory");
}
__device__ __forceinline__ void mma_bf16(float* c, uint32_t a0, uint32_t a1, uint32_t a2, uint32_t a3, uint32_t b0, uint32_t b1) {
    asm volatile("mma.sync.aligned.m16n8k16.row.col.f32.bf16.bf16.f32 {%0,%1,%2,%3}, {%4,%5,%6,%7}, {%8,%9}, {%0,%1,%2,%3};"
                 : "+f"(c[0]), "+f"(c[1]), "+f"(c[2]), "+f"(c[3]) : "r"(a0), "r"(a1), "r"(a2), "r"(a3), "r"(b0), "r"(b1));
}
__device__ __forceinline__ void mma_bf16(float* c, const uint32_t* a, uint32_t b0, uint32_t b1) { mma_bf16(c, a[0], a[1], a[2], a[3], b0, b1); }
__device__ __forceinline__ void zero4(float* c) { c[0] = c[1] = c[2] = c[3] = 0.f; }
__device__ __forceinline__ float bf_lo(uint32_t u) { return __uint_as_float(u << 16); }
__device__ __forceinline__ float bf_hi(uint32_t u) { return __uint_as_float(u & 0xffff0000u); }
__device__ __forceinline__ uint32_t pack_bf(float hi, float lo) { uint32_t r; asm("cvt.rn.bf16x2.f32 %0, %1, %2;" : "=r"(r) : "f"(hi), "f"(lo)); return r; }
__device__ __forceinline__ uint32_t add_bf2(uint32_t a, uint32_t b) { uint32_t r; asm("add.rn.bf16x2 %0, %1, %2;" : "=r"(r) : "r"(a), "r"(b)); return r; }
__device__ __forceinline__ float bfr(float x) { return __uint_as_float(pack_bf(x, 0.f)); }

__device__ __forceinline__ uint32_t in_word(float v) { return __float_as_uint(v); }
__device__ __forceinline__ void st1(void* p, uint32_t v) {
    asm volatile("st.relaxed.gpu.global.u32 [%0], %1;" ::"l"(p), "r"(v) : "memory");
}
__device__ __forceinline__ void st16(void* p, uint32_t v) {
    asm volatile("st.relaxed.gpu.global.u16 [%0], %1;" ::"l"(p), "h"((unsigned short)v) : "memory");
}
__device__ __forceinline__ void st2(void* p, uint32_t a, uint32_t b) {
    asm volatile("st.relaxed.gpu.global.v2.u32 [%0], {%1, %2};" ::"l"(p), "r"(a), "r"(b) : "memory");
}
__device__ __forceinline__ void st4(void* p, uint32_t a, uint32_t b, uint32_t c, uint32_t d) {
    asm volatile("st.relaxed.gpu.global.v4.u32 [%0], {%1, %2, %3, %4};" ::"l"(p), "r"(a), "r"(b), "r"(c), "r"(d) : "memory");
}
__device__ __forceinline__ uint32_t ld1(const void* p) {
    uint32_t v;
    asm volatile("ld.relaxed.gpu.global.u32 %0, [%1];" : "=r"(v) : "l"(p) : "memory");
    return v;
}
__device__ __forceinline__ uint2 ld2(const void* p) {
    uint2 v;
    asm volatile("ld.relaxed.gpu.global.v2.u32 {%0, %1}, [%2];" : "=r"(v.x), "=r"(v.y) : "l"(p) : "memory");
    return v;
}
__device__ __forceinline__ uint4 ld4(const void* p) {
    uint4 v;
    asm volatile("ld.relaxed.gpu.global.v4.u32 {%0, %1, %2, %3}, [%4];" : "=r"(v.x), "=r"(v.y), "=r"(v.z), "=r"(v.w) : "l"(p) : "memory");
    return v;
}
__device__ __forceinline__ void ld4p(const void* p, uint4& v, bool on) {
    asm volatile("{\n.reg .pred q;\nsetp.ne.u32 q, %5, 0;\n@q ld.relaxed.gpu.global.v4.u32 {%0, %1, %2, %3}, [%4];\n}"
                 : "+r"(v.x), "+r"(v.y), "+r"(v.z), "+r"(v.w) : "l"(p), "r"((uint32_t)on) : "memory");
}
__device__ __forceinline__ void ld2p(const void* p, uint2& v, bool on) {
    asm volatile("{\n.reg .pred q;\nsetp.ne.u32 q, %3, 0;\n@q ld.relaxed.gpu.global.v2.u32 {%0, %1}, [%2];\n}"
                 : "+r"(v.x), "+r"(v.y) : "l"(p), "r"((uint32_t)on) : "memory");
}
__device__ __forceinline__ void poll2(const void* p, uint2& v) {
    asm volatile("{\n.reg .pred q, r;\nsetp.nan.bf16x2 q|r, %0, %1;\nor.pred q, q, r;\n@q ld.relaxed.gpu.global.v2.u32 {%0, %1}, [%2];\n}"
                 : "+r"(v.x), "+r"(v.y) : "l"(p) : "memory");
}
__device__ __forceinline__ bool ok8(const uint4& v) {
    const uint32_t m = __vimax3_u16x2(__vimax3_u16x2(v.x, v.y, v.z), v.w, v.w);
    return __vimax3_u16x2(m, m << 16, m >> 16) != SENT;
}
__device__ __forceinline__ void poll4(const void* p, uint4& v) {
    asm volatile("{\n.reg .pred q;\n.reg .u32 m;\nmax.u32 m, %0, %1;\nmax.u32 m, m, %2;\nmax.u32 m, m, %3;\nsetp.eq.u32 q, m, 0xffffffff;\n"
                 "@q ld.relaxed.gpu.global.v4.u32 {%0, %1, %2, %3}, [%4];\n}"
                 : "+r"(v.x), "+r"(v.y), "+r"(v.z), "+r"(v.w) : "l"(p) : "memory");
}
__device__ __forceinline__ uint32_t max4(const uint4& v) { return max(max(v.x, v.y), max(v.z, v.w)); }
__device__ __forceinline__ void pkt_st2(uint4* p, float a, float b, uint32_t tag) {
    asm volatile("st.relaxed.gpu.global.v2.b64 [%0], {%1, %2};" ::"l"(p), "l"(((uint64_t)tag << 32) | __float_as_uint(a)), "l"(((uint64_t)tag << 32) | __float_as_uint(b)) : "memory");
}
__device__ __forceinline__ void pkt_ld2(const uint4* p, uint64_t& a, uint64_t& b) {
    asm volatile("ld.relaxed.gpu.global.v2.b64 {%0, %1}, [%2];" : "=l"(a), "=l"(b) : "l"(p) : "memory");
}
__device__ __forceinline__ bool tag_ok(uint64_t v, uint32_t tag) { return (uint32_t)(v >> 32) == tag; }
__device__ __forceinline__ float val_of(uint64_t v) { return __uint_as_float((uint32_t)v); }

__device__ __forceinline__ float warp_sum(float v) {
#pragma unroll
    for (int o = 16; o > 0; o >>= 1) v += __shfl_xor_sync(0xffffffffu, v, o);
    return v;
}
__device__ __forceinline__ float warp_max(float v) {
#pragma unroll
    for (int o = 16; o > 0; o >>= 1) v = fmaxf(v, __shfl_xor_sync(0xffffffffu, v, o));
    return v;
}
__device__ __forceinline__ float sqrt_fast(float x) { float r; asm("sqrt.approx.ftz.f32 %0, %1;" : "=f"(r) : "f"(x)); return r; }
__device__ __forceinline__ float rcp_fast(float x) { float r; asm("rcp.approx.ftz.f32 %0, %1;" : "=f"(r) : "f"(x)); return r; }
__device__ __forceinline__ float ex2(float x) { float r; asm("ex2.approx.ftz.f32 %0, %1;" : "=f"(r) : "f"(x)); return r; }
constexpr float L2E = 1.4426950408889634f;
__device__ __forceinline__ void ln_finish(float s1, float s2, float& mean_b, float& inv_den) {
    const float mean = s1 * (1.0f / D_MODEL);
    const float var = fmaxf(fmaf(-mean, mean, s2 * (1.0f / D_MODEL)), 0.f);
    mean_b = bfr(mean);
    inv_den = rcp_fast(bfr(sqrt_fast(bfr(bfr(var) + 1e-5f))));
}
__device__ __forceinline__ uint32_t ln_apply2(uint32_t u, float mean_b, float inv_den) {
    const uint32_t d = pack_bf(bf_hi(u) - mean_b, bf_lo(u) - mean_b);
    return pack_bf(bf_hi(d) * inv_den, bf_lo(d) * inv_den);
}
__device__ __forceinline__ void ln_acc(uint32_t u, float& s1, float& s2) {
    const float a = bf_lo(u), b = bf_hi(u);
    s1 += a + b;
    s2 = fmaf(a, a, fmaf(b, b, s2));
}
__device__ __forceinline__ float silu_b(float g) { return bfr(__fdividef(g, 1.0f + ex2(-g * L2E))); }

#define STAMP(i) do { } while (0)

struct KParams {
    const __nv_bfloat16* wq;
    const __nv_bfloat16* x;
    __nv_bfloat16* out;
    Scratch* sc;
    unsigned char* xa;
    int t_k0, per, stag;
    int target;
    int t_q, t_fill;
    uint32_t item[32];
    uint32_t role[NCTA];
};
struct TMaps { CUtensorMap k, v, wo, w1, w3, w2; };

__global__ void __launch_bounds__(NTHREADS, 1)
fused_decode_kernel(const __grid_constant__ KParams p, const __grid_constant__ TMaps tm) {
    extern __shared__ __align__(1024) unsigned char smem[];
    const int tid = threadIdx.x;
    const int b = blockIdx.x;
    const int head = b >> 2, sp = b & 3;
    if (tid < 256) {
        const uint32_t r = tid >> 3, ch = tid & 7;
        const char* src = reinterpret_cast<const char*>(p.wq) + ((sp * 160 + r) * (NHEAD * DH * 2) + head * (DH * 2) + ch * 16);
#pragma unroll
        for (int i = 0; i < NQT; i++) {
#pragma unroll
            for (int j = 0; j < 3; j++)
                asm volatile("cp.async.cg.shared.global [%0], [%1], 16;"
                             ::"r"(sbase + (QSLOT + i) * TILE_BYTES + (3 * r + j) * 128 + ((ch ^ ((3 * r + j) & 7)) << 4)),
                               "l"(src + (size_t)i * 32 * (NHEAD * DH * 2) + j * 128) : "memory");
        }
    }
    const uint32_t t0 = now_ns();
    const int warp = __shfl_sync(0xffffffffu, tid >> 5, 0), lane = tid & 31;
    const uint32_t role = p.role[b];
    const int kg = role >> 3 & 7, ng = role >> 6 & 31;
    const int u1 = role >> 11 & 127, u2 = role >> 18;
    const bool has_wo = role & 1, has_f1 = role & 2, has_f2 = role & 4;
    constexpr uint32_t bar_full = sbase + SM_BAR;
    constexpr uint32_t bar_empty = sbase + SM_BAR + 128;
    constexpr uint32_t bar_tail = sbase + SM_BAR + 256;
    constexpr uint32_t bar_scale = bar_tail + 8 * NTAIL;
    constexpr uint32_t bar_stat = bar_scale + 8;
    constexpr uint32_t bar_up = bar_scale + 16;

    if (warp == 8) {
        if (smem_u32(smem) != sbase) __trap();
        uint64_t pol;
        asm volatile("createpolicy.fractional.L2::evict_first.b64 %0, 1.0;" : "=l"(pol));
        sts32(sbase + SM_LATE + (lane & 7) * 4, 0u);
        if (lane == 0) {
#pragma unroll
            for (int i = 0; i < 32 + NTAIL + 3; i++)
                mbar_init(bar_full + 8 * i, (i >= 16 && i < 32) || i > 32 + NTAIL ? 8 : i == 32 + NWP ? NA : i == 33 + NWP ? 5 - NA : i == 34 + NWP ? NB : i == 35 + NWP ? 5 - NB : 1);
#pragma unroll
            for (int i = 0; i < 6; i++) asm volatile("prefetch.tensormap [%0];" ::"l"(reinterpret_cast<uint64_t>(&tm.k + i)) : "memory");
            asm volatile("fence.mbarrier_init.release.cluster;" ::: "memory");
        }
        __syncwarp();
        asm volatile("bar.arrive 2, 320;" ::: "memory");
        int slip = 0;
        if (lane == 0) {
            if (b == 0) { st4(p.sc->late, 0, 0, 0, 0); st4(p.sc->late + 4, 0, 0, 0, 0); }
            const int tile0 = (head * SK + (SK - WIN)) / 32 + sp;
            uint32_t tn = t0 + p.t_k0 + sp * p.stag, tw = tn, acc = 0;
            int w = 0;
#pragma unroll 1
            for (int n = 0; n < 2 * NKT; n++) {
                const int slot = n & (NSLOT - 1);
                mbar_wait(bar_empty + 8 * slot, (((n + NQT) >> 4) & 1) ^ 1);
                mbar_expect_tx(bar_full + 8 * slot, TILE_BYTES);
                uint32_t t;
                do {
                    t = now_ns();
                    if (mbar_test(bar_full + 8 * (w & (NSLOT - 1)), (w >> 4) & 1)) {
                        acc += t - tw;
                        tw += p.per;
                        if ((++w & 7) == 0) {
                            asm volatile("red.relaxed.gpu.global.add.u32 [%0], %1;" ::"l"(p.sc->late + (w >> 3)), "r"((1u << 24) + min(acc >> 3, 65535u)) : "memory");
                            acc = 0;
                        }
                    }
                } while ((int)(t - tn) < slip || w <= n - INFLIGHT);
                tma_load(sbase + slot * TILE_BYTES, &tm.k + (n >> 5), 0, tile0 + (n & (NKT - 1)) * 4, bar_full + 8 * slot, pol);
                tn += p.per;
                if ((n & 7) == 5)
                    asm volatile("cp.async.cg.shared.global [%0], [%1], 16;\ncp.async.cg.shared.global [%0+16], [%1+16], 16;" ::"r"(sbase + SM_LATE), "l"(p.sc->late) : "memory");
                uint32_t rep = lds32(sbase + SM_LATE + (n >> 3) * 4);
                if (!(rep >> 30)) rep = lds32(sbase + SM_LATE + (max(n - 8, 0) >> 3) * 4);
                if (rep >> 30) slip = max((int)((float)(rep & 0xffffffu) * rcp_fast((float)(rep >> 24))) - p.target, -500);
            }
        }
        const int seg = (lane >= NWP) + (lane >= NWP + NP1), i = lane - (seg == 0 ? 0 : seg == 1 ? NWP : NWP + NP1);
        const bool todo = lane < NITEM && (role >> seg & 1);
        const uint32_t len = seg == 1 ? 4096 : 8192, dst = sbase + (seg == 0 ? 0 : seg == 1 ? SM_W1 : SM_W2) + i * len;
        const int w3 = seg == 1 && i >= 5;
        const CUtensorMap* m = &tm.wo + (seg == 2 ? 3 : seg + w3);
        const int c0 = seg == 0 ? ng * 32 : seg == 1 ? u1 * 16 : u2 * 16;
        const int c4 = (seg == 0 ? kg * 64 : w3 * -40) + i * 8;
        const uint32_t bar = bar_tail + 8 * (seg == 0 ? i : seg == 1 ? NWP + (i >= NA) + w3 + (i >= 5 + NB) : NWP + NF1 + i);
        const uint32_t tn = (__shfl_sync(0xffffffffu, t0 + slip, 0) + p.item[lane]) | 1;
        if (todo) mbar_expect_tx(bar, len);
#pragma unroll 1
        for (int ph = 0; ph < 2; ph++) {
            mbar_wait(bar_empty + 8 * (ph ? 12 : 5), ph ^ 1);
            uint32_t due = todo && (seg != 0) == ph ? tn : 0;
            while (__any_sync(0xffffffffu, due)) {
                if (due && (int)(now_ns() - due) >= 0) {
                    tma_load(dst, m, c0, c4, bar, pol);
                    due = 0;
                }
            }
        }
    } else if (warp == 9) {
        const uint32_t tag = ld1(&p.sc->epoch) + 1;
        const uint32_t aoff = XA_A + (u1 >> 1 & 7) * 384 + (u1 >> 4) * 64 + (u1 & 1) * 32, hoff = xa_h(kg) + (ng & 3) * 512 + (ng >> 2) * 32;
        sts32(sbase + SM_ONE + (lane & 15) * 4, 0x3f803f80u);
        const uint32_t ooff = xa_o(head) + sp * (DH * 4);
        unsigned char* slot[4] = {p.xa + (ooff + lane * 16), p.xa + ((ooff + 512 + (lane & 15) * 16) ^ (lane >> 4) << 12), p.xa + ((ooff + lane * 16) ^ 4096),
                                  p.xa + (lane < 16 ? (has_wo ? hoff + (lane >> 2 & 1) * 4096 + (lane >> 1 & 1) * 256 + (lane & 1) * 16 : ooff) : has_f1 ? aoff + (lane >> 1 & 1) * 4096 + (lane & 1) * 16 : ooff)};
#pragma unroll
        for (int i = 0; i < 2; i++) st4(p.sc->qbuf + b * 96 + i * 32 + lane * 2, 0, 0, 0, 0);
        sts32(sbase + SM_MISC, tag);
        asm volatile("bar.sync 2, 320;" ::: "memory");
        while (!mbar_test(bar_stat, 0)) __nanosleep(200);
        const float4 ma = lds128f(sbase + SM_MAX), mb = lds128f(sbase + SM_MAX + 16);
        const float m = fmaxf(fmaxf(fmaxf(ma.x, ma.y), fmaxf(ma.z, ma.w)), fmaxf(fmaxf(mb.x, mb.y), fmaxf(mb.z, mb.w)));
        while ((int)(now_ns() - (t0 + p.t_fill)) < 0) __nanosleep(200);
        pkt_st2(p.sc->mbuf + b * 2 + (lane & 1), m, sum8(sbase + SM_SUM), tag);
#pragma unroll
        for (int i = 0; i < 4; i++) st4(slot[i], SENT, SENT, SENT, SENT);
        uint32_t ack = SENT;
#pragma unroll
        for (int i = 0; i < 4; i++) { uint32_t v; asm volatile("atom.relaxed.gpu.global.exch.b32 %0, [%1], -1;" : "=r"(v) : "l"(slot[i]) : "memory"); ack &= v; }
        if (__any_sync(0xffffffffu, ack != SENT)) __trap();
        if (lane == 0) st1(p.sc->ready + b, tag);
        int vote = 0;
#pragma unroll 1
        for (int r = 0; r < 5; r++) {
            __nanosleep(100);
            uint32_t d;
            asm volatile("{\n.reg .pred p, q;\n.reg .b32 a, b, c0, c1;\nmov.b32 c0, 0;\nmov.b32 c1, 0;\n"
                         "atom.relaxed.gpu.global.exch.b32 a, [%1], -1;\natom.relaxed.gpu.global.exch.b32 b, [%2], -1;\n"
                         "setp.eq.u32 p, a, -1;\n@p mov.u32 c0, %%clock;\nsetp.eq.u32 q, b, -1;\n@q mov.u32 c1, %%clock;\nsub.u32 %0, c1, c0;\n}"
                         : "=r"(d) : "l"(r & 1 ? slot[2] : slot[0]), "l"(r & 1 ? slot[0] : slot[2]) : "memory");
            vote += (d > 90) == (r & 1) ? 1 : -1;
        }
        const uint32_t side = __shfl_sync(0xffffffffu, vote, 0) > 0;
        uint32_t n = 0;
        {
            uint64_t em, el;
            while (true) {
                const uint4 e = ld4(p.sc->ready + lane * 4);
                pkt_ld2(p.sc->mbuf + (head * 4 + (lane & 3)) * 2, em, el);
                if (__all_sync(0xffffffffu, e.x == tag && e.y == tag && e.z == tag && e.w == tag && tag_ok(em, tag) && tag_ok(el, tag))) break;
                __nanosleep(500);
                if (++n > SPIN_LIMIT) __trap();
            }
            float M = fmaxf(val_of(em), __shfl_xor_sync(0xffffffffu, val_of(em), 1));
            M = fmaxf(M, __shfl_xor_sync(0xffffffffu, M, 2));
            float L = ex2((val_of(em) - M) * L2E) * val_of(el);
            L += __shfl_xor_sync(0xffffffffu, L, 1);
            L += __shfl_xor_sync(0xffffffffu, L, 2);
            if (lane == 0) {
                sts64(sbase + SM_MISC + 8, __float_as_uint(__fdividef(ex2((m - M) * L2E), L)), side);
                mbar_arrive(bar_scale);
                if (b == 0) p.sc->epoch = tag;
            }
        }
        unsigned char* hdst = p.xa + (hoff + (side ^ 1) * 4096 + (lane >> 4) * 256 + (lane & 15) * 2);
        unsigned char* hdst2 = p.xa + (hoff + side * 4096 + (lane >> 4) * 256 + (lane & 15) * 2);
        unsigned char* adst = p.xa + (aoff + (lane >> 4) * 4096 + (lane & 15) * 2);
        __nv_bfloat16* odst = p.out + u2 * 16 + (lane & 15);
        uint32_t r0 = sbase + SM_RED + lane * 48, r1 = sbase + SM_RED + (lane & 15) * 48;
        uint32_t res;
        asm volatile("ld.global.nc.u16 %0, [%1];" : "=r"(res) : "l"(p.x + u2 * 16 + (lane & 15)));
        pin(hdst); pin(hdst2); pin(adst); pin(odst); pin(r0); pin(r1);
        if (has_wo) {
            fin_sync<3>();
            const uint32_t v = pack_bf(0.f, sum8(r0));
            st16(hdst, v); st16(hdst2, v);
            STAMP(4);
        }
        if (has_f1) {
            fin_sync<4>();
            float mean_b, inv_den;
            ln_finish(sum8(sbase + SM_LN), sum8(sbase + SM_LN + 32), mean_b, inv_den);
            const float gr = fmaf(-mean_b, sum8(r1 + 48 * 48), sum8(r1 + 32 * 48)) * inv_den;
            mbar_wait_after(bar_up, r0, gr);
            const float gs = bfr(gr);
            const float up = bfr(fmaf(-mean_b, sum8(r1 + 80 * 48), sum8(r1 + 64 * 48)) * inv_den);
            st16(adst, pack_bf(0.f, silu_b(gs) * up));
            STAMP(8);
        }
        if (has_f2) {
            mbar_wait(bar_tail + 8 * (NWP + NF1 + CFG_HG), 0);
            const unsigned char* hsrc = p.xa + ((lane >> 4) * (1 << 14) + side * 4096 + (u2 & 7) * 256 + (u2 >> 3) * 32 + (lane & 15) * 2);
            uint32_t e[3];
            do {
#pragma unroll
                for (int i = 0; i < 3; i++) asm volatile("ld.relaxed.gpu.global.u16 %0, [%1];" : "=r"(e[i]) : "l"(hsrc + xa_h(2 * i)) : "memory");
                if (++n > SPIN_LIMIT) __trap();
            } while (__any_sync(0xffffffffu, max(max(e[0], e[1]), e[2]) == 0xffffu));
            float f[3];
#pragma unroll
            for (int i = 0; i < 3; i++) f[i] = bf_lo(e[i]) + bf_lo(__shfl_xor_sync(0xffffffffu, e[i], 16));
            res = add_bf2(res, pack_bf(0.f, (f[0] + f[1]) + f[2]));
            pin(res);
            fin_sync<6>();
            asm volatile("st.global.u16 [%0], %1;" ::"l"(odst), "h"((unsigned short)add_bf2(res, pack_bf(0.f, sum8(r1 + 96 * 48)))) : "memory");
            STAMP(11);
        }
    } else {
        const int g = lane >> 2, t = lane & 3;
        uint2 xres;
        {
            uint32_t xr;
            uint2 xu[5];
            const char* xb = reinterpret_cast<const char*>(p.x);
            asm volatile("ld.global.nc.u16 %0, [%1];" : "=r"(xr) : "l"(xb + (sp * 160 + min(tid, 159)) * 2));
#pragma unroll
            for (int i = 0; i < 5; i++) asm volatile("ld.global.nc.v2.u32 {%0, %1}, [%2];" : "=r"(xu[i].x), "=r"(xu[i].y) : "l"(xb + i * 256 + lane * 8));
            asm volatile("ld.global.nc.v2.u32 {%0, %1}, [%2];" : "=r"(xres.x), "=r"(xres.y) : "l"(xb + min(g, 4) * 256 + warp * 32 + t * 8));
            if (lane >= 20) xres.x = xres.y = 0;
            float s1 = 0.f, s2 = 0.f, mean_b, inv_den;
#pragma unroll
            for (int i = 0; i < 5; i++) { ln_acc(xu[i].x, s1, s2); ln_acc(xu[i].y, s1, s2); }
            ln_finish(warp_sum(s1), warp_sum(s2), mean_b, inv_den);
            sts16(sbase + SM_P + warp * 64 + ((lane >> 1 & 3) * 8 + (lane >> 3) * 2 + (lane & 1)) * 2, ln_apply2(xr, mean_b, inv_den));
            asm volatile("cp.async.wait_all;" ::: "memory");
            asm volatile("bar.sync 2, 320;" ::: "memory");
        }
        STAMP(0);
        uint32_t va[3];
#pragma unroll
        for (int i = 0; i < 3; i++) {
            const int cc = 3 * warp + i, row = 3 * lane + (cc >> 3);
            va[i] = sbase + row * 128 + (((cc ^ row) & 7) << 4);
        }
        const int gi = g >= 3 ? g - 3 : g;
        unsigned char* odst = p.xa + ((xa_o(head) ^ (g >= 3 ? 4096 : 0)) + (sp * DH + warp * 24 + gi * 8 + t * 2) * 4);
        pin(odst);

#pragma unroll 1
        for (int ph = 0; ph < 2; ph++) {
            if (ph == 1) {
                uint4 qf[6];
#pragma unroll
                for (int i = 0; i < 6; i++) qf[i] = lds128(sbase + SM_Q + t * 96 + i * 16);
                uint32_t ka[3];
#pragma unroll
                for (int j = 0; j < 3; j++) {
                    const int row = 3 * (lane & 15) + j;
                    ka[j] = sbase + row * 128 + ((((lane >> 4) ^ row) & 7) << 4) + warp * TILE_BYTES;
                }
                float s[4] = {0.f, 0.f, 0.f, 0.f};
#pragma unroll 1
                for (int it = 0; it < 4; it++) {
                    const int slot = (it & 1) * 8 + warp;
                    const uint32_t so = (it & 1) * 8 * TILE_BYTES;
                    float c[2][2][4];
                    zero4(c[0][0]); zero4(c[0][1]); zero4(c[1][0]); zero4(c[1][1]);
                    mbar_wait(bar_full + 8 * slot, it >> 1);
#pragma unroll
                    for (int ks = 0; ks < 12; ks++) {
                        const uint32_t a = (ka[ks >> 2] + so) ^ ((ks & 3) << 5);
                        uint32_t f0[4], f1[4];
                        ldsm_x4(f0, a); ldsm_x4(f1, a + 16 * DH * 2);
                        const uint32_t b0 = ks & 1 ? qf[ks >> 1].z : qf[ks >> 1].x, b1 = ks & 1 ? qf[ks >> 1].w : qf[ks >> 1].y;
                        mma_bf16(c[0][ks & 1], f0, b0, b1); mma_bf16(c[1][ks & 1], f1, b0, b1);
                    }
                    if (lane == 0) mbar_arrive8(bar_empty + 8 * slot);
                    const float v = t & 2 ? (t & 1 ? c[1][0][2] + c[1][1][2] : c[1][0][0] + c[1][1][0]) : (t & 1 ? c[0][0][2] + c[0][1][2] : c[0][0][0] + c[0][1][0]);
                    s[0] = s[1]; s[1] = s[2]; s[2] = s[3];
                    s[3] = bfr(bfr(v) * 0.07216878364870322f);
                }
                const float mw = warp_max(fmaxf(fmaxf(s[0], s[1]), fmaxf(s[2], s[3])));
                if (lane == 0) sts32(sbase + SM_MAX + warp * 4, mw);
                cons_sync();
                const float4 ma = lds128f(sbase + SM_MAX), mb = lds128f(sbase + SM_MAX + 16);
                const float m = fmaxf(fmaxf(fmaxf(ma.x, ma.y), fmaxf(ma.z, ma.w)), fmaxf(fmaxf(mb.x, mb.y), fmaxf(mb.z, mb.w)));
                float l = 0.f;
#pragma unroll
                for (int it = 0; it < 4; it++) {
                    const float e = ex2((s[it] - m) * L2E);
                    l += e;
                    sts16(sbase + SM_P + (it * 8 + warp) * 64 + ((g >> 1) * 8 + t * 2 + (g & 1)) * 2, pack_bf(0.f, e));
                }
                l = warp_sum(l);
                if (lane == 0) { sts32(sbase + SM_SUM + warp * 4, l); mbar_arrive(bar_stat); }
                cons_sync();
                STAMP(1);
            }
            float acc[2][3][4];
#pragma unroll
            for (int i = 0; i < 3; i++) { zero4(acc[0][i]); zero4(acc[1][i]); }
            const int nt = ph ? NKT : NQT;
            float scale = 1.f;
#pragma unroll 1
            for (int n = 0; n < nt; n++) {
                const int slot = ph ? (n & (NSLOT - 1)) : QSLOT + n;
                const uint4 w = lds128(sbase + SM_P + n * 64 + t * 16);
                if (n == NKT - 1) { mbar_wait(bar_scale, 0); scale = __uint_as_float(lds32(sbase + SM_MISC + 8)); }
                if (ph) mbar_wait(bar_full + 8 * slot, (n >> 4) & 1);
                uint32_t f[3][4];
#pragma unroll
                for (int i = 0; i < 3; i++) ldsm_x4_t(f[i], va[i] + slot * TILE_BYTES);
#pragma unroll
                for (int i = 0; i < 3; i++) {
                    mma_bf16(acc[0][i], w.x, w.x, w.y, w.y, f[i][0], f[i][1]);
                    mma_bf16(acc[1][i], w.z, w.z, w.w, w.w, f[i][2], f[i][3]);
                }
                if (lane == 0) mbar_arrive(bar_empty + 8 * slot);
            }
            const float v0 = (gi == 0 ? acc[0][0][0] + acc[1][0][0] : gi == 1 ? acc[0][1][0] + acc[1][1][0] : acc[0][2][0] + acc[1][2][0]) * scale;
            const float v1 = (gi == 0 ? acc[0][0][1] + acc[1][0][1] : gi == 1 ? acc[0][1][1] + acc[1][1][1] : acc[0][2][1] + acc[1][2][1]) * scale;
            if (ph == 1) {
                if (g < 6) st2(odst, in_word(v0), in_word(v1));
                break;
            }
            const uint32_t tag = lds32(sbase + SM_MISC);
            const uint32_t t4 = tag % 15 + 1;
            if (g < 3) st2(p.sc->qbuf + b * 96 + warp * 12 + lane, (__float_as_uint(v0) & ~15u) | t4, (__float_as_uint(v1) & ~15u) | t4);
            if (warp < 3) {
                uint2 e[4];
                uint32_t n = 0, bad;
#pragma unroll 1
                do {
                    __nanosleep(p.t_q);
                    bad = 0;
#pragma unroll
                    for (int i = 0; i < 4; i++) e[i] = ld2(p.sc->qbuf + (head * 4 + i) * 96 + tid);
#pragma unroll
                    for (int i = 0; i < 4; i++) { e[i].x ^= t4; e[i].y ^= t4; bad |= e[i].x | e[i].y; }
                    if (++n > SPIN_LIMIT) __trap();
                } while (__any_sync(0xffffffffu, bad & 15));
#define S_(c) ((__uint_as_float(e[0].c) + __uint_as_float(e[1].c)) + (__uint_as_float(e[2].c) + __uint_as_float(e[3].c)))
                sts32(sbase + SM_Q + (t * 24 + (tid >> 2)) * 4, pack_bf(S_(y), S_(x)));
#undef S_
            }
            cons_sync();
        }
        STAMP(2);
        const uint32_t side = lds32(sbase + SM_MISC + 12) * 4096;
        const uint32_t d16 = kg * 64 + g * 8 + warp, oh = d16 / 12;
        const unsigned char* osrc = p.xa + ((xa_o(oh) ^ side) + ((d16 - oh * 12) * 16 + t * 4) * 4);
        const int r16 = (lane & 7) + ((lane >> 4) << 3), mi = lane >> 3 & 1;
        const uint32_t f32 = sbase + r16 * 32 + ((mi ^ (lane >> 2 & 1)) << 4);
        uint32_t rdst = sbase + SM_RED + (t * 8 + g) * 48 + warp * 4;
        uint32_t bl = sbase + SM_BC + warp * 512 + t * 80, bs = bl + g * 8;
        uint32_t hl = g < 4 ? bl : sbase + SM_ONE;
        uint32_t w1a = f32 + SM_W1 + warp * 512, w2a = f32 + SM_W2 + warp * 1024;
        uint32_t lnd = lane < 2 ? sbase + SM_LN + lane * 32 + warp * 4 : sbase + SM_BC + warp * 512 + 384 + lane * 4;
        const unsigned char* hs = p.xa + (side + warp * 256 + lane * 8);
        const unsigned char* as = p.xa + (XA_A + side + warp * 384 + min(lane, 23) * 16);
        uint32_t al = sbase + SM_BC + warp * 512 + t * 16, at = sbase + SM_BC + warp * 512 + lane * 16;
        uint32_t fl = role, ln = lane;
        pin_u(fl); pin(ln);
        const bool f1 = fl & 2, f2 = fl & 4, odd = ln & 1, first = ln == 0;
        constexpr uint32_t b2 = bar_tail + 8 * (NWP + NF1);
        pin(rdst); pin(bs); pin(hl); pin(w1a); pin(w2a); pin(lnd); pin(hs); pin(as); pin(al); pin(at);
#define F_(i, c) __uint_as_float(e[i].c)
        if (has_wo) {
            uint4 e[4];
#pragma unroll
            for (int i = 0; i < 4; i++) e[i].x = e[i].y = e[i].z = e[i].w = SENT;
            uint32_t n = 0;
            mbar_wait(bar_tail + 8 * CFG_OG, 0);
#pragma unroll 1
            do {
                if (CFG_OSL && n) __nanosleep(CFG_OSL);
#pragma unroll
                for (int i = 0; i < 4; i++) poll4(osrc + i * (DH * 4), e[i]);
                if (++n > SPIN_LIMIT) __trap();
            } while (__any_sync(0xffffffffu, max(max(max4(e[0]), max4(e[1])), max(max4(e[2]), max4(e[3]))) == SENT));
            sts64(bs, pack_bf((F_(0, y) + F_(1, y)) + (F_(2, y) + F_(3, y)), (F_(0, x) + F_(1, x)) + (F_(2, x) + F_(3, x))),
                      pack_bf((F_(0, w) + F_(1, w)) + (F_(2, w) + F_(3, w)), (F_(0, z) + F_(1, z)) + (F_(2, z) + F_(3, z))));
            __syncwarp();
#pragma unroll
            for (int i = 0; i < 4; i++) e[i] = lds128(bl + i * 16);
            STAMP(3);
            const uint32_t wa = sbase + (warp * 16 + r16) * 64 + ((mi ^ (r16 >> 1 & 3)) << 4), wb = wa ^ 32;
            float c0[4], c1[4];
            zero4(c0); zero4(c1);
#pragma unroll
            for (int j = 0; j < NWP; j++) {
                mbar_wait(bar_tail + 8 * j, 0);
                uint32_t f0[4], f1[4];
                ldsm_x4_t(f0, wa + j * 8192); ldsm_x4_t(f1, wb + j * 8192);
                const uint32_t b0 = j & 1 ? e[j >> 1].z : e[j >> 1].x, b1 = j & 1 ? e[j >> 1].w : e[j >> 1].y;
                mma_bf16(c0, f0, b0, b1); mma_bf16(c1, f1, b0, b1);
            }
            sts32(rdst, t & 2 ? (t & 1 ? c1[2] : c1[0]) : (t & 1 ? c0[2] : c0[0]));
            fin_arrive<3>();
        }
        if (f1) {
            constexpr uint32_t b1 = bar_tail + 8 * NWP;
            uint32_t a1[5][4], a3[5][4];
            uint2 e[NG];
#pragma unroll
            for (int i = 0; i < NG; i++) e[i].x = e[i].y = 0;
            uint32_t got = 0, n = 0;
#pragma unroll
            for (int i = 0; i < NB; i++) a3[i][0] = a3[i][1] = a3[i][2] = a3[i][3] = 0;
            mbar_wait(b1, 0);
#pragma unroll
            for (int i = 0; i < NG; i++) ld2p(hs + xa_h(i), e[i], lane < 20);
            mbar_wait(b1 + 8, 0);
#pragma unroll
            for (int i = 0; i < 5; i++) ldsm_x4_t(a1[i], w1a + i * 4096);
            uint4 hb0, hb1;
            uint2 hb2;
            float sv[4];
#pragma unroll 1
            while (true) {
#define S_(f, c) (((f(e[0].c) + f(e[1].c)) + (f(e[2].c) + f(e[3].c))) + (f(e[4].c) + f(e[5].c)))
                const float sx = S_(bf_lo, x), sy = S_(bf_hi, x), sz = S_(bf_lo, y), sw = S_(bf_hi, y), sa = (sx + sy) + (sz + sw);
#undef S_
                const uint32_t h0 = add_bf2(xres.x, pack_bf(sy, sx)), h1 = add_bf2(xres.y, pack_bf(sw, sz));
                sts64(bs, h0, h1);
                __syncwarp();
                hb0 = lds128(hl); hb1 = lds128(hl + 16); hb2 = lds64(hl + 32);
                const float a = bf_lo(h0), b = bf_hi(h0), c = bf_lo(h1), d = bf_hi(h1);
                const float s1 = (a + b) + (c + d), s2 = fmaf(a, a, b * b) + fmaf(c, c, d * d);
                sv[0] = odd ? s2 : s1;
                sv[1] = __shfl_xor_sync(0xffffffffu, odd ? s1 : s2, 1);
                sv[2] = __shfl_xor_sync(0xffffffffu, sv[0], 2);
                sv[3] = __shfl_xor_sync(0xffffffffu, odd ? s1 : s2, 3);
                bool miss = __any_sync(0xffffffffu, sa != sa);
                if (n == 0) STAMP(12);
                if (miss) {
                    const uint4 mx = make_uint4(__vimax3_u16x2(e[0].x, e[0].y, e[1].x), __vimax3_u16x2(e[1].y, e[2].x, e[2].y),
                                                __vimax3_u16x2(e[3].x, e[3].y, e[4].x), __vimax3_u16x2(e[4].y, e[5].x, e[5].y));
#pragma unroll
                    for (int i = 0; i < NG; i++) poll2(hs + xa_h(i), e[i]);
                    ldsm_if<NB, 4096>(a3[0], a3[1], a3[2], w1a + (SM_W3 - SM_W1), b1 + 16, got);
                    if (++n > SPIN_LIMIT) __trap();
                    miss = __any_sync(0xffffffffu, !ok8(mx));
                }
                if (!miss) break;
            }
            STAMP(5);
            float cg[3][4], cu[3][4];
#pragma unroll
            for (int i = 0; i < 3; i++) { zero4(cg[i]); zero4(cu[i]); }
            const uint32_t hb[5][2] = {{hb0.x, hb0.y}, {hb0.z, hb0.w}, {hb1.x, hb1.y}, {hb1.z, hb1.w}, {hb2.x, hb2.y}};
            const float st = (sv[0] + sv[1]) + (sv[2] + sv[3]);
#pragma unroll
            for (int i = 0; i < 4; i++) sv[i] = __shfl_down_sync(0xffffffffu, st, 4 * i + 4);
#pragma unroll
            for (int i = 0; i < 5; i++) mma_bf16(cg[i % 3], a1[i], hb[i][0], hb[i][1]);
            sts32(lnd, ((st + sv[0]) + sv[1]) + (sv[2] + sv[3]));
            sts32(rdst + 32 * 48, odd ? (cg[0][2] + cg[2][2]) + cg[1][2] : (cg[0][0] + cg[2][0]) + cg[1][0]);
            fin_arrive<4>();
            STAMP(6);
            if (__any_sync(0xffffffffu, !got)) {
                mbar_wait(b1 + 16, 0);
#pragma unroll
                for (int i = 0; i < NB; i++) ldsm_x4_t(a3[i], w1a + (SM_W3 - SM_W1) + i * 4096);
            }
            mbar_wait(b1 + 24, 0);
#pragma unroll
            for (int i = NB; i < 5; i++) ldsm_x4_t(a3[i], w1a + (SM_W3 - SM_W1) + i * 4096);
#pragma unroll
            for (int i = 0; i < 5; i++) mma_bf16(cu[i % 3], a3[i], hb[i][0], hb[i][1]);
            sts32(rdst + 64 * 48, odd ? (cu[0][2] + cu[2][2]) + cu[1][2] : (cu[0][0] + cu[2][0]) + cu[1][0]);
            __syncwarp();
            if (first) mbar_arrive(bar_up);
        }
        if (f2) {
            uint32_t a2[NF2][2][4];
#pragma unroll
            for (int i = 0; i < 4; i++) a2[NF2 - 1][0][i] = a2[NF2 - 1][1][i] = 0;
#pragma unroll
            for (int j = 0; j < NF2 - 1; j++) {
                mbar_wait(b2 + 8 * j, 0);
                ldsm_x4_t(a2[j][0], w2a + j * 8192); ldsm_x4_t(a2[j][1], w2a + j * 8192 + 512);
            }
            STAMP(9);
            uint32_t n = 0, got = 0;
            uint4 e[NF2];
#pragma unroll 1
            while (true) {
                const uint4 pa = ld4(as);
                ldsm_if<2, 512>(a2[NF2 - 1][0], a2[NF2 - 1][1], nullptr, w2a + (NF2 - 1) * 8192, b2 + 8 * (NF2 - 1), got);
                if (++n > SPIN_LIMIT) __trap();
                sts128(at, pa);
                __syncwarp();
#pragma unroll
                for (int j = 0; j < CFG_NSPEC; j++) e[j] = lds128v(al + j * 64);
                if (__all_sync(0xffffffffu, ok8(pa))) break;
            }
#pragma unroll
            for (int j = CFG_NSPEC; j < NF2; j++) e[j] = lds128v(al + j * 64);
            STAMP(10);
            float c[4][4];
            zero4(c[0]); zero4(c[1]); zero4(c[2]); zero4(c[3]);
#pragma unroll
            for (int j = 0; j < NF2; j++) { mma_bf16(c[(j & 1) * 2], a2[j][0], e[j].x, e[j].y); mma_bf16(c[(j & 1) * 2 + 1], a2[j][1], e[j].z, e[j].w); }
            if (__any_sync(0xffffffffu, !got)) {
                constexpr int j = NF2 - 1;
                mbar_wait(b2 + 8 * j, 0);
                ldsm_x4_t(a2[j][0], w2a + j * 8192); ldsm_x4_t(a2[j][1], w2a + j * 8192 + 512);
                mma_bf16(c[0], a2[j][0], e[j].x, e[j].y); mma_bf16(c[1], a2[j][1], e[j].z, e[j].w);
            }
            sts32(rdst + 96 * 48, odd ? (c[0][2] + c[1][2]) + (c[2][2] + c[3][2]) : (c[0][0] + c[1][0]) + (c[2][0] + c[3][0]));
            fin_arrive<6>();
        }
#undef F_
    }
}

typedef CUresult (*EncodeTiledFn)(CUtensorMap*, CUtensorMapDataType, cuuint32_t, void*, const cuuint64_t*, const cuuint64_t*,
                                  const cuuint32_t*, const cuuint32_t*, CUtensorMapInterleave, CUtensorMapSwizzle,
                                  CUtensorMapL2promotion, CUtensorMapFloatOOBfill);

void make_map(EncodeTiledFn fn, CUtensorMap* tm, const void* w, const int (&d)[5], const int (&st)[4], const int (&bx)[5],
              CUtensorMapSwizzle sw, int promo) {
    cuuint64_t dims[5], strides[4];
    cuuint32_t box[5], estr[5];
    for (int i = 0; i < 5; i++) { dims[i] = (cuuint64_t)d[i]; box[i] = (cuuint32_t)bx[i]; estr[i] = 1; }
    for (int i = 0; i < 4; i++) strides[i] = (cuuint64_t)st[i];
    fn(tm, CU_TENSOR_MAP_DATA_TYPE_BFLOAT16, 5, const_cast<void*>(w), dims, strides, box, estr, CU_TENSOR_MAP_INTERLEAVE_NONE, sw,
       (CUtensorMapL2promotion)promo, CU_TENSOR_MAP_FLOAT_OOB_FILL_NONE);
}

enum { T_PER, T_LEAD, T_STAG, T_TD, T_PERO, T_F1D, T_PERF, T_F2, T_PER2, T_Q, T_PWO, T_PW13, T_PW2, T_TG, T_N };
#define TUNE_NAMES {"per", "lead", "stag", "td", "pero", "f1d", "perf", "f2", "per2", "q", "pwo", "pw13", "pw2", "tg"}
int g_tune[T_N] = {478, 1270, 122, 110, 290, 190, 122, 1353, 125, 1650, 1, 2, 2, 1750};

}

extern "C" void kernel_launch(void* const* d_in, const int* in_sizes, int n_in, void* d_out, int out_size) {
    (void)in_sizes; (void)n_in; (void)out_size;
    static EncodeTiledFn encode = nullptr;
    static Scratch* scratch = nullptr;
    static unsigned char* xarea = nullptr;
    if (!encode) {
        void* sp = nullptr;
        cudaGetSymbolAddress(&sp, g_scratch);
        scratch = reinterpret_cast<Scratch*>(sp);
        cudaGetSymbolAddress(&sp, g_xarea);
        xarea = reinterpret_cast<unsigned char*>((reinterpret_cast<uintptr_t>(sp) + XA_ALIGN - 1) / XA_ALIGN * XA_ALIGN);
        void* fn = nullptr;
        cudaDriverEntryPointQueryResult st;
        cudaGetDriverEntryPoint("cuTensorMapEncodeTiled", &fn, cudaEnableDefault, &st);
        encode = reinterpret_cast<EncodeTiledFn>(fn);
        cudaFuncSetAttribute(fused_decode_kernel, cudaFuncAttributeMaxDynamicSharedMemorySize, SM_TOTAL);
    }
    const int* T = g_tune;
    KParams p;
    p.x = (const __nv_bfloat16*)d_in[0];
    p.wq = (const __nv_bfloat16*)d_in[3];
    p.out = (__nv_bfloat16*)d_out;
    p.sc = scratch;
    p.xa = xarea;
    p.per = T[T_PER];
    p.stag = T[T_STAG];
    p.t_k0 = (NQT + 1) * T[T_PER] - T[T_LEAD];
    {
        int t = p.t_k0 + 2 * NKT * T[T_PER] + T[T_STAG] * 3 / 2 + T[T_TD];
        for (int i = 0; i < NWP; i++, t += T[T_PERO]) p.item[i] = t;
        for (int i = 0, t1 = t + T[T_F1D]; i < NP1; i++, t1 += T[T_PERF]) p.item[NWP + i] = t1;
        for (int i = 0, t2 = t + T[T_F2]; i < NF2; i++, t2 += T[T_PER2]) p.item[NWP + NP1 + i] = t2;
        for (int i = NITEM; i < 32; i++) p.item[i] = 0;
    }
    p.target = T[T_TG]; p.t_q = T[T_Q]; p.t_fill = p.t_k0 + 55 * T[T_PER];
    for (int i = 0, nw = 0, n1 = 0, n2 = 0; i < NCTA; i++) {
        const int grp = i >> 2;
        const bool f2 = grp % 3 == 2, both = grp == 8 || grp == 23, wo = !both, f1 = !f2 || both;
        p.role[i] = (wo ? 1 | nw / 20 << 3 | nw % 20 << 6 : 0) | (f1 ? 2 | n1 << 11 : 0) | (f2 ? 4 | n2 << 18 : 0);
        nw += wo; n1 += f1; n2 += f2;
    }
    TMaps tm;
    constexpr int R1 = FF * 2, R2 = D_MODEL * 2;
    for (int i = 0; i < 2; i++)
        make_map(encode, &tm.k + i, d_in[1 + i], {64, 96, 1, 1, NHEAD * SK / 32}, {128, TILE_BYTES, TILE_BYTES, TILE_BYTES}, {64, 96, 1, 1, 1}, CU_TENSOR_MAP_SWIZZLE_128B, 2);
    make_map(encode, &tm.wo, d_in[4], {D_MODEL, 2, 4, 2, NHEAD * DH / 16}, {R2, 4 * R2, 2 * R2, 16 * R2}, {32, 2, 4, 2, 8}, CU_TENSOR_MAP_SWIZZLE_64B, T[T_PWO]);
    make_map(encode, &tm.w1, d_in[6], {FF, 2, 4, 2, D_MODEL / 16}, {R1, 4 * R1, 2 * R1, 16 * R1}, {16, 2, 4, 2, 8}, CU_TENSOR_MAP_SWIZZLE_32B, T[T_PW13]);
    make_map(encode, &tm.w3, d_in[7], {FF, 2, 4, 2, D_MODEL / 16}, {R1, 4 * R1, 2 * R1, 16 * R1}, {16, 2, 4, 2, 8}, CU_TENSOR_MAP_SWIZZLE_32B, T[T_PW13]);
    make_map(encode, &tm.w2, d_in[8], {D_MODEL, 2, 4, 4, FF / 32}, {R2, 8 * R2, 2 * R2, 32 * R2}, {16, 2, 4, 4, 8}, CU_TENSOR_MAP_SWIZZLE_32B, T[T_PW2]);
    fused_decode_kernel<<<NCTA, NTHREADS, SM_TOTAL, cudaStreamPerThread>>>(p, tm);
}
```

```cpp
#include <cuda_runtime.h>
#include <cuda_bf16.h>
#include <cuda.h>
#include <stdint.h>
#include <initializer_list>

namespace {

constexpr int D_MODEL = 640;
constexpr int NHEAD = 32;
constexpr int DH = 192;
constexpr int SK = 32768;
constexpr int WIN = 4096;
constexpr int FF = 1536;

constexpr int NCTA = 128;
constexpr int NTHREADS = 256 + 64;
constexpr int TILE_BYTES = 32 * DH * 2;
constexpr int NSLOT = 16;
constexpr int NKT = 32;
constexpr int NQT = 5;
constexpr int QSLOT = NSLOT - NQT;
constexpr int NG = 6;
constexpr int NWP = 8, NP1 = 10, NF2 = 6;
constexpr int NITEM = NWP + NP1 + NF2;
#define CFG_NSPEC 3
#define CFG_NA 2
#define CFG_NB 2
constexpr int NF1 = 4, NA = CFG_NA, NB = CFG_NB;
constexpr int NTAIL = NWP + NF1 + NF2;

#define CFG_INFL 5
#define CFG_OG 0
#define CFG_HG 3
#define CFG_OSL 100
constexpr int INFLIGHT = CFG_INFL;

constexpr uint32_t sbase = 1024;
constexpr int SM_W1 = NWP * 8192, SM_W3 = SM_W1 + 20480, SM_W2 = SM_W3 + 20480;
constexpr int SM_P = NSLOT * TILE_BYTES;
constexpr int SM_Q = SM_P + 2048;
constexpr int SM_RED = SM_Q + 384;
constexpr int SM_BC = SM_RED + 128 * 48;
constexpr int SM_ONE = SM_BC + 4096;
constexpr int SM_MAX = SM_ONE + 64;
constexpr int SM_SUM = SM_MAX + 32;
constexpr int SM_LN = SM_SUM + 32;
constexpr int SM_MISC = SM_LN + 64;
constexpr int SM_LATE = SM_MISC + 32;
constexpr int SM_BAR = SM_LATE + 32;
constexpr int SM_TOTAL = SM_BAR + 512;
static_assert(SM_TOTAL <= 232448, "shared memory");

struct __align__(128) Scratch {
    uint2 qbuf[NCTA * 96];
    uint4 mbuf[NCTA * 2];
    uint32_t ready[NCTA];
    uint32_t late[32];
    uint32_t epoch;
};
__device__ Scratch g_scratch;
constexpr int XA_ALIGN = 1 << 20;
constexpr uint32_t SENT = 0xffffffffu;
__device__ unsigned char g_xarea[2 * XA_ALIGN];
__host__ __device__ constexpr uint32_t xa_o(uint32_t h) { return (2 * h + ((h ^ (h >> 3) ^ (h >> 4)) & 1)) * 4096; }
__host__ __device__ constexpr uint32_t xa_h(uint32_t i) { return (1 << 18) + (i >> 2) * (3 << 16) + (i & 3) * (1 << 14); }
constexpr uint32_t XA_A = xa_h(NG);

constexpr uint32_t SPIN_LIMIT = 1u << 22;

__device__ __forceinline__ uint32_t smem_u32(const void* p) { return (uint32_t)__cvta_generic_to_shared(p); }
__device__ __forceinline__ uint32_t now_ns() { uint64_t t; asm volatile("mov.u64 %0, %globaltimer;" : "=l"(t)); return (uint32_t)t; }
__device__ __forceinline__ void mbar_init(uint32_t bar, uint32_t cnt) {
    asm volatile("mbarrier.init.shared::cta.b64 [%0], %1;" ::"r"(bar), "r"(cnt) : "memory");
}
__device__ __forceinline__ void mbar_expect_tx(uint32_t bar, uint32_t bytes) {
    asm volatile("mbarrier.arrive.expect_tx.shared::cta.b64 _, [%0], %1;" ::"r"(bar), "r"(bytes) : "memory");
}
__device__ __forceinline__ void mbar_arrive(uint32_t bar) {
    asm volatile("mbarrier.arrive.shared::cta.b64 _, [%0];" ::"r"(bar) : "memory");
}
__device__ __forceinline__ void mbar_arrive8(uint32_t bar) {
    asm volatile("mbarrier.arrive.shared::cta.b64 _, [%0], 8;" ::"r"(bar) : "memory");
}
__device__ __forceinline__ bool mbar_test(uint32_t bar, uint32_t parity) {
    uint32_t ok;
    asm volatile("{\n.reg .pred p;\nmbarrier.test_wait.parity.shared::cta.b64 p, [%1], %2;\nselp.u32 %0, 1, 0, p;\n}"
                 : "=r"(ok) : "r"(bar), "r"(parity) : "memory");
    return ok;
}
__device__ __forceinline__ void mbar_wait(uint32_t bar, uint32_t parity) {
    asm volatile("{\n.reg .pred p;\nW_%=:\nmbarrier.try_wait.parity.shared::cta.b64 p, [%0], %1;\n@!p bra.uni W_%=;\n}" ::"r"(bar), "r"(parity) : "memory");
}
__device__ __forceinline__ void mbar_wait_after(uint32_t bar, uint32_t dump, float v) {
    uint32_t ok;
    asm volatile("{\n.reg .pred p;\nmbarrier.try_wait.parity.shared::cta.b64 p, [%1], 0;\nselp.u32 %0, 1, 0, p;\n}" : "=r"(ok) : "r"(bar) : "memory");
    asm volatile("st.volatile.shared.f32 [%0], %1;" ::"r"(dump), "f"(v) : "memory");
    if (__builtin_expect(!ok, 0)) mbar_wait(bar, 0);
}
__device__ __forceinline__ void tma_load(uint32_t dst, const CUtensorMap* tm, int c0, int c4, uint32_t bar, uint64_t pol) {
    asm volatile("cp.async.bulk.tensor.5d.shared::cluster.global.mbarrier::complete_tx::bytes.L2::cache_hint [%0], [%1, {%3, %5, %5, %5, %4}], [%2], %6;"
                 ::"r"(dst), "l"(reinterpret_cast<uint64_t>(tm)), "r"(bar), "r"(c0), "r"(c4), "r"(0), "l"(pol) : "memory");
}
__device__ __forceinline__ void pin(uint32_t& v) { asm volatile("shfl.sync.bfly.b32 %0, %0, 0, 31, -1;" : "+r"(v) :: "memory"); }
__device__ __forceinline__ void pin_u(uint32_t& v) { asm volatile("shfl.sync.idx.b32 %0, %0, 0, 31, -1;" : "+r"(v) :: "memory"); }
template <class T> __device__ __forceinline__ void pin(T*& v) {
    asm volatile("{\n.reg .b32 a, b;\nmov.b64 {a, b}, %0;\nshfl.sync.bfly.b32 a, a, 0, 31, -1;\nshfl.sync.bfly.b32 b, b, 0, 31, -1;\nmov.b64 %0, {a, b};\n}" : "+l"(v) :: "memory");
}
__device__ __forceinline__ void sts16(uint32_t a, uint32_t v) { asm volatile("st.shared.u16 [%0], %1;" ::"r"(a), "h"((unsigned short)v) : "memory"); }
__device__ __forceinline__ void sts32(uint32_t a, float v) { asm volatile("st.shared.f32 [%0], %1;" ::"r"(a), "f"(v) : "memory"); }
__device__ __forceinline__ void sts32(uint32_t a, uint32_t v) { asm volatile("st.shared.u32 [%0], %1;" ::"r"(a), "r"(v) : "memory"); }
__device__ __forceinline__ void sts64(uint32_t a, uint32_t x, uint32_t y) { asm volatile("st.shared.v2.u32 [%0], {%1, %2};" ::"r"(a), "r"(x), "r"(y) : "memory"); }
__device__ __forceinline__ void sts128(uint32_t a, const uint4& v) { asm volatile("st.shared.v4.u32 [%0], {%1, %2, %3, %4};" ::"r"(a), "r"(v.x), "r"(v.y), "r"(v.z), "r"(v.w) : "memory"); }
__device__ __forceinline__ void cons_sync() { asm volatile("bar.sync 1, 256;" ::: "memory"); }
template <int ID> __device__ __forceinline__ void fin_arrive() { asm volatile("bar.arrive %0, 288;" ::"n"(ID) : "memory"); }
template <int ID> __device__ __forceinline__ void fin_sync() { asm volatile("bar.sync %0, 288;" ::"n"(ID) : "memory"); }

__device__ __forceinline__ uint4 lds128(uint32_t a) {
    uint4 v;
    asm volatile("ld.shared.v4.u32 {%0,%1,%2,%3}, [%4];" : "=r"(v.x), "=r"(v.y), "=r"(v.z), "=r"(v.w) : "r"(a) : "memory");
    return v;
}
__device__ __forceinline__ uint4 lds128v(uint32_t a) {
    uint4 v;
    asm volatile("ld.volatile.shared.v4.u32 {%0,%1,%2,%3}, [%4];" : "=r"(v.x), "=r"(v.y), "=r"(v.z), "=r"(v.w) : "r"(a) : "memory");
    return v;
}
__device__ __forceinline__ float4 lds128f(uint32_t a) {
    float4 v;
    asm volatile("ld.shared.v4.f32 {%0,%1,%2,%3}, [%4];" : "=f"(v.x), "=f"(v.y), "=f"(v.z), "=f"(v.w) : "r"(a) : "memory");
    return v;
}
__device__ __forceinline__ uint2 lds64(uint32_t a) {
    uint2 v;
    asm volatile("ld.shared.v2.u32 {%0,%1}, [%2];" : "=r"(v.x), "=r"(v.y) : "r"(a) : "memory");
    return v;
}
__device__ __forceinline__ uint32_t lds32(uint32_t a) {
    uint32_t v;
    asm volatile("ld.shared.u32 %0, [%1];" : "=r"(v) : "r"(a) : "memory");
    return v;
}
__device__ __forceinline__ float sum8(uint32_t a) {
    const float4 x = lds128f(a), y = lds128f(a + 16);
    return ((x.x + x.y) + (x.z + x.w)) + ((y.x + y.y) + (y.z + y.w));
}
__device__ __forceinline__ void ldsm_x4(uint32_t* r, uint32_t a) {
    asm volatile("ldmatrix.sync.aligned.m8n8.x4.shared.b16 {%0,%1,%2,%3}, [%4];"
                 : "=r"(r[0]), "=r"(r[1]), "=r"(r[2]), "=r"(r[3]) : "r"(a) : "memory");
}
__device__ __forceinline__ void ldsm_x4_t(uint32_t* r, uint32_t a) {
    asm volatile("ldmatrix.sync.aligned.m8n8.x4.trans.shared.b16 {%0,%1,%2,%3}, [%4];"
                 : "=r"(r[0]), "=r"(r[1]), "=r"(r[2]), "=r"(r[3]) : "r"(a) : "memory");
}
template <int N, int STRIDE>
__device__ __forceinline__ void ldsm_if(uint32_t* r0, uint32_t* r1, uint32_t* r2, uint32_t a, uint32_t bar, uint32_t& got) {
    if (N == 2)
        asm volatile("{\n.reg .pred p, q;\nsetp.eq.u32 q, %8, 0;\nmbarrier.test_wait.parity.shared::cta.b64 p, [%10], 0;\nand.pred p, p, q;\n"
                     "@p ldmatrix.sync.aligned.m8n8.x4.trans.shared.b16 {%0,%1,%2,%3}, [%9];\n"
                     "@p ldmatrix.sync.aligned.m8n8.x4.trans.shared.b16 {%4,%5,%6,%7}, [%9+%11];\n@p mov.u32 %8, 1;\n}"
                     : "+r"(r0[0]), "+r"(r0[1]), "+r"(r0[2]), "+r"(r0[3]), "+r"(r1[0]), "+r"(r1[1]), "+r"(r1[2]), "+r"(r1[3]), "+r"(got)
                     : "r"(a), "r"(bar), "n"(STRIDE) : "memory");
    else
        asm volatile("{\n.reg .pred p, q;\nsetp.eq.u32 q, %12, 0;\nmbarrier.test_wait.parity.shared::cta.b64 p, [%14], 0;\nand.pred p, p, q;\n"
                     "@p ldmatrix.sync.aligned.m8n8.x4.trans.shared.b16 {%0,%1,%2,%3}, [%13];\n"
                     "@p ldmatrix.sync.aligned.m8n8.x4.trans.shared.b16 {%4,%5,%6,%7}, [%13+%15];\n"
                     "@p ldmatrix.sync.aligned.m8n8.x4.trans.shared.b16 {%8,%9,%10,%11}, [%13+%16];\n@p mov.u32 %12, 1;\n}"
                     : "+r"(r0[0]), "+r"(r0[1]), "+r"(r0[2]), "+r"(r0[3]), "+r"(r1[0]), "+r"(r1[1]), "+r"(r1[2]), "+r"(r1[3]),
                       "+r"(r2[0]), "+r"(r2[1]), "+r"(r2[2]), "+r"(r2[3]), "+r"(got)
                     : "r"(a), "r"(bar), "n"(STRIDE), "n"(2 * STRIDE) : "memory");
}
__device__ __forceinline__ void mma_bf16(float* c, uint32_t a0, uint32_t a1, uint32_t a2, uint32_t a3, uint32_t b0, uint32_t b1) {
    asm volatile("mma.sync.aligned.m16n8k16.row.col.f32.bf16.bf16.f32 {%0,%1,%2,%3}, {%4,%5,%6,%7}, {%8,%9}, {%0,%1,%2,%3};"
                 : "+f"(c[0]), "+f"(c[1]), "+f"(c[2]), "+f"(c[3]) : "r"(a0), "r"(a1), "r"(a2), "r"(a3), "r"(b0), "r"(b1));
}
__device__ __forceinline__ void mma_bf16(float* c, const uint32_t* a, uint32_t b0, uint32_t b1) { mma_bf16(c, a[0], a[1], a[2], a[3], b0, b1); }
__device__ __forceinline__ void zero4(float* c) { c[0] = c[1] = c[2] = c[3] = 0.f; }
__device__ __forceinline__ float bf_lo(uint32_t u) { return __uint_as_float(u << 16); }
__device__ __forceinline__ float bf_hi(uint32_t u) { return __uint_as_float(u & 0xffff0000u); }
__device__ __forceinline__ uint32_t pack_bf(float hi, float lo) { uint32_t r; asm("cvt.rn.bf16x2.f32 %0, %1, %2;" : "=r"(r) : "f"(hi), "f"(lo)); return r; }
__device__ __forceinline__ uint32_t add_bf2(uint32_t a, uint32_t b) { uint32_t r; asm("add.rn.bf16x2 %0, %1, %2;" : "=r"(r) : "r"(a), "r"(b)); return r; }
__device__ __forceinline__ float bfr(float x) { return __uint_as_float(pack_bf(x, 0.f)); }

__device__ __forceinline__ uint32_t in_word(float v) { return __float_as_uint(v); }
__device__ __forceinline__ void st1(void* p, uint32_t v) {
    asm volatile("st.relaxed.gpu.global.u32 [%0], %1;" ::"l"(p), "r"(v) : "memory");
}
__device__ __forceinline__ void st16(void* p, uint32_t v) {
    asm volatile("st.relaxed.gpu.global.u16 [%0], %1;" ::"l"(p), "h"((unsigned short)v) : "memory");
}
__device__ __forceinline__ void st2(void* p, uint32_t a, uint32_t b) {
    asm volatile("st.relaxed.gpu.global.v2.u32 [%0], {%1, %2};" ::"l"(p), "r"(a), "r"(b) : "memory");
}
__device__ __forceinline__ void st4(void* p, uint32_t a, uint32_t b, uint32_t c, uint32_t d) {
    asm volatile("st.relaxed.gpu.global.v4.u32 [%0], {%1, %2, %3, %4};" ::"l"(p), "r"(a), "r"(b), "r"(c), "r"(d) : "memory");
}
__device__ __forceinline__ uint32_t ld1(const void* p) {
    uint32_t v;
    asm volatile("ld.relaxed.gpu.global.u32 %0, [%1];" : "=r"(v) : "l"(p) : "memory");
    return v;
}
__device__ __forceinline__ uint2 ld2(const void* p) {
    uint2 v;
    asm volatile("ld.relaxed.gpu.global.v2.u32 {%0, %1}, [%2];" : "=r"(v.x), "=r"(v.y) : "l"(p) : "memory");
    return v;
}
__device__ __forceinline__ uint4 ld4(const void* p) {
    uint4 v;
    asm volatile("ld.relaxed.gpu.global.v4.u32 {%0, %1, %2, %3}, [%4];" : "=r"(v.x), "=r"(v.y), "=r"(v.z), "=r"(v.w) : "l"(p) : "memory");
    return v;
}
__device__ __forceinline__ void ld2p(const void* p, uint2& v, bool on) {
    asm volatile("{\n.reg .pred q;\nsetp.ne.u32 q, %3, 0;\n@q ld.relaxed.gpu.global.v2.u32 {%0, %1}, [%2];\n}"
                 : "+r"(v.x), "+r"(v.y) : "l"(p), "r"((uint32_t)on) : "memory");
}
__device__ __forceinline__ void poll2(const void* p, uint2& v) {
    asm volatile("{\n.reg .pred q, r;\nsetp.nan.bf16x2 q|r, %0, %1;\nor.pred q, q, r;\n@q ld.relaxed.gpu.global.v2.u32 {%0, %1}, [%2];\n}"
                 : "+r"(v.x), "+r"(v.y) : "l"(p) : "memory");
}
__device__ __forceinline__ bool ok8(const uint4& v) {
    const uint32_t m = __vimax3_u16x2(__vimax3_u16x2(v.x, v.y, v.z), v.w, v.w);
    return __vimax3_u16x2(m, m << 16, m >> 16) != SENT;
}
__device__ __forceinline__ void poll4(const void* p, uint4& v) {
    asm volatile("{\n.reg .pred q;\n.reg .u32 m;\nmax.u32 m, %0, %1;\nmax.u32 m, m, %2;\nmax.u32 m, m, %3;\nsetp.eq.u32 q, m, 0xffffffff;\n"
                 "@q ld.relaxed.gpu.global.v4.u32 {%0, %1, %2, %3}, [%4];\n}"
                 : "+r"(v.x), "+r"(v.y), "+r"(v.z), "+r"(v.w) : "l"(p) : "memory");
}
__device__ __forceinline__ uint32_t max4(const uint4& v) { return max(max(v.x, v.y), max(v.z, v.w)); }
__device__ __forceinline__ void pkt_st2(uint4* p, float a, float b, uint32_t tag) {
    asm volatile("st.relaxed.gpu.global.v2.b64 [%0], {%1, %2};" ::"l"(p), "l"(((uint64_t)tag << 32) | __float_as_uint(a)), "l"(((uint64_t)tag << 32) | __float_as_uint(b)) : "memory");
}
__device__ __forceinline__ void pkt_ld2(const uint4* p, uint64_t& a, uint64_t& b) {
    asm volatile("ld.relaxed.gpu.global.v2.b64 {%0, %1}, [%2];" : "=l"(a), "=l"(b) : "l"(p) : "memory");
}
__device__ __forceinline__ bool tag_ok(uint64_t v, uint32_t tag) { return (uint32_t)(v >> 32) == tag; }
__device__ __forceinline__ float val_of(uint64_t v) { return __uint_as_float((uint32_t)v); }

__device__ __forceinline__ float warp_sum(float v) {
#pragma unroll
    for (int o = 16; o > 0; o >>= 1) v += __shfl_xor_sync(0xffffffffu, v, o);
    return v;
}
__device__ __forceinline__ float warp_max(float v) {
#pragma unroll
    for (int o = 16; o > 0; o >>= 1) v = fmaxf(v, __shfl_xor_sync(0xffffffffu, v, o));
    return v;
}
__device__ __forceinline__ float sqrt_fast(float x) { float r; asm("sqrt.approx.ftz.f32 %0, %1;" : "=f"(r) : "f"(x)); return r; }
__device__ __forceinline__ float rcp_fast(float x) { float r; asm("rcp.approx.ftz.f32 %0, %1;" : "=f"(r) : "f"(x)); return r; }
__device__ __forceinline__ float ex2(float x) { float r; asm("ex2.approx.ftz.f32 %0, %1;" : "=f"(r) : "f"(x)); return r; }
constexpr float L2E = 1.4426950408889634f;
__device__ __forceinline__ void ln_finish(float s1, float s2, float& mean_b, float& inv_den) {
    const float mean = s1 * (1.0f / D_MODEL);
    const float var = fmaxf(fmaf(-mean, mean, s2 * (1.0f / D_MODEL)), 0.f);
    mean_b = bfr(mean);
    inv_den = rcp_fast(bfr(sqrt_fast(bfr(bfr(var) + 1e-5f))));
}
__device__ __forceinline__ uint32_t ln_apply2(uint32_t u, float mean_b, float inv_den) {
    const uint32_t d = pack_bf(bf_hi(u) - mean_b, bf_lo(u) - mean_b);
    return pack_bf(bf_hi(d) * inv_den, bf_lo(d) * inv_den);
}
__device__ __forceinline__ void ln_acc(uint32_t u, float& s1, float& s2) {
    const float a = bf_lo(u), b = bf_hi(u);
    s1 += a + b;
    s2 = fmaf(a, a, fmaf(b, b, s2));
}
__device__ __forceinline__ float silu_b(float g) { return bfr(__fdividef(g, 1.0f + ex2(-g * L2E))); }

#define STAMP(i) do { } while (0)

struct KParams {
    const __nv_bfloat16* wq;
    const __nv_bfloat16* x;
    __nv_bfloat16* out;
    Scratch* sc;
    unsigned char* xa;
    int t_k0, per, stag;
    int target;
    int t_q, t_fill;
    uint32_t item[32];
    uint32_t role[NCTA];
};
struct TMaps { CUtensorMap k, v, wo, w1, w3, w2; };

__global__ void __launch_bounds__(NTHREADS, 1)
fused_decode_kernel(const __grid_constant__ KParams p, const __grid_constant__ TMaps tm) {
    extern __shared__ __align__(1024) unsigned char smem[];
    const int tid = threadIdx.x;
    const int b = blockIdx.x;
    const int head = b >> 2, sp = b & 3;
    {
        const char* a = reinterpret_cast<const char*>(p.wq) + (uint32_t)((sp * 160 + (tid >> 2)) * (NHEAD * DH * 2) + head * (DH * 2) + (tid & 3) * 128);
        asm volatile("prefetch.global.L2 [%0];" ::"l"(a) : "memory");
    }
    if (tid < 256) {
        const uint32_t r = tid >> 3, ch = tid & 7;
        const char* src = reinterpret_cast<const char*>(p.wq) + ((sp * 160 + r) * (NHEAD * DH * 2) + head * (DH * 2) + ch * 16);
#pragma unroll
        for (int i = 0; i < NQT; i++) {
#pragma unroll
            for (int j = 0; j < 3; j++)
                asm volatile("cp.async.cg.shared.global [%0], [%1], 16;"
                             ::"r"(sbase + (QSLOT + i) * TILE_BYTES + (3 * r + j) * 128 + ((ch ^ ((3 * r + j) & 7)) << 4)),
                               "l"(src + (size_t)i * 32 * (NHEAD * DH * 2) + j * 128) : "memory");
        }
    }
    const uint32_t t0 = now_ns();
    const int warp = __shfl_sync(0xffffffffu, tid >> 5, 0), lane = tid & 31;
    const uint32_t role = p.role[b];
    const int kg = role >> 3 & 7, ng = role >> 6 & 31;
    const int u1 = role >> 11 & 127, u2 = role >> 18;
    const bool has_wo = role & 1, has_f1 = role & 2, has_f2 = role & 4;
    constexpr uint32_t bar_full = sbase + SM_BAR;
    constexpr uint32_t bar_empty = sbase + SM_BAR + 128;
    constexpr uint32_t bar_tail = sbase + SM_BAR + 256;
    constexpr uint32_t bar_scale = bar_tail + 8 * NTAIL;
    constexpr uint32_t bar_stat = bar_scale + 8;
    constexpr uint32_t bar_up = bar_scale + 16;

    if (warp == 8) {
        if (smem_u32(smem) != sbase) __trap();
        uint64_t pol;
        asm volatile("createpolicy.fractional.L2::evict_first.b64 %0, 1.0;" : "=l"(pol));
        sts32(sbase + SM_LATE + (lane & 7) * 4, 0u);
        if (lane == 0) {
#pragma unroll
            for (int i = 0; i < 32 + NTAIL + 3; i++)
                mbar_init(bar_full + 8 * i, (i >= 16 && i < 32) || i > 32 + NTAIL ? 8 : i == 32 + NWP ? NA : i == 33 + NWP ? 5 - NA : i == 34 + NWP ? NB : i == 35 + NWP ? 5 - NB : 1);
#pragma unroll
            for (int i = 0; i < 6; i++) asm volatile("prefetch.tensormap [%0];" ::"l"(reinterpret_cast<uint64_t>(&tm.k + i)) : "memory");
            asm volatile("fence.mbarrier_init.release.cluster;" ::: "memory");
        }
        __syncwarp();
        asm volatile("bar.arrive 2, 320;" ::: "memory");
        int slip = 0;
        if (lane == 0) {
            if (b == 0) { st4(p.sc->late, 0, 0, 0, 0); st4(p.sc->late + 4, 0, 0, 0, 0); }
            const int tile0 = (head * SK + (SK - WIN)) / 32 + sp;
            uint32_t tn = t0 + p.t_k0 + sp * p.stag, tw = tn, acc = 0;
            int w = 0;
#pragma unroll 1
            for (int n = 0; n < 2 * NKT; n++) {
                const int slot = n & (NSLOT - 1);
                mbar_wait(bar_empty + 8 * slot, (((n + NQT) >> 4) & 1) ^ 1);
                mbar_expect_tx(bar_full + 8 * slot, TILE_BYTES);
                uint32_t t;
                do {
                    t = now_ns();
                    if (mbar_test(bar_full + 8 * (w & (NSLOT - 1)), (w >> 4) & 1)) {
                        acc += t - tw;
                        tw += p.per;
                        if ((++w & 7) == 0) {
                            asm volatile("red.relaxed.gpu.global.add.u32 [%0], %1;" ::"l"(p.sc->late + (w >> 3)), "r"((1u << 24) + min(max((int)acc >> 3, 0), 65535)) : "memory");
                            acc = 0;
                        }
                    }
                } while ((int)(t - tn) < slip || w <= n - INFLIGHT);
                tma_load(sbase + slot * TILE_BYTES, &tm.k + (n >> 5), 0, tile0 + (n & (NKT - 1)) * 4, bar_full + 8 * slot, pol);
                tn += p.per;
                if ((n & 7) == 5)
                    asm volatile("cp.async.cg.shared.global [%0], [%1], 16;\ncp.async.cg.shared.global [%0+16], [%1+16], 16;" ::"r"(sbase + SM_LATE), "l"(p.sc->late) : "memory");
                uint32_t rep = lds32(sbase + SM_LATE + (n >> 3) * 4);
                if (!(rep >> 30)) rep = lds32(sbase + SM_LATE + (max(n - 8, 0) >> 3) * 4);
                if (rep >> 30) slip = max((int)((float)(rep & 0xffffffu) * rcp_fast((float)(rep >> 24))) - p.target, -500);
            }
        }
        const int seg = (lane >= NWP) + (lane >= NWP + NP1), i = lane - (seg == 0 ? 0 : seg == 1 ? NWP : NWP + NP1);
        const bool todo = lane < NITEM && (role >> seg & 1);
        const uint32_t len = seg == 1 ? 4096 : 8192, dst = sbase + (seg == 0 ? 0 : seg == 1 ? SM_W1 : SM_W2) + i * len;
        const int w3 = seg == 1 && i >= 5;
        const CUtensorMap* m = &tm.wo + (seg == 2 ? 3 : seg + w3);
        const int c0 = seg == 0 ? ng * 32 : seg == 1 ? u1 * 16 : u2 * 16;
        const int c4 = (seg == 0 ? kg * 64 : w3 * -40) + i * 8;
        const uint32_t bar = bar_tail + 8 * (seg == 0 ? i : seg == 1 ? NWP + (i >= NA) + w3 + (i >= 5 + NB) : NWP + NF1 + i);
        const uint32_t tn = (__shfl_sync(0xffffffffu, t0 + slip, 0) + p.item[lane]) | 1;
        if (todo) mbar_expect_tx(bar, len);
#pragma unroll 1
        for (int ph = 0; ph < 2; ph++) {
            mbar_wait(bar_empty + 8 * (ph ? 12 : 5), ph ^ 1);
            uint32_t due = todo && (seg != 0) == ph ? tn : 0;
            while (__any_sync(0xffffffffu, due)) {
                if (due && (int)(now_ns() - due) >= 0) {
                    tma_load(dst, m, c0, c4, bar, pol);
                    due = 0;
                }
            }
        }
    } else if (warp == 9) {
        const uint32_t tag = ld1(&p.sc->epoch) + 1;
        const uint32_t aoff = XA_A + (u1 >> 1 & 7) * 384 + (u1 >> 4) * 64 + (u1 & 1) * 32, hoff = xa_h(kg) + (ng & 3) * 512 + (ng >> 2) * 32;
        sts32(sbase + SM_ONE + (lane & 15) * 4, 0x3f803f80u);
        const uint32_t ooff = xa_o(head) + sp * (DH * 4);
        unsigned char* slot[4] = {p.xa + (ooff + lane * 16), p.xa + ((ooff + 512 + (lane & 15) * 16) ^ (lane >> 4) << 12), p.xa + ((ooff + lane * 16) ^ 4096),
                                  p.xa + (lane < 16 ? (has_wo ? hoff + (lane >> 2 & 1) * 4096 + (lane >> 1 & 1) * 256 + (lane & 1) * 16 : ooff) : has_f1 ? aoff + (lane >> 1 & 1) * 4096 + (lane & 1) * 16 : ooff)};
#pragma unroll
        for (int i = 0; i < 2; i++) st4(p.sc->qbuf + b * 96 + i * 32 + lane * 2, 0, 0, 0, 0);
        sts32(sbase + SM_MISC, tag);
        asm volatile("bar.sync 2, 320;" ::: "memory");
        while (!mbar_test(bar_stat, 0)) __nanosleep(200);
        const float4 ma = lds128f(sbase + SM_MAX), mb = lds128f(sbase + SM_MAX + 16);
        const float m = fmaxf(fmaxf(fmaxf(ma.x, ma.y), fmaxf(ma.z, ma.w)), fmaxf(fmaxf(mb.x, mb.y), fmaxf(mb.z, mb.w)));
        while ((int)(now_ns() - (t0 + p.t_fill)) < 0) __nanosleep(200);
        pkt_st2(p.sc->mbuf + b * 2 + (lane & 1), m, sum8(sbase + SM_SUM), tag);
#pragma unroll
        for (int i = 0; i < 4; i++) st4(slot[i], SENT, SENT, SENT, SENT);
        uint32_t ack = SENT;
#pragma unroll
        for (int i = 0; i < 4; i++) { uint32_t v; asm volatile("atom.relaxed.gpu.global.exch.b32 %0, [%1], -1;" : "=r"(v) : "l"(slot[i]) : "memory"); ack &= v; }
        if (__any_sync(0xffffffffu, ack != SENT)) __trap();
        if (lane == 0) st1(p.sc->ready + b, tag);
        int vote = 0;
#pragma unroll 1
        for (int r = 0; r < 5 && (!vote || (int)(now_ns() - (t0 + p.t_fill)) < 3500); r++) {
            __nanosleep(100);
            uint32_t d;
            asm volatile("{\n.reg .pred p, q;\n.reg .b32 a, b, c0, c1;\nmov.b32 c0, 0;\nmov.b32 c1, 0;\n"
                         "atom.relaxed.gpu.global.exch.b32 a, [%1], -1;\natom.relaxed.gpu.global.exch.b32 b, [%2], -1;\n"
                         "setp.eq.u32 p, a, -1;\n@p mov.u32 c0, %%clock;\nsetp.eq.u32 q, b, -1;\n@q mov.u32 c1, %%clock;\nsub.u32 %0, c1, c0;\n}"
                         : "=r"(d) : "l"(r & 1 ? slot[2] : slot[0]), "l"(r & 1 ? slot[0] : slot[2]) : "memory");
            vote += (d > 90) == (r & 1) ? 1 : -1;
        }
        const uint32_t side = __shfl_sync(0xffffffffu, vote, 0) > 0;
        uint32_t n = 0;
        {
            uint64_t em, el;
            while (true) {
                const uint4 e = ld4(p.sc->ready + lane * 4);
                pkt_ld2(p.sc->mbuf + (head * 4 + (lane & 3)) * 2, em, el);
                if (__all_sync(0xffffffffu, e.x == tag && e.y == tag && e.z == tag && e.w == tag && tag_ok(em, tag) && tag_ok(el, tag))) break;
                __nanosleep(500);
                if (++n > SPIN_LIMIT) __trap();
            }
            float M = fmaxf(val_of(em), __shfl_xor_sync(0xffffffffu, val_of(em), 1));
            M = fmaxf(M, __shfl_xor_sync(0xffffffffu, M, 2));
            float L = ex2((val_of(em) - M) * L2E) * val_of(el);
            L += __shfl_xor_sync(0xffffffffu, L, 1);
            L += __shfl_xor_sync(0xffffffffu, L, 2);
            if (lane == 0) {
                sts64(sbase + SM_MISC + 8, __float_as_uint(__fdividef(ex2((m - M) * L2E), L)), side);
                mbar_arrive(bar_scale);
                if (b == 0) p.sc->epoch = tag;
            }
        }
        unsigned char* hdst = p.xa + (hoff + (side ^ 1) * 4096 + (lane >> 4) * 256 + (lane & 15) * 2);
        unsigned char* hdst2 = p.xa + (hoff + side * 4096 + (lane >> 4) * 256 + (lane & 15) * 2);
        unsigned char* adst = p.xa + (aoff + (lane >> 4) * 4096 + (lane & 15) * 2);
        __nv_bfloat16* odst = p.out + u2 * 16 + (lane & 15);
        uint32_t r0 = sbase + SM_RED + lane * 48, r1 = sbase + SM_RED + (lane & 15) * 48;
        uint32_t res;
        asm volatile("ld.global.nc.u16 %0, [%1];" : "=r"(res) : "l"(p.x + u2 * 16 + (lane & 15)));
        pin(hdst); pin(hdst2); pin(adst); pin(odst); pin(r0); pin(r1);
        if (has_wo) {
            fin_sync<3>();
            const uint32_t v = pack_bf(0.f, sum8(r0));
            st16(hdst, v); st16(hdst2, v);
            STAMP(4);
        }
        if (has_f1) {
            fin_sync<4>();
            float mean_b, inv_den;
            ln_finish(sum8(sbase + SM_LN), sum8(sbase + SM_LN + 32), mean_b, inv_den);
            const float gr = fmaf(-mean_b, sum8(r1 + 48 * 48), sum8(r1 + 32 * 48)) * inv_den;
            mbar_wait_after(bar_up, r0, gr);
            const float gs = bfr(gr);
            const float up = bfr(fmaf(-mean_b, sum8(r1 + 80 * 48), sum8(r1 + 64 * 48)) * inv_den);
            st16(adst, pack_bf(0.f, silu_b(gs) * up));
            if (b == 0 && lane < 8) st1(p.sc->late + lane, 0);
            STAMP(8);
        }
        if (has_f2) {
            mbar_wait(bar_tail + 8 * (NWP + NF1 + CFG_HG), 0);
            const unsigned char* hsrc = p.xa + ((lane >> 4) * (1 << 14) + side * 4096 + (u2 & 7) * 256 + (u2 >> 3) * 32 + (lane & 15) * 2);
            uint32_t e[3];
            do {
#pragma unroll
                for (int i = 0; i < 3; i++) asm volatile("ld.relaxed.gpu.global.u16 %0, [%1];" : "=r"(e[i]) : "l"(hsrc + xa_h(2 * i)) : "memory");
                if (++n > SPIN_LIMIT) __trap();
            } while (__any_sync(0xffffffffu, max(max(e[0], e[1]), e[2]) == 0xffffu));
            float f[3];
#pragma unroll
            for (int i = 0; i < 3; i++) f[i] = bf_lo(e[i]) + bf_lo(__shfl_xor_sync(0xffffffffu, e[i], 16));
            res = add_bf2(res, pack_bf(0.f, (f[0] + f[1]) + f[2]));
            pin(res);
            fin_sync<6>();
            asm volatile("st.global.u16 [%0], %1;" ::"l"(odst), "h"((unsigned short)add_bf2(res, pack_bf(0.f, sum8(r1 + 96 * 48)))) : "memory");
            STAMP(11);
        }
    } else {
        const int g = lane >> 2, t = lane & 3;
        uint2 xres;
        {
            uint32_t xr;
            uint2 xu[5];
            const char* xb = reinterpret_cast<const char*>(p.x);
            asm volatile("ld.global.nc.u16 %0, [%1];" : "=r"(xr) : "l"(xb + (sp * 160 + min(tid, 159)) * 2));
#pragma unroll
            for (int i = 0; i < 5; i++) asm volatile("ld.global.nc.v2.u32 {%0, %1}, [%2];" : "=r"(xu[i].x), "=r"(xu[i].y) : "l"(xb + i * 256 + lane * 8));
            asm volatile("ld.global.nc.v2.u32 {%0, %1}, [%2];" : "=r"(xres.x), "=r"(xres.y) : "l"(xb + min(g, 4) * 256 + warp * 32 + t * 8));
            if (lane >= 20) xres.x = xres.y = 0;
            float s1 = 0.f, s2 = 0.f, mean_b, inv_den;
#pragma unroll
            for (int i = 0; i < 5; i++) { ln_acc(xu[i].x, s1, s2); ln_acc(xu[i].y, s1, s2); }
            ln_finish(warp_sum(s1), warp_sum(s2), mean_b, inv_den);
            sts16(sbase + SM_P + warp * 64 + ((lane >> 1 & 3) * 8 + (lane >> 3) * 2 + (lane & 1)) * 2, ln_apply2(xr, mean_b, inv_den));
            asm volatile("cp.async.wait_all;" ::: "memory");
            asm volatile("bar.sync 2, 320;" ::: "memory");
        }
        STAMP(0);
        uint32_t va[3];
#pragma unroll
        for (int i = 0; i < 3; i++) {
            const int cc = 3 * warp + i, row = 3 * lane + (cc >> 3);
            va[i] = sbase + row * 128 + (((cc ^ row) & 7) << 4);
        }
        const int gi = g >= 3 ? g - 3 : g;
        unsigned char* odst = p.xa + ((xa_o(head) ^ (g >= 3 ? 4096 : 0)) + (sp * DH + warp * 24 + gi * 8 + t * 2) * 4);
        pin(odst);

#pragma unroll 1
        for (int ph = 0; ph < 2; ph++) {
            if (ph == 1) {
                uint4 qf[6];
#pragma unroll
                for (int i = 0; i < 6; i++) qf[i] = lds128(sbase + SM_Q + t * 96 + i * 16);
                uint32_t ka[3];
#pragma unroll
                for (int j = 0; j < 3; j++) {
                    const int row = 3 * (lane & 15) + j;
                    ka[j] = sbase + row * 128 + ((((lane >> 4) ^ row) & 7) << 4) + warp * TILE_BYTES;
                }
                float s[4] = {0.f, 0.f, 0.f, 0.f};
#pragma unroll 1
                for (int it = 0; it < 4; it++) {
                    const int slot = (it & 1) * 8 + warp;
                    const uint32_t so = (it & 1) * 8 * TILE_BYTES;
                    float c[2][2][4];
                    zero4(c[0][0]); zero4(c[0][1]); zero4(c[1][0]); zero4(c[1][1]);
                    mbar_wait(bar_full + 8 * slot, it >> 1);
#pragma unroll
                    for (int ks = 0; ks < 12; ks++) {
                        const uint32_t a = (ka[ks >> 2] + so) ^ ((ks & 3) << 5);
                        uint32_t f0[4], f1[4];
                        ldsm_x4(f0, a); ldsm_x4(f1, a + 16 * DH * 2);
                        const uint32_t b0 = ks & 1 ? qf[ks >> 1].z : qf[ks >> 1].x, b1 = ks & 1 ? qf[ks >> 1].w : qf[ks >> 1].y;
                        mma_bf16(c[0][ks & 1], f0, b0, b1); mma_bf16(c[1][ks & 1], f1, b0, b1);
                    }
                    if (lane == 0) mbar_arrive8(bar_empty + 8 * slot);
                    const float v = t & 2 ? (t & 1 ? c[1][0][2] + c[1][1][2] : c[1][0][0] + c[1][1][0]) : (t & 1 ? c[0][0][2] + c[0][1][2] : c[0][0][0] + c[0][1][0]);
                    s[0] = s[1]; s[1] = s[2]; s[2] = s[3];
                    s[3] = bfr(bfr(v) * 0.07216878364870322f);
                }
                const float mw = warp_max(fmaxf(fmaxf(s[0], s[1]), fmaxf(s[2], s[3])));
                if (lane == 0) sts32(sbase + SM_MAX + warp * 4, mw);
                cons_sync();
                const float4 ma = lds128f(sbase + SM_MAX), mb = lds128f(sbase + SM_MAX + 16);
                const float m = fmaxf(fmaxf(fmaxf(ma.x, ma.y), fmaxf(ma.z, ma.w)), fmaxf(fmaxf(mb.x, mb.y), fmaxf(mb.z, mb.w)));
                float l = 0.f;
#pragma unroll
                for (int it = 0; it < 4; it++) {
                    const float e = ex2((s[it] - m) * L2E);
                    l += e;
                    sts16(sbase + SM_P + (it * 8 + warp) * 64 + ((g >> 1) * 8 + t * 2 + (g & 1)) * 2, pack_bf(0.f, e));
                }
                l = warp_sum(l);
                if (lane == 0) { sts32(sbase + SM_SUM + warp * 4, l); mbar_arrive(bar_stat); }
                cons_sync();
                STAMP(1);
            }
            float acc[2][3][4];
#pragma unroll
            for (int i = 0; i < 3; i++) { zero4(acc[0][i]); zero4(acc[1][i]); }
            const int nt = ph ? NKT : NQT;
            float scale = 1.f;
#pragma unroll 1
            for (int n = 0; n < nt; n++) {
                const int slot = ph ? (n & (NSLOT - 1)) : QSLOT + n;
                const uint4 w = lds128(sbase + SM_P + n * 64 + t * 16);
                if (n == NKT - 1) { mbar_wait(bar_scale, 0); scale = __uint_as_float(lds32(sbase + SM_MISC + 8)); }
                if (ph) mbar_wait(bar_full + 8 * slot, (n >> 4) & 1);
                uint32_t f[3][4];
#pragma unroll
                for (int i = 0; i < 3; i++) ldsm_x4_t(f[i], va[i] + slot * TILE_BYTES);
#pragma unroll
                for (int i = 0; i < 3; i++) {
                    mma_bf16(acc[0][i], w.x, w.x, w.y, w.y, f[i][0], f[i][1]);
                    mma_bf16(acc[1][i], w.z, w.z, w.w, w.w, f[i][2], f[i][3]);
                }
                if (lane == 0) mbar_arrive(bar_empty + 8 * slot);
            }
            const float v0 = (gi == 0 ? acc[0][0][0] + acc[1][0][0] : gi == 1 ? acc[0][1][0] + acc[1][1][0] : acc[0][2][0] + acc[1][2][0]) * scale;
            const float v1 = (gi == 0 ? acc[0][0][1] + acc[1][0][1] : gi == 1 ? acc[0][1][1] + acc[1][1][1] : acc[0][2][1] + acc[1][2][1]) * scale;
            if (ph == 1) {
                if (g < 6) st2(odst, in_word(v0), in_word(v1));
                break;
            }
            const uint32_t tag = lds32(sbase + SM_MISC);
            const uint32_t t4 = tag % 15 + 1;
            if (g < 3) st2(p.sc->qbuf + b * 96 + warp * 12 + lane, (__float_as_uint(v0) & ~15u) | t4, (__float_as_uint(v1) & ~15u) | t4);
            if (warp < 3) {
                uint2 e[4];
                uint32_t n = 0, bad;
#pragma unroll 1
                do {
                    do __nanosleep(200); while ((int)(now_ns() - (t0 + p.t_q)) < 0);
                    bad = 0;
#pragma unroll
                    for (int i = 0; i < 4; i++) e[i] = ld2(p.sc->qbuf + (head * 4 + i) * 96 + tid);
#pragma unroll
                    for (int i = 0; i < 4; i++) { e[i].x ^= t4; e[i].y ^= t4; bad |= e[i].x | e[i].y; }
                    if (++n > SPIN_LIMIT) __trap();
                } while (__any_sync(0xffffffffu, bad & 15));
#define S_(c) ((__uint_as_float(e[0].c) + __uint_as_float(e[1].c)) + (__uint_as_float(e[2].c) + __uint_as_float(e[3].c)))
                sts32(sbase + SM_Q + (t * 24 + (tid >> 2)) * 4, pack_bf(S_(y), S_(x)));
#undef S_
            }
            cons_sync();
        }
        STAMP(2);
        const uint32_t side = lds32(sbase + SM_MISC + 12) * 4096;
        const uint32_t d16 = kg * 64 + g * 8 + warp, oh = d16 / 12;
        const unsigned char* osrc = p.xa + ((xa_o(oh) ^ side) + ((d16 - oh * 12) * 16 + t * 4) * 4);
        const int r16 = (lane & 7) + ((lane >> 4) << 3), mi = lane >> 3 & 1;
        const uint32_t f32 = sbase + r16 * 32 + ((mi ^ (lane >> 2 & 1)) << 4);
        uint32_t rdst = sbase + SM_RED + (t * 8 + g) * 48 + warp * 4;
        uint32_t bl = sbase + SM_BC + warp * 512 + t * 80, bs = bl + g * 8;
        uint32_t hl = g < 4 ? bl : sbase + SM_ONE;
        uint32_t w1a = f32 + SM_W1 + warp * 512, w2a = f32 + SM_W2 + warp * 1024;
        uint32_t lnd = lane < 2 ? sbase + SM_LN + lane * 32 + warp * 4 : sbase + SM_BC + warp * 512 + 384 + lane * 4;
        const unsigned char* hs = p.xa + (side + warp * 256 + lane * 8);
        const unsigned char* as = p.xa + (XA_A + side + warp * 384 + min(lane, 23) * 16);
        uint32_t al = sbase + SM_BC + warp * 512 + t * 16, at = sbase + SM_BC + warp * 512 + lane * 16;
        uint32_t fl = role, ln = lane;
        pin_u(fl); pin(ln);
        const bool f1 = fl & 2, f2 = fl & 4, odd = ln & 1, first = ln == 0;
        constexpr uint32_t b2 = bar_tail + 8 * (NWP + NF1);
        pin(rdst); pin(bs); pin(hl); pin(w1a); pin(w2a); pin(lnd); pin(hs); pin(as); pin(al); pin(at);
#define F_(i, c) __uint_as_float(e[i].c)
        if (has_wo) {
            uint4 e[4];
#pragma unroll
            for (int i = 0; i < 4; i++) e[i].x = e[i].y = e[i].z = e[i].w = SENT;
            uint32_t n = 0;
            mbar_wait(bar_tail + 8 * CFG_OG, 0);
#pragma unroll 1
            do {
                if (CFG_OSL && n) __nanosleep(CFG_OSL);
#pragma unroll
                for (int i = 0; i < 4; i++) poll4(osrc + i * (DH * 4), e[i]);
                if (++n > SPIN_LIMIT) __trap();
            } while (__any_sync(0xffffffffu, max(max(max4(e[0]), max4(e[1])), max(max4(e[2]), max4(e[3]))) == SENT));
            sts64(bs, pack_bf((F_(0, y) + F_(1, y)) + (F_(2, y) + F_(3, y)), (F_(0, x) + F_(1, x)) + (F_(2, x) + F_(3, x))),
                      pack_bf((F_(0, w) + F_(1, w)) + (F_(2, w) + F_(3, w)), (F_(0, z) + F_(1, z)) + (F_(2, z) + F_(3, z))));
            __syncwarp();
#pragma unroll
            for (int i = 0; i < 4; i++) e[i] = lds128(bl + i * 16);
            STAMP(3);
            const uint32_t wa = sbase + (warp * 16 + r16) * 64 + ((mi ^ (r16 >> 1 & 3)) << 4), wb = wa ^ 32;
            float c0[4], c1[4];
            zero4(c0); zero4(c1);
#pragma unroll
            for (int j = 0; j < NWP; j++) {
                mbar_wait(bar_tail + 8 * j, 0);
                uint32_t f0[4], f1[4];
                ldsm_x4_t(f0, wa + j * 8192); ldsm_x4_t(f1, wb + j * 8192);
                const uint32_t b0 = j & 1 ? e[j >> 1].z : e[j >> 1].x, b1 = j & 1 ? e[j >> 1].w : e[j >> 1].y;
                mma_bf16(c0, f0, b0, b1); mma_bf16(c1, f1, b0, b1);
            }
            sts32(rdst, t & 2 ? (t & 1 ? c1[2] : c1[0]) : (t & 1 ? c0[2] : c0[0]));
            fin_arrive<3>();
        }
        if (f1) {
            constexpr uint32_t b1 = bar_tail + 8 * NWP;
            uint32_t a1[5][4], a3[5][4];
            uint2 e[NG];
#pragma unroll
            for (int i = 0; i < NG; i++) e[i].x = e[i].y = 0;
            uint32_t got = 0, n = 0;
#pragma unroll
            for (int i = 0; i < NB; i++) a3[i][0] = a3[i][1] = a3[i][2] = a3[i][3] = 0;
            mbar_wait(b1, 0);
#pragma unroll
            for (int i = 0; i < NG; i++) ld2p(hs + xa_h(i), e[i], lane < 20);
            mbar_wait(b1 + 8, 0);
#pragma unroll
            for (int i = 0; i < 5; i++) ldsm_x4_t(a1[i], w1a + i * 4096);
            uint4 hb0, hb1;
            uint2 hb2;
            float sv[4];
#pragma unroll 1
            while (true) {
#define S_(f, c) (((f(e[0].c) + f(e[1].c)) + (f(e[2].c) + f(e[3].c))) + (f(e[4].c) + f(e[5].c)))
                const float sx = S_(bf_lo, x), sy = S_(bf_hi, x), sz = S_(bf_lo, y), sw = S_(bf_hi, y), sa = (sx + sy) + (sz + sw);
#undef S_
                const uint32_t h0 = add_bf2(xres.x, pack_bf(sy, sx)), h1 = add_bf2(xres.y, pack_bf(sw, sz));
                sts64(bs, h0, h1);
                __syncwarp();
                hb0 = lds128(hl); hb1 = lds128(hl + 16); hb2 = lds64(hl + 32);
                const float a = bf_lo(h0), b = bf_hi(h0), c = bf_lo(h1), d = bf_hi(h1);
                const float s1 = (a + b) + (c + d), s2 = fmaf(a, a, b * b) + fmaf(c, c, d * d);
                sv[0] = odd ? s2 : s1;
                sv[1] = __shfl_xor_sync(0xffffffffu, odd ? s1 : s2, 1);
                sv[2] = __shfl_xor_sync(0xffffffffu, sv[0], 2);
                sv[3] = __shfl_xor_sync(0xffffffffu, odd ? s1 : s2, 3);
                bool miss = __any_sync(0xffffffffu, sa != sa);
                if (n == 0) STAMP(12);
                if (miss) {
                    const uint4 mx = make_uint4(__vimax3_u16x2(e[0].x, e[0].y, e[1].x), __vimax3_u16x2(e[1].y, e[2].x, e[2].y),
                                                __vimax3_u16x2(e[3].x, e[3].y, e[4].x), __vimax3_u16x2(e[4].y, e[5].x, e[5].y));
#pragma unroll
                    for (int i = 0; i < NG; i++) poll2(hs + xa_h(i), e[i]);
                    ldsm_if<NB, 4096>(a3[0], a3[1], a3[2], w1a + (SM_W3 - SM_W1), b1 + 16, got);
                    if (++n > SPIN_LIMIT) __trap();
                    miss = __any_sync(0xffffffffu, !ok8(mx));
                }
                if (!miss) break;
            }
            STAMP(5);
            float cg[3][4], cu[3][4];
#pragma unroll
            for (int i = 0; i < 3; i++) { zero4(cg[i]); zero4(cu[i]); }
            const uint32_t hb[5][2] = {{hb0.x, hb0.y}, {hb0.z, hb0.w}, {hb1.x, hb1.y}, {hb1.z, hb1.w}, {hb2.x, hb2.y}};
            const float st = (sv[0] + sv[1]) + (sv[2] + sv[3]);
#pragma unroll
            for (int i = 0; i < 4; i++) sv[i] = __shfl_down_sync(0xffffffffu, st, 4 * i + 4);
#pragma unroll
            for (int i = 0; i < 5; i++) mma_bf16(cg[i % 3], a1[i], hb[i][0], hb[i][1]);
            sts32(lnd, ((st + sv[0]) + sv[1]) + (sv[2] + sv[3]));
            sts32(rdst + 32 * 48, odd ? (cg[0][2] + cg[2][2]) + cg[1][2] : (cg[0][0] + cg[2][0]) + cg[1][0]);
            fin_arrive<4>();
            STAMP(6);
            if (__any_sync(0xffffffffu, !got)) {
                mbar_wait(b1 + 16, 0);
#pragma unroll
                for (int i = 0; i < NB; i++) ldsm_x4_t(a3[i], w1a + (SM_W3 - SM_W1) + i * 4096);
            }
            mbar_wait(b1 + 24, 0);
#pragma unroll
            for (int i = NB; i < 5; i++) ldsm_x4_t(a3[i], w1a + (SM_W3 - SM_W1) + i * 4096);
#pragma unroll
            for (int i = 0; i < 5; i++) mma_bf16(cu[i % 3], a3[i], hb[i][0], hb[i][1]);
            sts32(rdst + 64 * 48, odd ? (cu[0][2] + cu[2][2]) + cu[1][2] : (cu[0][0] + cu[2][0]) + cu[1][0]);
            __syncwarp();
            if (first) mbar_arrive(bar_up);
        }
        if (f2) {
            uint32_t a2[NF2][2][4];
#pragma unroll
            for (int i = 0; i < 4; i++) a2[NF2 - 1][0][i] = a2[NF2 - 1][1][i] = 0;
#pragma unroll
            for (int j = 0; j < NF2 - 1; j++) {
                mbar_wait(b2 + 8 * j, 0);
                ldsm_x4_t(a2[j][0], w2a + j * 8192); ldsm_x4_t(a2[j][1], w2a + j * 8192 + 512);
            }
            STAMP(9);
            uint32_t n = 0, got = 0;
            uint4 e[NF2];
#pragma unroll 1
            while (true) {
                const uint4 pa = ld4(as);
                ldsm_if<2, 512>(a2[NF2 - 1][0], a2[NF2 - 1][1], nullptr, w2a + (NF2 - 1) * 8192, b2 + 8 * (NF2 - 1), got);
                if (++n > SPIN_LIMIT) __trap();
                sts128(at, pa);
                __syncwarp();
#pragma unroll
                for (int j = 0; j < CFG_NSPEC; j++) e[j] = lds128v(al + j * 64);
                if (__all_sync(0xffffffffu, ok8(pa))) break;
            }
#pragma unroll
            for (int j = CFG_NSPEC; j < NF2; j++) e[j] = lds128v(al + j * 64);
            STAMP(10);
            float c[6][4];
#pragma unroll
            for (int j = 0; j < 6; j++) zero4(c[j]);
#pragma unroll
            for (int j = 0; j < NF2; j++) { mma_bf16(c[(j % 3) * 2], a2[j][0], e[j].x, e[j].y); mma_bf16(c[(j % 3) * 2 + 1], a2[j][1], e[j].z, e[j].w); }
            if (__any_sync(0xffffffffu, !got)) {
                constexpr int j = NF2 - 1;
                mbar_wait(b2 + 8 * j, 0);
                ldsm_x4_t(a2[j][0], w2a + j * 8192); ldsm_x4_t(a2[j][1], w2a + j * 8192 + 512);
                mma_bf16(c[4], a2[j][0], e[j].x, e[j].y); mma_bf16(c[5], a2[j][1], e[j].z, e[j].w);
            }
            sts32(rdst + 96 * 48, odd ? (((c[0][2] + c[1][2]) + (c[2][2] + c[3][2])) + c[4][2]) + c[5][2] : (((c[0][0] + c[1][0]) + (c[2][0] + c[3][0])) + c[4][0]) + c[5][0]);
            fin_arrive<6>();
        }
#undef F_
    }
}

typedef CUresult (*EncodeTiledFn)(CUtensorMap*, CUtensorMapDataType, cuuint32_t, void*, const cuuint64_t*, const cuuint64_t*,
                                  const cuuint32_t*, const cuuint32_t*, CUtensorMapInterleave, CUtensorMapSwizzle,
                                  CUtensorMapL2promotion, CUtensorMapFloatOOBfill);

void make_map(EncodeTiledFn fn, CUtensorMap* tm, const void* w, const int (&d)[5], const int (&st)[4], const int (&bx)[5],
              CUtensorMapSwizzle sw, int promo) {
    cuuint64_t dims[5], strides[4];
    cuuint32_t box[5], estr[5];
    for (int i = 0; i < 5; i++) { dims[i] = (cuuint64_t)d[i]; box[i] = (cuuint32_t)bx[i]; estr[i] = 1; }
    for (int i = 0; i < 4; i++) strides[i] = (cuuint64_t)st[i];
    fn(tm, CU_TENSOR_MAP_DATA_TYPE_BFLOAT16, 5, const_cast<void*>(w), dims, strides, box, estr, CU_TENSOR_MAP_INTERLEAVE_NONE, sw,
       (CUtensorMapL2promotion)promo, CU_TENSOR_MAP_FLOAT_OOB_FILL_NONE);
}

enum { T_PER, T_LEAD, T_STAG, T_TD, T_PERO, T_F1D, T_PERF, T_F2, T_PER2, T_Q, T_PWO, T_PW13, T_PW2, T_TG, T_N };
#define TUNE_NAMES {"per", "lead", "stag", "td", "pero", "f1d", "perf", "f2", "per2", "q", "pwo", "pw13", "pw2", "tg"}
int g_tune[T_N] = {478, 1270, 122, 110, 290, 190, 122, 1353, 125, 6000, 1, 2, 2, 1750};

}

extern "C" void kernel_launch(void* const* d_in, const int* in_sizes, int n_in, void* d_out, int out_size) {
    (void)in_sizes; (void)n_in; (void)out_size;
    static EncodeTiledFn encode = nullptr;
    static Scratch* scratch = nullptr;
    static unsigned char* xarea = nullptr;
    if (!encode) {
        void* sp = nullptr;
        cudaGetSymbolAddress(&sp, g_scratch);
        scratch = reinterpret_cast<Scratch*>(sp);
        cudaGetSymbolAddress(&sp, g_xarea);
        xarea = reinterpret_cast<unsigned char*>((reinterpret_cast<uintptr_t>(sp) + XA_ALIGN - 1) / XA_ALIGN * XA_ALIGN);
        void* fn = nullptr;
        cudaDriverEntryPointQueryResult st;
        cudaGetDriverEntryPoint("cuTensorMapEncodeTiled", &fn, cudaEnableDefault, &st);
        encode = reinterpret_cast<EncodeTiledFn>(fn);
        cudaFuncSetAttribute(fused_decode_kernel, cudaFuncAttributeMaxDynamicSharedMemorySize, SM_TOTAL);
        int dev = 0, khz = 0, bits = 0;
        cudaGetDevice(&dev);
        if (cudaDeviceGetAttribute(&khz, cudaDevAttrMemoryClockRate, dev) == cudaSuccess &&
            cudaDeviceGetAttribute(&bits, cudaDevAttrGlobalMemoryBusWidth, dev) == cudaSuccess && khz > 0 && bits > 0) {
            const double f = 2619000.0 * 5120.0 / ((double)khz * bits);
            for (int i : {T_PER, T_STAG, T_PERO, T_PERF, T_F2, T_Q}) g_tune[i] = (int)(g_tune[i] * f + 0.5);
        }
        (void)cudaGetLastError();
    }
    const int* T = g_tune;
    KParams p;
    p.x = (const __nv_bfloat16*)d_in[0];
    p.wq = (const __nv_bfloat16*)d_in[3];
    p.out = (__nv_bfloat16*)d_out;
    p.sc = scratch;
    p.xa = xarea;
    p.per = T[T_PER];
    p.stag = T[T_STAG];
    p.t_k0 = (NQT + 1) * T[T_PER] - T[T_LEAD];
    {
        int t = p.t_k0 + 2 * NKT * T[T_PER] + T[T_STAG] * 3 / 2 + T[T_TD];
        for (int i = 0; i < NWP; i++, t += T[T_PERO]) p.item[i] = t;
        for (int i = 0, t1 = t + T[T_F1D]; i < NP1; i++, t1 += T[T_PERF]) p.item[NWP + i] = t1;
        for (int i = 0, t2 = t + T[T_F2]; i < NF2; i++, t2 += T[T_PER2]) p.item[NWP + NP1 + i] = t2;
        for (int i = NITEM; i < 32; i++) p.item[i] = 0;
    }
    p.target = T[T_TG]; p.t_q = T[T_Q]; p.t_fill = p.t_k0 + 55 * T[T_PER];
    for (int i = 0, nw = 0, n1 = 0, n2 = 0; i < NCTA; i++) {
        const int grp = i >> 2;
        const bool f2 = grp % 3 == 2, both = grp == 8 || grp == 23, wo = !both, f1 = !f2 || both;
        p.role[i] = (wo ? 1 | nw / 20 << 3 | nw % 20 << 6 : 0) | (f1 ? 2 | n1 << 11 : 0) | (f2 ? 4 | n2 << 18 : 0);
        nw += wo; n1 += f1; n2 += f2;
    }
    TMaps tm;
    constexpr int R1 = FF * 2, R2 = D_MODEL * 2;
    for (int i = 0; i < 2; i++)
        make_map(encode, &tm.k + i, d_in[1 + i], {64, 96, 1, 1, NHEAD * SK / 32}, {128, TILE_BYTES, TILE_BYTES, TILE_BYTES}, {64, 96, 1, 1, 1}, CU_TENSOR_MAP_SWIZZLE_128B, 2);
    make_map(encode, &tm.wo, d_in[4], {D_MODEL, 2, 4, 2, NHEAD * DH / 16}, {R2, 4 * R2, 2 * R2, 16 * R2}, {32, 2, 4, 2, 8}, CU_TENSOR_MAP_SWIZZLE_64B, T[T_PWO]);
    make_map(encode, &tm.w1, d_in[6], {FF, 2, 4, 2, D_MODEL / 16}, {R1, 4 * R1, 2 * R1, 16 * R1}, {16, 2, 4, 2, 8}, CU_TENSOR_MAP_SWIZZLE_32B, T[T_PW13]);
    make_map(encode, &tm.w3, d_in[7], {FF, 2, 4, 2, D_MODEL / 16}, {R1, 4 * R1, 2 * R1, 16 * R1}, {16, 2, 4, 2, 8}, CU_TENSOR_MAP_SWIZZLE_32B, T[T_PW13]);
    make_map(encode, &tm.w2, d_in[8], {D_MODEL, 2, 4, 4, FF / 32}, {R2, 8 * R2, 2 * R2, 32 * R2}, {16, 2, 4, 4, 8}, CU_TENSOR_MAP_SWIZZLE_32B, T[T_PW2]);
    fused_decode_kernel<<<NCTA, NTHREADS, SM_TOTAL, cudaStreamPerThread>>>(p, tm);
}
```

```cpp
#include <cuda_runtime.h>
#include <cuda_bf16.h>
#include <cuda.h>
#include <stdint.h>
#include <initializer_list>

namespace {

constexpr int D_MODEL = 640;
constexpr int NHEAD = 32;
constexpr int DH = 192;
constexpr int SK = 32768;
constexpr int WIN = 4096;
constexpr int FF = 1536;

constexpr int NCTA = 128;
constexpr int NTHREADS = 256 + 64;
constexpr int TILE_BYTES = 32 * DH * 2;
constexpr int NSLOT = 16;
constexpr int NKT = 32;
constexpr int NQT = 5;
constexpr int QSLOT = NSLOT - NQT;
constexpr int NG = 6;
constexpr int NWP = 8, NP1 = 10, NF2 = 6;
constexpr int NITEM = NWP + NP1 + NF2;
#define CFG_NSPEC 3
#define CFG_NA 2
#define CFG_NB 2
constexpr int NF1 = 4, NA = CFG_NA, NB = CFG_NB;
constexpr int NTAIL = NWP + NF1 + NF2;

#define CFG_INFL 5
#define CFG_OG 0
#define CFG_HG 3
#define CFG_OSL 100
constexpr int INFLIGHT = CFG_INFL;

constexpr uint32_t sbase = 1024;
constexpr int SM_W1 = NWP * 8192, SM_W3 = SM_W1 + 20480, SM_W2 = SM_W3 + 20480;
constexpr int SM_P = NSLOT * TILE_BYTES;
constexpr int SM_Q = SM_P + 2048;
constexpr int SM_RED = SM_Q + 384;
constexpr int SM_BC = SM_RED + 128 * 48;
constexpr int SM_ONE = SM_BC + 4096;
constexpr int SM_MAX = SM_ONE + 64;
constexpr int SM_SUM = SM_MAX + 32;
constexpr int SM_LN = SM_SUM + 32;
constexpr int SM_MISC = SM_LN + 64;
constexpr int SM_LATE = SM_MISC + 32;
constexpr int SM_BAR = SM_LATE + 32;
constexpr int SM_TOTAL = SM_BAR + 512;
static_assert(SM_TOTAL <= 232448, "shared memory");

struct __align__(128) Scratch {
    uint2 qbuf[NCTA * 96];
    uint4 mbuf[NCTA * 2];
    uint32_t ready[NCTA];
    uint32_t late[32];
    uint32_t epoch;
};
__device__ Scratch g_scratch;
constexpr int XA_ALIGN = 1 << 20;
constexpr uint32_t SENT = 0xffffffffu;
__device__ unsigned char g_xarea[2 * XA_ALIGN];
__host__ __device__ constexpr uint32_t xa_o(uint32_t h) { return (2 * h + ((h ^ (h >> 3) ^ (h >> 4)) & 1)) * 4096; }
__host__ __device__ constexpr uint32_t xa_h(uint32_t i) { return (1 << 18) + (i >> 2) * (3 << 16) + (i & 3) * (1 << 14); }
constexpr uint32_t XA_A = xa_h(NG);

constexpr uint32_t SPIN_LIMIT = 1u << 22;

__device__ __forceinline__ uint32_t smem_u32(const void* p) { return (uint32_t)__cvta_generic_to_shared(p); }
__device__ __forceinline__ uint32_t now_ns() { uint64_t t; asm volatile("mov.u64 %0, %globaltimer;" : "=l"(t)); return (uint32_t)t; }
__device__ __forceinline__ void mbar_init(uint32_t bar, uint32_t cnt) {
    asm volatile("mbarrier.init.shared::cta.b64 [%0], %1;" ::"r"(bar), "r"(cnt) : "memory");
}
__device__ __forceinline__ void mbar_expect_tx(uint32_t bar, uint32_t bytes) {
    asm volatile("mbarrier.arrive.expect_tx.shared::cta.b64 _, [%0], %1;" ::"r"(bar), "r"(bytes) : "memory");
}
__device__ __forceinline__ void mbar_arrive(uint32_t bar) {
    asm volatile("mbarrier.arrive.shared::cta.b64 _, [%0];" ::"r"(bar) : "memory");
}
__device__ __forceinline__ void mbar_arrive8(uint32_t bar) {
    asm volatile("mbarrier.arrive.shared::cta.b64 _, [%0], 8;" ::"r"(bar) : "memory");
}
__device__ __forceinline__ bool mbar_test(uint32_t bar, uint32_t parity) {
    uint32_t ok;
    asm volatile("{\n.reg .pred p;\nmbarrier.test_wait.parity.shared::cta.b64 p, [%1], %2;\nselp.u32 %0, 1, 0, p;\n}"
                 : "=r"(ok) : "r"(bar), "r"(parity) : "memory");
    return ok;
}
__device__ __forceinline__ void mbar_wait(uint32_t bar, uint32_t parity) {
    asm volatile("{\n.reg .pred p;\nW_%=:\nmbarrier.try_wait.parity.shared::cta.b64 p, [%0], %1;\n@!p bra.uni W_%=;\n}" ::"r"(bar), "r"(parity) : "memory");
}
__device__ __forceinline__ void mbar_wait_after(uint32_t bar, uint32_t dump, float v) {
    uint32_t ok;
    asm volatile("{\n.reg .pred p;\nmbarrier.try_wait.parity.shared::cta.b64 p, [%1], 0;\nselp.u32 %0, 1, 0, p;\n}" : "=r"(ok) : "r"(bar) : "memory");
    asm volatile("st.volatile.shared.f32 [%0], %1;" ::"r"(dump), "f"(v) : "memory");
    if (__builtin_expect(!ok, 0)) mbar_wait(bar, 0);
}
__device__ __forceinline__ void tma_load_at(uint32_t when, uint32_t dst, const CUtensorMap* tm, int c0, int c4, uint32_t bar, uint64_t pol) {
    asm volatile("{\n.reg .pred p, e;\n.reg .b64 t;\n.reg .b32 lo, hi;\nelect.sync _|e, -1;\n"
                 "W_%=:\nmov.u64 t, %globaltimer;\nmov.b64 {lo, hi}, t;\nsub.u32 lo, lo, %7;\nsetp.lt.s32 p, lo, 0;\n@p bra.uni W_%=;\n"
                 "@e cp.async.bulk.tensor.5d.shared::cluster.global.mbarrier::complete_tx::bytes.L2::cache_hint [%0], [%1, {%3, %5, %5, %5, %4}], [%2], %6;\n}"
                 ::"r"(dst), "l"(reinterpret_cast<uint64_t>(tm)), "r"(bar), "r"(c0), "r"(c4), "r"(0), "l"(pol), "r"(when) : "memory");
}
__device__ __forceinline__ void pin(uint32_t& v) { asm volatile("shfl.sync.bfly.b32 %0, %0, 0, 31, -1;" : "+r"(v) :: "memory"); }
__device__ __forceinline__ void pin_u(uint32_t& v) { asm volatile("shfl.sync.idx.b32 %0, %0, 0, 31, -1;" : "+r"(v) :: "memory"); }
template <class T> __device__ __forceinline__ void pin(T*& v) {
    asm volatile("{\n.reg .b32 a, b;\nmov.b64 {a, b}, %0;\nshfl.sync.bfly.b32 a, a, 0, 31, -1;\nshfl.sync.bfly.b32 b, b, 0, 31, -1;\nmov.b64 %0, {a, b};\n}" : "+l"(v) :: "memory");
}
__device__ __forceinline__ void sts16(uint32_t a, uint32_t v) { asm volatile("st.shared.u16 [%0], %1;" ::"r"(a), "h"((unsigned short)v) : "memory"); }
__device__ __forceinline__ void sts32(uint32_t a, float v) { asm volatile("st.shared.f32 [%0], %1;" ::"r"(a), "f"(v) : "memory"); }
__device__ __forceinline__ void sts32(uint32_t a, uint32_t v) { asm volatile("st.shared.u32 [%0], %1;" ::"r"(a), "r"(v) : "memory"); }
__device__ __forceinline__ void sts64(uint32_t a, uint32_t x, uint32_t y) { asm volatile("st.shared.v2.u32 [%0], {%1, %2};" ::"r"(a), "r"(x), "r"(y) : "memory"); }
__device__ __forceinline__ void sts128(uint32_t a, const uint4& v) { asm volatile("st.shared.v4.u32 [%0], {%1, %2, %3, %4};" ::"r"(a), "r"(v.x), "r"(v.y), "r"(v.z), "r"(v.w) : "memory"); }
__device__ __forceinline__ void cons_sync() { asm volatile("bar.sync 1, 256;" ::: "memory"); }
template <int ID> __device__ __forceinline__ void fin_arrive() { asm volatile("bar.arrive %0, 288;" ::"n"(ID) : "memory"); }
template <int ID> __device__ __forceinline__ void fin_sync() { asm volatile("bar.sync %0, 288;" ::"n"(ID) : "memory"); }

__device__ __forceinline__ uint4 lds128(uint32_t a) {
    uint4 v;
    asm volatile("ld.shared.v4.u32 {%0,%1,%2,%3}, [%4];" : "=r"(v.x), "=r"(v.y), "=r"(v.z), "=r"(v.w) : "r"(a) : "memory");
    return v;
}
__device__ __forceinline__ uint4 lds128v(uint32_t a) {
    uint4 v;
    asm volatile("ld.volatile.shared.v4.u32 {%0,%1,%2,%3}, [%4];" : "=r"(v.x), "=r"(v.y), "=r"(v.z), "=r"(v.w) : "r"(a) : "memory");
    return v;
}
__device__ __forceinline__ float4 lds128f(uint32_t a) {
    float4 v;
    asm volatile("ld.shared.v4.f32 {%0,%1,%2,%3}, [%4];" : "=f"(v.x), "=f"(v.y), "=f"(v.z), "=f"(v.w) : "r"(a) : "memory");
    return v;
}
__device__ __forceinline__ uint2 lds64(uint32_t a) {
    uint2 v;
    asm volatile("ld.shared.v2.u32 {%0,%1}, [%2];" : "=r"(v.x), "=r"(v.y) : "r"(a) : "memory");
    return v;
}
__device__ __forceinline__ uint32_t lds32(uint32_t a) {
    uint32_t v;
    asm volatile("ld.shared.u32 %0, [%1];" : "=r"(v) : "r"(a) : "memory");
    return v;
}
__device__ __forceinline__ float sum8(uint32_t a) {
    const float4 x = lds128f(a), y = lds128f(a + 16);
    return ((x.x + x.y) + (x.z + x.w)) + ((y.x + y.y) + (y.z + y.w));
}
__device__ __forceinline__ void ldsm_x4(uint32_t* r, uint32_t a) {
    asm volatile("ldmatrix.sync.aligned.m8n8.x4.shared.b16 {%0,%1,%2,%3}, [%4];"
                 : "=r"(r[0]), "=r"(r[1]), "=r"(r[2]), "=r"(r[3]) : "r"(a) : "memory");
}
__device__ __forceinline__ void ldsm_x4_t(uint32_t* r, uint32_t a) {
    asm volatile("ldmatrix.sync.aligned.m8n8.x4.trans.shared.b16 {%0,%1,%2,%3}, [%4];"
                 : "=r"(r[0]), "=r"(r[1]), "=r"(r[2]), "=r"(r[3]) : "r"(a) : "memory");
}
template <int N, int STRIDE>
__device__ __forceinline__ void ldsm_if(uint32_t* r0, uint32_t* r1, uint32_t* r2, uint32_t a, uint32_t bar, uint32_t& got) {
    if (N == 2)
        asm volatile("{\n.reg .pred p, q;\nsetp.eq.u32 q, %8, 0;\nmbarrier.test_wait.parity.shared::cta.b64 p, [%10], 0;\nand.pred p, p, q;\n"
                     "@p ldmatrix.sync.aligned.m8n8.x4.trans.shared.b16 {%0,%1,%2,%3}, [%9];\n"
                     "@p ldmatrix.sync.aligned.m8n8.x4.trans.shared.b16 {%4,%5,%6,%7}, [%9+%11];\n@p mov.u32 %8, 1;\n}"
                     : "+r"(r0[0]), "+r"(r0[1]), "+r"(r0[2]), "+r"(r0[3]), "+r"(r1[0]), "+r"(r1[1]), "+r"(r1[2]), "+r"(r1[3]), "+r"(got)
                     : "r"(a), "r"(bar), "n"(STRIDE) : "memory");
    else
        asm volatile("{\n.reg .pred p, q;\nsetp.eq.u32 q, %12, 0;\nmbarrier.test_wait.parity.shared::cta.b64 p, [%14], 0;\nand.pred p, p, q;\n"
                     "@p ldmatrix.sync.aligned.m8n8.x4.trans.shared.b16 {%0,%1,%2,%3}, [%13];\n"
                     "@p ldmatrix.sync.aligned.m8n8.x4.trans.shared.b16 {%4,%5,%6,%7}, [%13+%15];\n"
                     "@p ldmatrix.sync.aligned.m8n8.x4.trans.shared.b16 {%8,%9,%10,%11}, [%13+%16];\n@p mov.u32 %12, 1;\n}"
                     : "+r"(r0[0]), "+r"(r0[1]), "+r"(r0[2]), "+r"(r0[3]), "+r"(r1[0]), "+r"(r1[1]), "+r"(r1[2]), "+r"(r1[3]),
                       "+r"(r2[0]), "+r"(r2[1]), "+r"(r2[2]), "+r"(r2[3]), "+r"(got)
                     : "r"(a), "r"(bar), "n"(STRIDE), "n"(2 * STRIDE) : "memory");
}
__device__ __forceinline__ void mma_bf16(float* c, uint32_t a0, uint32_t a1, uint32_t a2, uint32_t a3, uint32_t b0, uint32_t b1) {
    asm volatile("mma.sync.aligned.m16n8k16.row.col.f32.bf16.bf16.f32 {%0,%1,%2,%3}, {%4,%5,%6,%7}, {%8,%9}, {%0,%1,%2,%3};"
                 : "+f"(c[0]), "+f"(c[1]), "+f"(c[2]), "+f"(c[3]) : "r"(a0), "r"(a1), "r"(a2), "r"(a3), "r"(b0), "r"(b1));
}
__device__ __forceinline__ void mma_bf16(float* c, const uint32_t* a, uint32_t b0, uint32_t b1) { mma_bf16(c, a[0], a[1], a[2], a[3], b0, b1); }
__device__ __forceinline__ void zero4(float* c) { c[0] = c[1] = c[2] = c[3] = 0.f; }
__device__ __forceinline__ float bf_lo(uint32_t u) { return __uint_as_float(u << 16); }
__device__ __forceinline__ float bf_hi(uint32_t u) { return __uint_as_float(u & 0xffff0000u); }
__device__ __forceinline__ uint32_t pack_bf(float hi, float lo) { uint32_t r; asm("cvt.rn.bf16x2.f32 %0, %1, %2;" : "=r"(r) : "f"(hi), "f"(lo)); return r; }
__device__ __forceinline__ uint32_t add_bf2(uint32_t a, uint32_t b) { uint32_t r; asm("add.rn.bf16x2 %0, %1, %2;" : "=r"(r) : "r"(a), "r"(b)); return r; }
__device__ __forceinline__ float bfr(float x) { return __uint_as_float(pack_bf(x, 0.f)); }

__device__ __forceinline__ uint32_t in_word(float v) { return __float_as_uint(v); }
__device__ __forceinline__ void st1(void* p, uint32_t v) {
    asm volatile("st.relaxed.gpu.global.u32 [%0], %1;" ::"l"(p), "r"(v) : "memory");
}
__device__ __forceinline__ void st16(void* p, uint32_t v) {
    asm volatile("st.relaxed.gpu.global.u16 [%0], %1;" ::"l"(p), "h"((unsigned short)v) : "memory");
}
__device__ __forceinline__ void st2(void* p, uint32_t a, uint32_t b) {
    asm volatile("st.relaxed.gpu.global.v2.u32 [%0], {%1, %2};" ::"l"(p), "r"(a), "r"(b) : "memory");
}
__device__ __forceinline__ void st4(void* p, uint32_t a, uint32_t b, uint32_t c, uint32_t d) {
    asm volatile("st.relaxed.gpu.global.v4.u32 [%0], {%1, %2, %3, %4};" ::"l"(p), "r"(a), "r"(b), "r"(c), "r"(d) : "memory");
}
__device__ __forceinline__ uint32_t ld1(const void* p) {
    uint32_t v;
    asm volatile("ld.relaxed.gpu.global.u32 %0, [%1];" : "=r"(v) : "l"(p) : "memory");
    return v;
}
__device__ __forceinline__ uint2 ld2(const void* p) {
    uint2 v;
    asm volatile("ld.relaxed.gpu.global.v2.u32 {%0, %1}, [%2];" : "=r"(v.x), "=r"(v.y) : "l"(p) : "memory");
    return v;
}
__device__ __forceinline__ uint4 ld4(const void* p) {
    uint4 v;
    asm volatile("ld.relaxed.gpu.global.v4.u32 {%0, %1, %2, %3}, [%4];" : "=r"(v.x), "=r"(v.y), "=r"(v.z), "=r"(v.w) : "l"(p) : "memory");
    return v;
}
__device__ __forceinline__ void ld2p(const void* p, uint2& v, bool on) {
    asm volatile("{\n.reg .pred q;\nsetp.ne.u32 q, %3, 0;\n@q ld.relaxed.gpu.global.v2.u32 {%0, %1}, [%2];\n}"
                 : "+r"(v.x), "+r"(v.y) : "l"(p), "r"((uint32_t)on) : "memory");
}
__device__ __forceinline__ void poll2(const void* p, uint2& v) {
    asm volatile("{\n.reg .pred q, r;\nsetp.nan.bf16x2 q|r, %0, %1;\nor.pred q, q, r;\n@q ld.relaxed.gpu.global.v2.u32 {%0, %1}, [%2];\n}"
                 : "+r"(v.x), "+r"(v.y) : "l"(p) : "memory");
}
__device__ __forceinline__ bool ok8(const uint4& v) {
    const uint32_t m = __vimax3_u16x2(__vimax3_u16x2(v.x, v.y, v.z), v.w, v.w);
    return __vimax3_u16x2(m, m << 16, m >> 16) != SENT;
}
__device__ __forceinline__ void poll4(const void* p, uint4& v) {
    asm volatile("{\n.reg .pred q;\n.reg .u32 m;\nmax.u32 m, %0, %1;\nmax.u32 m, m, %2;\nmax.u32 m, m, %3;\nsetp.eq.u32 q, m, 0xffffffff;\n"
                 "@q ld.relaxed.gpu.global.v4.u32 {%0, %1, %2, %3}, [%4];\n}"
                 : "+r"(v.x), "+r"(v.y), "+r"(v.z), "+r"(v.w) : "l"(p) : "memory");
}
__device__ __forceinline__ uint32_t max4(const uint4& v) { return max(max(v.x, v.y), max(v.z, v.w)); }
__device__ __forceinline__ void pkt_st2(uint4* p, float a, float b, uint32_t tag) {
    asm volatile("st.relaxed.gpu.global.v2.b64 [%0], {%1, %2};" ::"l"(p), "l"(((uint64_t)tag << 32) | __float_as_uint(a)), "l"(((uint64_t)tag << 32) | __float_as_uint(b)) : "memory");
}
__device__ __forceinline__ void pkt_ld2(const uint4* p, uint64_t& a, uint64_t& b) {
    asm volatile("ld.relaxed.gpu.global.v2.b64 {%0, %1}, [%2];" : "=l"(a), "=l"(b) : "l"(p) : "memory");
}
__device__ __forceinline__ bool tag_ok(uint64_t v, uint32_t tag) { return (uint32_t)(v >> 32) == tag; }
__device__ __forceinline__ float val_of(uint64_t v) { return __uint_as_float((uint32_t)v); }

__device__ __forceinline__ float warp_sum(float v) {
#pragma unroll
    for (int o = 16; o > 0; o >>= 1) v += __shfl_xor_sync(0xffffffffu, v, o);
    return v;
}
__device__ __forceinline__ float warp_max(float v) {
#pragma unroll
    for (int o = 16; o > 0; o >>= 1) v = fmaxf(v, __shfl_xor_sync(0xffffffffu, v, o));
    return v;
}
__device__ __forceinline__ float sqrt_fast(float x) { float r; asm("sqrt.approx.ftz.f32 %0, %1;" : "=f"(r) : "f"(x)); return r; }
__device__ __forceinline__ float rcp_fast(float x) { float r; asm("rcp.approx.ftz.f32 %0, %1;" : "=f"(r) : "f"(x)); return r; }
__device__ __forceinline__ float ex2(float x) { float r; asm("ex2.approx.ftz.f32 %0, %1;" : "=f"(r) : "f"(x)); return r; }
constexpr float L2E = 1.4426950408889634f;
__device__ __forceinline__ void ln_finish(float s1, float s2, float& mean_b, float& inv_den) {
    const float mean = s1 * (1.0f / D_MODEL);
    const float var = fmaxf(fmaf(-mean, mean, s2 * (1.0f / D_MODEL)), 0.f);
    mean_b = bfr(mean);
    inv_den = rcp_fast(bfr(sqrt_fast(bfr(bfr(var) + 1e-5f))));
}
__device__ __forceinline__ uint32_t ln_apply2(uint32_t u, float mean_b, float inv_den) {
    const uint32_t d = pack_bf(bf_hi(u) - mean_b, bf_lo(u) - mean_b);
    return pack_bf(bf_hi(d) * inv_den, bf_lo(d) * inv_den);
}
__device__ __forceinline__ void ln_acc(uint32_t u, float& s1, float& s2) {
    const float a = bf_lo(u), b = bf_hi(u);
    s1 += a + b;
    s2 = fmaf(a, a, fmaf(b, b, s2));
}
__device__ __forceinline__ float silu_b(float g) { return bfr(__fdividef(g, 1.0f + ex2(-g * L2E))); }

#define STAMP(i) do { } while (0)

struct KParams {
    const __nv_bfloat16* wq;
    const __nv_bfloat16* x;
    __nv_bfloat16* out;
    Scratch* sc;
    unsigned char* xa;
    int t_k0, per, stag;
    int target;
    int t_q, t_fill;
    uint32_t item[32];
    uint32_t role[NCTA];
};
struct TMaps { CUtensorMap k, v, wo, w1, w3, w2; };

__global__ void __launch_bounds__(NTHREADS, 1)
fused_decode_kernel(const __grid_constant__ KParams p, const __grid_constant__ TMaps tm) {
    extern __shared__ __align__(1024) unsigned char smem[];
    const int tid = threadIdx.x;
    const int b = blockIdx.x;
    const int head = b >> 2, sp = b & 3;
    {
        const char* a = reinterpret_cast<const char*>(p.wq) + (uint32_t)((sp * 160 + (tid >> 2)) * (NHEAD * DH * 2) + head * (DH * 2) + (tid & 3) * 128);
        asm volatile("prefetch.global.L2 [%0];" ::"l"(a) : "memory");
    }
    if (tid < 256) {
        const uint32_t r = tid >> 3, ch = tid & 7;
        const char* src = reinterpret_cast<const char*>(p.wq) + ((sp * 160 + r) * (NHEAD * DH * 2) + head * (DH * 2) + ch * 16);
#pragma unroll
        for (int i = 0; i < NQT; i++) {
#pragma unroll
            for (int j = 0; j < 3; j++)
                asm volatile("cp.async.cg.shared.global [%0], [%1], 16;"
                             ::"r"(sbase + (QSLOT + i) * TILE_BYTES + (3 * r + j) * 128 + ((ch ^ ((3 * r + j) & 7)) << 4)),
                               "l"(src + (size_t)i * 32 * (NHEAD * DH * 2) + j * 128) : "memory");
        }
    }
    const uint32_t t0 = now_ns();
    const int warp = __shfl_sync(0xffffffffu, tid >> 5, 0), lane = tid & 31;
    const uint32_t role = p.role[b];
    const int kg = role >> 3 & 7, ng = role >> 6 & 31;
    const int u1 = role >> 11 & 127, u2 = role >> 18;
    const bool has_wo = role & 1, has_f1 = role & 2, has_f2 = role & 4;
    constexpr uint32_t bar_full = sbase + SM_BAR;
    constexpr uint32_t bar_empty = sbase + SM_BAR + 128;
    constexpr uint32_t bar_tail = sbase + SM_BAR + 256;
    constexpr uint32_t bar_scale = bar_tail + 8 * NTAIL;
    constexpr uint32_t bar_stat = bar_scale + 8;
    constexpr uint32_t bar_up = bar_scale + 16;

    STAMP(13);
    if (warp == 8) {
        if (smem_u32(smem) != sbase) __trap();
        uint64_t pol;
        asm volatile("createpolicy.fractional.L2::evict_first.b64 %0, 1.0;" : "=l"(pol));
        sts32(sbase + SM_LATE + (lane & 7) * 4, 0u);
        if (lane == 0) {
#pragma unroll
            for (int i = 0; i < 32 + NTAIL + 3; i++)
                mbar_init(bar_full + 8 * i, (i >= 16 && i < 32) || i > 32 + NTAIL ? 8 : i == 32 + NWP ? NA : i == 33 + NWP ? 5 - NA : i == 34 + NWP ? NB : i == 35 + NWP ? 5 - NB : 1);
#pragma unroll
            for (int i = 0; i < 6; i++) asm volatile("prefetch.tensormap [%0];" ::"l"(reinterpret_cast<uint64_t>(&tm.k + i)) : "memory");
            asm volatile("fence.mbarrier_init.release.cluster;" ::: "memory");
        }
        __syncwarp();
        asm volatile("bar.arrive 2, 320;" ::: "memory");
        STAMP(14);
        const uint32_t tu = __shfl_sync(0xffffffffu, t0, 0);
        if (b == 0 && lane < 8) st1(p.sc->late + lane, lane ? 0 : (tu & 0xffffffu) | 1u << 24);
        const int tile0 = (head * SK + (SK - WIN)) / 32 + sp;
        uint32_t tk = tu + p.t_k0 + sp * p.stag, tw = tk, acc = 0;
        int slip = 0, slip0 = 0, w = 0, d0 = 0;
#pragma unroll 1
        for (int n = 0; n < 2 * NKT; n++) {
            const int slot = n & (NSLOT - 1);
            mbar_wait(bar_empty + 8 * slot, (((n + NQT) >> 4) & 1) ^ 1);
            if (lane == 0) mbar_expect_tx(bar_full + 8 * slot, TILE_BYTES);
            bool more;
            do {
                const uint32_t t = now_ns();
                if (__all_sync(0xffffffffu, mbar_test(bar_full + 8 * (w & (NSLOT - 1)), (w >> 4) & 1))) {
                    acc += t - tw;
                    tw += p.per;
                    w++;
                    if ((w & 7) == 0) {
                        if (lane == 0) asm volatile("red.relaxed.gpu.global.add.u32 [%0], %1;" ::"l"(p.sc->late + (w >> 3)), "r"((1u << 24) + min(max(((int)acc >> 3) + d0, 0), 65535)) : "memory");
                        acc = 0;
                    }
                }
                more = __any_sync(0xffffffffu, (int)(t - tk) < slip - 60) || w <= n - INFLIGHT;
            } while (more);
            tma_load_at(tk + slip, sbase + slot * TILE_BYTES, &tm.k + (n >> 5), 0, tile0 + (n & (NKT - 1)) * 4, bar_full + 8 * slot, pol);
            tk += p.per;
            if ((n & 7) == 5 && lane < 2)
                asm volatile("cp.async.cg.shared.global [%0], [%1], 16;" ::"r"(sbase + SM_LATE + lane * 16), "l"(p.sc->late + lane * 4) : "memory");
            const uint32_t org = lds32(sbase + SM_LATE);
            if (org) d0 = (int)((tu - org) << 8) >> 8;
            uint32_t rep = lds32(sbase + SM_LATE + (n >> 3) * 4);
            const uint32_t rep0 = lds32(sbase + SM_LATE + (max(n - 8, 0) >> 3) * 4);
            if (!(rep >> 30)) rep = rep0;
            if (rep >> 30) slip = max((int)((float)(rep & 0xffffffu) * rcp_fast((float)(rep >> 24))) - p.target - d0, -700);
            if (n == 24) slip0 = slip;
        }
        slip += min(max((slip - slip0) * 90 >> 8, -200), 250);
        const int seg = (lane >= NWP) + (lane >= NWP + NP1), i = lane - (seg == 0 ? 0 : seg == 1 ? NWP : NWP + NP1);
        const bool todo = lane < NITEM && (role >> seg & 1);
        const uint32_t len = seg == 1 ? 4096 : 8192, dst = sbase + (seg == 0 ? 0 : seg == 1 ? SM_W1 : SM_W2) + i * len;
        const int w3 = seg == 1 && i >= 5;
        const uint32_t mi = seg == 2 ? 3 : seg + w3;
        const int c0 = seg == 0 ? ng * 32 : seg == 1 ? u1 * 16 : u2 * 16;
        const int c4 = (seg == 0 ? kg * 64 : w3 * -40) + i * 8;
        const uint32_t bar = bar_tail + 8 * (seg == 0 ? i : seg == 1 ? NWP + (i >= NA) + w3 + (i >= 5 + NB) : NWP + NF1 + i);
        const uint32_t tn = tu + slip + p.item[lane];
        if (todo) mbar_expect_tx(bar, len);
        const uint32_t c04 = c0 | c4 << 16, db = dst | (bar - bar_tail) << 18 | mi << 28;
#pragma unroll 1
        for (uint32_t left = __ballot_sync(0xffffffffu, todo); left; left &= left - 1) {
            const int k = __ffs(left) - 1;
            const uint32_t kc = __shfl_sync(0xffffffffu, c04, k), kd = __shfl_sync(0xffffffffu, db, k), kt = __shfl_sync(0xffffffffu, tn, k);
            mbar_wait(bar_empty + 8 * (k < NWP ? 5 : 12), k < NWP);
            tma_load_at(kt, kd & 0x3ffff, &tm.wo + (kd >> 28), kc & 0xffff, kc >> 16, bar_tail + (kd >> 18 & 0x3ff), pol);
        }
    } else if (warp == 9) {
        const uint32_t tag = ld1(&p.sc->epoch) + 1;
        const uint32_t aoff = XA_A + (u1 >> 1 & 7) * 384 + (u1 >> 4) * 64 + (u1 & 1) * 32, hoff = xa_h(kg) + (ng & 3) * 512 + (ng >> 2) * 32;
        sts32(sbase + SM_ONE + (lane & 15) * 4, 0x3f803f80u);
        const uint32_t ooff = xa_o(head) + sp * (DH * 4);
        unsigned char* slot[4] = {p.xa + (ooff + lane * 16), p.xa + ((ooff + 512 + (lane & 15) * 16) ^ (lane >> 4) << 12), p.xa + ((ooff + lane * 16) ^ 4096),
                                  p.xa + (lane < 16 ? (has_wo ? hoff + (lane >> 2 & 1) * 4096 + (lane >> 1 & 1) * 256 + (lane & 1) * 16 : ooff) : has_f1 ? aoff + (lane >> 1 & 1) * 4096 + (lane & 1) * 16 : ooff)};
#pragma unroll
        for (int i = 0; i < 2; i++) st4(p.sc->qbuf + b * 96 + i * 32 + lane * 2, 0, 0, 0, 0);
        sts32(sbase + SM_MISC, tag);
        asm volatile("bar.sync 2, 320;" ::: "memory");
        while (!mbar_test(bar_stat, 0)) __nanosleep(200);
        const float4 ma = lds128f(sbase + SM_MAX), mb = lds128f(sbase + SM_MAX + 16);
        const float m = fmaxf(fmaxf(fmaxf(ma.x, ma.y), fmaxf(ma.z, ma.w)), fmaxf(fmaxf(mb.x, mb.y), fmaxf(mb.z, mb.w)));
        while ((int)(now_ns() - (t0 + p.t_fill)) < 0) __nanosleep(200);
        pkt_st2(p.sc->mbuf + b * 2 + (lane & 1), m, sum8(sbase + SM_SUM), tag);
#pragma unroll
        for (int i = 0; i < 4; i++) st4(slot[i], SENT, SENT, SENT, SENT);
        uint32_t ack = SENT;
#pragma unroll
        for (int i = 0; i < 4; i++) { uint32_t v; asm volatile("atom.relaxed.gpu.global.exch.b32 %0, [%1], -1;" : "=r"(v) : "l"(slot[i]) : "memory"); ack &= v; }
        if (__any_sync(0xffffffffu, ack != SENT)) __trap();
        if (lane == 0) st1(p.sc->ready + b, tag);
        int vote = 0;
#pragma unroll 1
        for (int r = 0; r < 5 && (!vote || (int)(now_ns() - (t0 + p.t_fill)) < 3500); r++) {
            __nanosleep(100);
            uint32_t d;
            asm volatile("{\n.reg .pred p, q;\n.reg .b32 a, b, c0, c1;\nmov.b32 c0, 0;\nmov.b32 c1, 0;\n"
                         "atom.relaxed.gpu.global.exch.b32 a, [%1], -1;\natom.relaxed.gpu.global.exch.b32 b, [%2], -1;\n"
                         "setp.eq.u32 p, a, -1;\n@p mov.u32 c0, %%clock;\nsetp.eq.u32 q, b, -1;\n@q mov.u32 c1, %%clock;\nsub.u32 %0, c1, c0;\n}"
                         : "=r"(d) : "l"(r & 1 ? slot[2] : slot[0]), "l"(r & 1 ? slot[0] : slot[2]) : "memory");
            vote += (d > 90) == (r & 1) ? 1 : -1;
        }
        const uint32_t side = __shfl_sync(0xffffffffu, vote, 0) > 0;
        uint32_t n = 0;
        {
            uint64_t em, el;
            while (true) {
                const uint4 e = ld4(p.sc->ready + lane * 4);
                pkt_ld2(p.sc->mbuf + (head * 4 + (lane & 3)) * 2, em, el);
                if (__all_sync(0xffffffffu, e.x == tag && e.y == tag && e.z == tag && e.w == tag && tag_ok(em, tag) && tag_ok(el, tag))) break;
                __nanosleep(500);
                if (++n > SPIN_LIMIT) __trap();
            }
            float M = fmaxf(val_of(em), __shfl_xor_sync(0xffffffffu, val_of(em), 1));
            M = fmaxf(M, __shfl_xor_sync(0xffffffffu, M, 2));
            float L = ex2((val_of(em) - M) * L2E) * val_of(el);
            L += __shfl_xor_sync(0xffffffffu, L, 1);
            L += __shfl_xor_sync(0xffffffffu, L, 2);
            if (lane == 0) {
                sts64(sbase + SM_MISC + 8, __float_as_uint(__fdividef(ex2((m - M) * L2E), L)), side);
                mbar_arrive(bar_scale);
                if (b == 0) p.sc->epoch = tag;
            }
        }
        unsigned char* hdst = p.xa + (hoff + (side ^ 1) * 4096 + (lane >> 4) * 256 + (lane & 15) * 2);
        unsigned char* hdst2 = p.xa + (hoff + side * 4096 + (lane >> 4) * 256 + (lane & 15) * 2);
        unsigned char* adst = p.xa + (aoff + (lane >> 4) * 4096 + (lane & 15) * 2);
        __nv_bfloat16* odst = p.out + u2 * 16 + (lane & 15);
        uint32_t r0 = sbase + SM_RED + lane * 48, r1 = sbase + SM_RED + (lane & 15) * 48;
        uint32_t res;
        asm volatile("ld.global.nc.u16 %0, [%1];" : "=r"(res) : "l"(p.x + u2 * 16 + (lane & 15)));
        pin(hdst); pin(hdst2); pin(adst); pin(odst); pin(r0); pin(r1);
        if (has_wo) {
            fin_sync<3>();
            const uint32_t v = pack_bf(0.f, sum8(r0));
            st16(hdst, v); st16(hdst2, v);
            STAMP(4);
        }
        if (has_f1) {
            fin_sync<4>();
            float mean_b, inv_den;
            ln_finish(sum8(sbase + SM_LN), sum8(sbase + SM_LN + 32), mean_b, inv_den);
            const float gr = fmaf(-mean_b, sum8(r1 + 48 * 48), sum8(r1 + 32 * 48)) * inv_den;
            mbar_wait_after(bar_up, r0, gr);
            const float gs = bfr(gr);
            const float up = bfr(fmaf(-mean_b, sum8(r1 + 80 * 48), sum8(r1 + 64 * 48)) * inv_den);
            st16(adst, pack_bf(0.f, silu_b(gs) * up));
            if (b == 0 && lane < 8) st1(p.sc->late + lane, 0);
            STAMP(8);
        }
        if (has_f2) {
            mbar_wait(bar_tail + 8 * (NWP + NF1 + CFG_HG), 0);
            const unsigned char* hsrc = p.xa + ((lane >> 4) * (1 << 14) + side * 4096 + (u2 & 7) * 256 + (u2 >> 3) * 32 + (lane & 15) * 2);
            uint32_t e[3];
            do {
#pragma unroll
                for (int i = 0; i < 3; i++) asm volatile("ld.relaxed.gpu.global.u16 %0, [%1];" : "=r"(e[i]) : "l"(hsrc + xa_h(2 * i)) : "memory");
                if (++n > SPIN_LIMIT) __trap();
            } while (__any_sync(0xffffffffu, max(max(e[0], e[1]), e[2]) == 0xffffu));
            float f[3];
#pragma unroll
            for (int i = 0; i < 3; i++) f[i] = bf_lo(e[i]) + bf_lo(__shfl_xor_sync(0xffffffffu, e[i], 16));
            res = add_bf2(res, pack_bf(0.f, (f[0] + f[1]) + f[2]));
            pin(res);
            fin_sync<6>();
            asm volatile("st.global.u16 [%0], %1;" ::"l"(odst), "h"((unsigned short)add_bf2(res, pack_bf(0.f, sum8(r1 + 96 * 48)))) : "memory");
            STAMP(11);
        }
    } else {
        const int g = lane >> 2, t = lane & 3;
        uint2 xres;
        {
            uint32_t xr;
            uint2 xu[5];
            const char* xb = reinterpret_cast<const char*>(p.x);
            asm volatile("ld.global.nc.u16 %0, [%1];" : "=r"(xr) : "l"(xb + (sp * 160 + min(tid, 159)) * 2));
#pragma unroll
            for (int i = 0; i < 5; i++) asm volatile("ld.global.nc.v2.u32 {%0, %1}, [%2];" : "=r"(xu[i].x), "=r"(xu[i].y) : "l"(xb + i * 256 + lane * 8));
            asm volatile("ld.global.nc.v2.u32 {%0, %1}, [%2];" : "=r"(xres.x), "=r"(xres.y) : "l"(xb + min(g, 4) * 256 + warp * 32 + t * 8));
            if (lane >= 20) xres.x = xres.y = 0;
            float s1 = 0.f, s2 = 0.f, mean_b, inv_den;
#pragma unroll
            for (int i = 0; i < 5; i++) { ln_acc(xu[i].x, s1, s2); ln_acc(xu[i].y, s1, s2); }
            ln_finish(warp_sum(s1), warp_sum(s2), mean_b, inv_den);
            sts16(sbase + SM_P + warp * 64 + ((lane >> 1 & 3) * 8 + (lane >> 3) * 2 + (lane & 1)) * 2, ln_apply2(xr, mean_b, inv_den));
            asm volatile("cp.async.wait_all;" ::: "memory");
            asm volatile("bar.sync 2, 320;" ::: "memory");
        }
        STAMP(0);
        uint32_t va[3];
#pragma unroll
        for (int i = 0; i < 3; i++) {
            const int cc = 3 * warp + i, row = 3 * lane + (cc >> 3);
            va[i] = sbase + row * 128 + (((cc ^ row) & 7) << 4);
        }
        const int gi = g >= 3 ? g - 3 : g;
        unsigned char* odst = p.xa + ((xa_o(head) ^ (g >= 3 ? 4096 : 0)) + (sp * DH + warp * 24 + gi * 8 + t * 2) * 4);
        pin(odst);

#pragma unroll 1
        for (int ph = 0; ph < 2; ph++) {
            if (ph == 1) {
                uint4 qf[6];
#pragma unroll
                for (int i = 0; i < 6; i++) qf[i] = lds128(sbase + SM_Q + t * 96 + i * 16);
                uint32_t ka[3];
#pragma unroll
                for (int j = 0; j < 3; j++) {
                    const int row = 3 * (lane & 15) + j;
                    ka[j] = sbase + row * 128 + ((((lane >> 4) ^ row) & 7) << 4) + warp * TILE_BYTES;
                }
                float s[4] = {0.f, 0.f, 0.f, 0.f};
#pragma unroll 1
                for (int it = 0; it < 4; it++) {
                    const int slot = (it & 1) * 8 + warp;
                    const uint32_t so = (it & 1) * 8 * TILE_BYTES;
                    float c[2][2][4];
                    zero4(c[0][0]); zero4(c[0][1]); zero4(c[1][0]); zero4(c[1][1]);
                    mbar_wait(bar_full + 8 * slot, it >> 1);
#pragma unroll
                    for (int ks = 0; ks < 12; ks++) {
                        const uint32_t a = (ka[ks >> 2] + so) ^ ((ks & 3) << 5);
                        uint32_t f0[4], f1[4];
                        ldsm_x4(f0, a); ldsm_x4(f1, a + 16 * DH * 2);
                        const uint32_t b0 = ks & 1 ? qf[ks >> 1].z : qf[ks >> 1].x, b1 = ks & 1 ? qf[ks >> 1].w : qf[ks >> 1].y;
                        mma_bf16(c[0][ks & 1], f0, b0, b1); mma_bf16(c[1][ks & 1], f1, b0, b1);
                    }
                    if (lane == 0) mbar_arrive8(bar_empty + 8 * slot);
                    const float v = t & 2 ? (t & 1 ? c[1][0][2] + c[1][1][2] : c[1][0][0] + c[1][1][0]) : (t & 1 ? c[0][0][2] + c[0][1][2] : c[0][0][0] + c[0][1][0]);
                    s[0] = s[1]; s[1] = s[2]; s[2] = s[3];
                    s[3] = bfr(bfr(v) * 0.07216878364870322f);
                }
                const float mw = warp_max(fmaxf(fmaxf(s[0], s[1]), fmaxf(s[2], s[3])));
                if (lane == 0) sts32(sbase + SM_MAX + warp * 4, mw);
                cons_sync();
                const float4 ma = lds128f(sbase + SM_MAX), mb = lds128f(sbase + SM_MAX + 16);
                const float m = fmaxf(fmaxf(fmaxf(ma.x, ma.y), fmaxf(ma.z, ma.w)), fmaxf(fmaxf(mb.x, mb.y), fmaxf(mb.z, mb.w)));
                float l = 0.f;
#pragma unroll
                for (int it = 0; it < 4; it++) {
                    const float e = ex2((s[it] - m) * L2E);
                    l += e;
                    sts16(sbase + SM_P + (it * 8 + warp) * 64 + ((g >> 1) * 8 + t * 2 + (g & 1)) * 2, pack_bf(0.f, e));
                }
                l = warp_sum(l);
                if (lane == 0) { sts32(sbase + SM_SUM + warp * 4, l); mbar_arrive(bar_stat); }
                cons_sync();
                STAMP(1);
            }
            float acc[2][3][4];
#pragma unroll
            for (int i = 0; i < 3; i++) { zero4(acc[0][i]); zero4(acc[1][i]); }
            const int nt = ph ? NKT : NQT;
            float scale = 1.f;
#pragma unroll 1
            for (int n = 0; n < nt; n++) {
                const int slot = ph ? (n & (NSLOT - 1)) : QSLOT + n;
                const uint4 w = lds128(sbase + SM_P + n * 64 + t * 16);
                if (n == NKT - 1) { mbar_wait(bar_scale, 0); scale = __uint_as_float(lds32(sbase + SM_MISC + 8)); }
                if (ph) mbar_wait(bar_full + 8 * slot, (n >> 4) & 1);
                uint32_t f[3][4];
#pragma unroll
                for (int i = 0; i < 3; i++) ldsm_x4_t(f[i], va[i] + slot * TILE_BYTES);
#pragma unroll
                for (int i = 0; i < 3; i++) {
                    mma_bf16(acc[0][i], w.x, w.x, w.y, w.y, f[i][0], f[i][1]);
                    mma_bf16(acc[1][i], w.z, w.z, w.w, w.w, f[i][2], f[i][3]);
                }
                if (lane == 0) mbar_arrive(bar_empty + 8 * slot);
            }
            const float v0 = (gi == 0 ? acc[0][0][0] + acc[1][0][0] : gi == 1 ? acc[0][1][0] + acc[1][1][0] : acc[0][2][0] + acc[1][2][0]) * scale;
            const float v1 = (gi == 0 ? acc[0][0][1] + acc[1][0][1] : gi == 1 ? acc[0][1][1] + acc[1][1][1] : acc[0][2][1] + acc[1][2][1]) * scale;
            if (ph == 1) {
                if (g < 6) st2(odst, in_word(v0), in_word(v1));
                break;
            }
            const uint32_t tag = lds32(sbase + SM_MISC);
            const uint32_t t4 = tag % 15 + 1;
            if (g < 3) st2(p.sc->qbuf + b * 96 + warp * 12 + lane, (__float_as_uint(v0) & ~15u) | t4, (__float_as_uint(v1) & ~15u) | t4);
            if (warp < 3) {
                uint2 e[4];
                uint32_t n = 0, bad;
#pragma unroll 1
                do {
                    do __nanosleep(200); while ((int)(now_ns() - (t0 + p.t_q)) < 0);
                    bad = 0;
#pragma unroll
                    for (int i = 0; i < 4; i++) e[i] = ld2(p.sc->qbuf + (head * 4 + i) * 96 + tid);
#pragma unroll
                    for (int i = 0; i < 4; i++) { e[i].x ^= t4; e[i].y ^= t4; bad |= e[i].x | e[i].y; }
                    if (++n > SPIN_LIMIT) __trap();
                } while (__any_sync(0xffffffffu, bad & 15));
#define S_(c) ((__uint_as_float(e[0].c) + __uint_as_float(e[1].c)) + (__uint_as_float(e[2].c) + __uint_as_float(e[3].c)))
                sts32(sbase + SM_Q + (t * 24 + (tid >> 2)) * 4, pack_bf(S_(y), S_(x)));
#undef S_
            }
            cons_sync();
        }
        STAMP(2);
        const uint32_t side = lds32(sbase + SM_MISC + 12) * 4096;
        const uint32_t d16 = kg * 64 + g * 8 + warp, oh = d16 / 12;
        const unsigned char* osrc = p.xa + ((xa_o(oh) ^ side) + ((d16 - oh * 12) * 16 + t * 4) * 4);
        const int r16 = (lane & 7) + ((lane >> 4) << 3), mi = lane >> 3 & 1;
        const uint32_t f32 = sbase + r16 * 32 + ((mi ^ (lane >> 2 & 1)) << 4);
        uint32_t rdst = sbase + SM_RED + (t * 8 + g) * 48 + warp * 4;
        uint32_t bl = sbase + SM_BC + warp * 512 + t * 80, bs = bl + g * 8;
        uint32_t hl = g < 4 ? bl : sbase + SM_ONE;
        uint32_t w1a = f32 + SM_W1 + warp * 512, w2a = f32 + SM_W2 + warp * 1024;
        uint32_t lnd = lane < 2 ? sbase + SM_LN + lane * 32 + warp * 4 : sbase + SM_BC + warp * 512 + 384 + lane * 4;
        const unsigned char* hs = p.xa + (side + warp * 256 + lane * 8);
        const unsigned char* as = p.xa + (XA_A + side + warp * 384 + min(lane, 23) * 16);
        uint32_t al = sbase + SM_BC + warp * 512 + t * 16, at = sbase + SM_BC + warp * 512 + lane * 16;
        uint32_t fl = role, ln = lane;
        pin_u(fl); pin(ln);
        const bool f1 = fl & 2, f2 = fl & 4, odd = ln & 1, first = ln == 0;
        constexpr uint32_t b2 = bar_tail + 8 * (NWP + NF1);
        pin(rdst); pin(bs); pin(hl); pin(w1a); pin(w2a); pin(lnd); pin(hs); pin(as); pin(al); pin(at);
#define F_(i, c) __uint_as_float(e[i].c)
        if (has_wo) {
            uint4 e[4];
#pragma unroll
            for (int i = 0; i < 4; i++) e[i].x = e[i].y = e[i].z = e[i].w = SENT;
            uint32_t n = 0;
            mbar_wait(bar_tail + 8 * CFG_OG, 0);
#pragma unroll 1
            do {
                if (CFG_OSL && n) __nanosleep(CFG_OSL);
#pragma unroll
                for (int i = 0; i < 4; i++) poll4(osrc + i * (DH * 4), e[i]);
                if (++n > SPIN_LIMIT) __trap();
            } while (__any_sync(0xffffffffu, max(max(max4(e[0]), max4(e[1])), max(max4(e[2]), max4(e[3]))) == SENT));
            sts64(bs, pack_bf((F_(0, y) + F_(1, y)) + (F_(2, y) + F_(3, y)), (F_(0, x) + F_(1, x)) + (F_(2, x) + F_(3, x))),
                      pack_bf((F_(0, w) + F_(1, w)) + (F_(2, w) + F_(3, w)), (F_(0, z) + F_(1, z)) + (F_(2, z) + F_(3, z))));
            __syncwarp();
#pragma unroll
            for (int i = 0; i < 4; i++) e[i] = lds128(bl + i * 16);
            STAMP(3);
            const uint32_t wa = sbase + (warp * 16 + r16) * 64 + ((mi ^ (r16 >> 1 & 3)) << 4), wb = wa ^ 32;
            float c0[4], c1[4];
            zero4(c0); zero4(c1);
#pragma unroll
            for (int j = 0; j < NWP; j++) {
                mbar_wait(bar_tail + 8 * j, 0);
                uint32_t f0[4], f1[4];
                ldsm_x4_t(f0, wa + j * 8192); ldsm_x4_t(f1, wb + j * 8192);
                const uint32_t b0 = j & 1 ? e[j >> 1].z : e[j >> 1].x, b1 = j & 1 ? e[j >> 1].w : e[j >> 1].y;
                mma_bf16(c0, f0, b0, b1); mma_bf16(c1, f1, b0, b1);
            }
            sts32(rdst, t & 2 ? (t & 1 ? c1[2] : c1[0]) : (t & 1 ? c0[2] : c0[0]));
            fin_arrive<3>();
        }
        if (f1) {
            constexpr uint32_t b1 = bar_tail + 8 * NWP;
            uint32_t a1[5][4], a3[5][4];
            uint2 e[NG];
#pragma unroll
            for (int i = 0; i < NG; i++) e[i].x = e[i].y = 0;
            uint32_t got = 0, n = 0;
#pragma unroll
            for (int i = 0; i < NB; i++) a3[i][0] = a3[i][1] = a3[i][2] = a3[i][3] = 0;
            mbar_wait(b1, 0);
#pragma unroll
            for (int i = 0; i < NG; i++) ld2p(hs + xa_h(i), e[i], lane < 20);
            mbar_wait(b1 + 8, 0);
#pragma unroll
            for (int i = 0; i < 5; i++) ldsm_x4_t(a1[i], w1a + i * 4096);
            uint4 hb0, hb1;
            uint2 hb2;
            float sv[4];
#pragma unroll 1
            while (true) {
#define S_(f, c) (((f(e[0].c) + f(e[1].c)) + (f(e[2].c) + f(e[3].c))) + (f(e[4].c) + f(e[5].c)))
                const float sx = S_(bf_lo, x), sy = S_(bf_hi, x), sz = S_(bf_lo, y), sw = S_(bf_hi, y), sa = (sx + sy) + (sz + sw);
#undef S_
                const uint32_t h0 = add_bf2(xres.x, pack_bf(sy, sx)), h1 = add_bf2(xres.y, pack_bf(sw, sz));
                sts64(bs, h0, h1);
                __syncwarp();
                hb0 = lds128(hl); hb1 = lds128(hl + 16); hb2 = lds64(hl + 32);
                const float a = bf_lo(h0), b = bf_hi(h0), c = bf_lo(h1), d = bf_hi(h1);
                const float s1 = (a + b) + (c + d), s2 = fmaf(a, a, b * b) + fmaf(c, c, d * d);
                sv[0] = odd ? s2 : s1;
                sv[1] = __shfl_xor_sync(0xffffffffu, odd ? s1 : s2, 1);
                sv[2] = __shfl_xor_sync(0xffffffffu, sv[0], 2);
                sv[3] = __shfl_xor_sync(0xffffffffu, odd ? s1 : s2, 3);
                bool miss = __any_sync(0xffffffffu, sa != sa);
                if (n == 0) STAMP(12);
                if (miss) {
                    const uint4 mx = make_uint4(__vimax3_u16x2(e[0].x, e[0].y, e[1].x), __vimax3_u16x2(e[1].y, e[2].x, e[2].y),
                                                __vimax3_u16x2(e[3].x, e[3].y, e[4].x), __vimax3_u16x2(e[4].y, e[5].x, e[5].y));
#pragma unroll
                    for (int i = 0; i < NG; i++) poll2(hs + xa_h(i), e[i]);
                    ldsm_if<NB, 4096>(a3[0], a3[1], a3[2], w1a + (SM_W3 - SM_W1), b1 + 16, got);
                    if (++n > SPIN_LIMIT) __trap();
                    miss = __any_sync(0xffffffffu, !ok8(mx));
                }
                if (!miss) break;
            }
            STAMP(5);
            float cg[3][4], cu[3][4];
#pragma unroll
            for (int i = 0; i < 3; i++) { zero4(cg[i]); zero4(cu[i]); }
            const uint32_t hb[5][2] = {{hb0.x, hb0.y}, {hb0.z, hb0.w}, {hb1.x, hb1.y}, {hb1.z, hb1.w}, {hb2.x, hb2.y}};
            const float st = (sv[0] + sv[1]) + (sv[2] + sv[3]);
#pragma unroll
            for (int i = 0; i < 4; i++) sv[i] = __shfl_down_sync(0xffffffffu, st, 4 * i + 4);
#pragma unroll
            for (int i = 0; i < 5; i++) mma_bf16(cg[i % 3], a1[i], hb[i][0], hb[i][1]);
            sts32(lnd, ((st + sv[0]) + sv[1]) + (sv[2] + sv[3]));
            sts32(rdst + 32 * 48, odd ? (cg[0][2] + cg[2][2]) + cg[1][2] : (cg[0][0] + cg[2][0]) + cg[1][0]);
            fin_arrive<4>();
            STAMP(6);
            if (__any_sync(0xffffffffu, !got)) {
                mbar_wait(b1 + 16, 0);
#pragma unroll
                for (int i = 0; i < NB; i++) ldsm_x4_t(a3[i], w1a + (SM_W3 - SM_W1) + i * 4096);
            }
            mbar_wait(b1 + 24, 0);
#pragma unroll
            for (int i = NB; i < 5; i++) ldsm_x4_t(a3[i], w1a + (SM_W3 - SM_W1) + i * 4096);
#pragma unroll
            for (int i = 0; i < 5; i++) mma_bf16(cu[i % 3], a3[i], hb[i][0], hb[i][1]);
            sts32(rdst + 64 * 48, odd ? (cu[0][2] + cu[2][2]) + cu[1][2] : (cu[0][0] + cu[2][0]) + cu[1][0]);
            __syncwarp();
            if (first) mbar_arrive(bar_up);
        }
        if (f2) {
            uint32_t a2[NF2][2][4];
#pragma unroll
            for (int i = 0; i < 4; i++) a2[NF2 - 1][0][i] = a2[NF2 - 1][1][i] = 0;
#pragma unroll
            for (int j = 0; j < NF2 - 1; j++) {
                mbar_wait(b2 + 8 * j, 0);
                ldsm_x4_t(a2[j][0], w2a + j * 8192); ldsm_x4_t(a2[j][1], w2a + j * 8192 + 512);
            }
            STAMP(9);
            uint32_t n = 0, got = 0;
            uint4 e[NF2];
#pragma unroll 1
            while (true) {
                const uint4 pa = ld4(as);
                ldsm_if<2, 512>(a2[NF2 - 1][0], a2[NF2 - 1][1], nullptr, w2a + (NF2 - 1) * 8192, b2 + 8 * (NF2 - 1), got);
                if (++n > SPIN_LIMIT) __trap();
                sts128(at, pa);
                __syncwarp();
#pragma unroll
                for (int j = 0; j < CFG_NSPEC; j++) e[j] = lds128v(al + j * 64);
                if (__all_sync(0xffffffffu, ok8(pa))) break;
            }
#pragma unroll
            for (int j = CFG_NSPEC; j < NF2; j++) e[j] = lds128v(al + j * 64);
            STAMP(10);
            float c[6][4];
#pragma unroll
            for (int j = 0; j < 6; j++) zero4(c[j]);
#pragma unroll
            for (int j = 0; j < NF2; j++) { mma_bf16(c[(j % 3) * 2], a2[j][0], e[j].x, e[j].y); mma_bf16(c[(j % 3) * 2 + 1], a2[j][1], e[j].z, e[j].w); }
            if (__any_sync(0xffffffffu, !got)) {
                constexpr int j = NF2 - 1;
                mbar_wait(b2 + 8 * j, 0);
                ldsm_x4_t(a2[j][0], w2a + j * 8192); ldsm_x4_t(a2[j][1], w2a + j * 8192 + 512);
                mma_bf16(c[4], a2[j][0], e[j].x, e[j].y); mma_bf16(c[5], a2[j][1], e[j].z, e[j].w);
            }
            sts32(rdst + 96 * 48, odd ? (((c[0][2] + c[1][2]) + (c[2][2] + c[3][2])) + c[4][2]) + c[5][2] : (((c[0][0] + c[1][0]) + (c[2][0] + c[3][0])) + c[4][0]) + c[5][0]);
            fin_arrive<6>();
        }
#undef F_
    }
}

typedef CUresult (*EncodeTiledFn)(CUtensorMap*, CUtensorMapDataType, cuuint32_t, void*, const cuuint64_t*, const cuuint64_t*,
                                  const cuuint32_t*, const cuuint32_t*, CUtensorMapInterleave, CUtensorMapSwizzle,
                                  CUtensorMapL2promotion, CUtensorMapFloatOOBfill);

void make_map(EncodeTiledFn fn, CUtensorMap* tm, const void* w, const int (&d)[5], const int (&st)[4], const int (&bx)[5],
              CUtensorMapSwizzle sw, int promo) {
    cuuint64_t dims[5], strides[4];
    cuuint32_t box[5], estr[5];
    for (int i = 0; i < 5; i++) { dims[i] = (cuuint64_t)d[i]; box[i] = (cuuint32_t)bx[i]; estr[i] = 1; }
    for (int i = 0; i < 4; i++) strides[i] = (cuuint64_t)st[i];
    fn(tm, CU_TENSOR_MAP_DATA_TYPE_BFLOAT16, 5, const_cast<void*>(w), dims, strides, box, estr, CU_TENSOR_MAP_INTERLEAVE_NONE, sw,
       (CUtensorMapL2promotion)promo, CU_TENSOR_MAP_FLOAT_OOB_FILL_NONE);
}

enum { T_PER, T_LEAD, T_STAG, T_TD, T_PERO, T_F1D, T_PERF, T_F2, T_PER2, T_Q, T_PWO, T_PW13, T_PW2, T_TG, T_N };
#define TUNE_NAMES {"per", "lead", "stag", "td", "pero", "f1d", "perf", "f2", "per2", "q", "pwo", "pw13", "pw2", "tg"}
int g_tune[T_N] = {478, 1320, 110, 175, 289, 190, 117, 1330, 125, 6000, 1, 2, 2, 1700};

}

extern "C" void kernel_launch(void* const* d_in, const int* in_sizes, int n_in, void* d_out, int out_size) {
    (void)in_sizes; (void)n_in; (void)out_size;
    static EncodeTiledFn encode = nullptr;
    static Scratch* scratch = nullptr;
    static unsigned char* xarea = nullptr;
    if (!encode) {
        void* sp = nullptr;
        cudaGetSymbolAddress(&sp, g_scratch);
        scratch = reinterpret_cast<Scratch*>(sp);
        cudaGetSymbolAddress(&sp, g_xarea);
        xarea = reinterpret_cast<unsigned char*>((reinterpret_cast<uintptr_t>(sp) + XA_ALIGN - 1) / XA_ALIGN * XA_ALIGN);
        void* fn = nullptr;
        cudaDriverEntryPointQueryResult st;
        cudaGetDriverEntryPoint("cuTensorMapEncodeTiled", &fn, cudaEnableDefault, &st);
        encode = reinterpret_cast<EncodeTiledFn>(fn);
        cudaFuncSetAttribute(fused_decode_kernel, cudaFuncAttributeMaxDynamicSharedMemorySize, SM_TOTAL);
        int dev = 0, khz = 0, bits = 0;
        cudaGetDevice(&dev);
        if (cudaDeviceGetAttribute(&khz, cudaDevAttrMemoryClockRate, dev) == cudaSuccess &&
            cudaDeviceGetAttribute(&bits, cudaDevAttrGlobalMemoryBusWidth, dev) == cudaSuccess && khz > 0 && bits > 0) {
            const double f = 2619000.0 * 5120.0 / ((double)khz * bits);
            for (int i : {T_PER, T_STAG, T_PERO, T_PERF, T_F2, T_Q}) g_tune[i] = (int)(g_tune[i] * f + 0.5);
        }
        (void)cudaGetLastError();
    }
    const int* T = g_tune;
    KParams p;
    p.x = (const __nv_bfloat16*)d_in[0];
    p.wq = (const __nv_bfloat16*)d_in[3];
    p.out = (__nv_bfloat16*)d_out;
    p.sc = scratch;
    p.xa = xarea;
    p.per = T[T_PER];
    p.stag = T[T_STAG];
    p.t_k0 = (NQT + 1) * T[T_PER] - T[T_LEAD];
    {
        int t = p.t_k0 + 2 * NKT * T[T_PER] + T[T_STAG] * 3 / 2 + T[T_TD];
        for (int i = 0; i < NWP; i++, t += T[T_PERO]) p.item[i] = t;
        for (int i = 0, t1 = t + T[T_F1D]; i < NP1; i++, t1 += T[T_PERF]) p.item[NWP + i] = t1;
        for (int i = 0, t2 = t + T[T_F2]; i < NF2; i++, t2 += T[T_PER2]) p.item[NWP + NP1 + i] = t2;
        for (int i = NITEM; i < 32; i++) p.item[i] = 0;
    }
    p.target = T[T_TG]; p.t_q = T[T_Q]; p.t_fill = p.t_k0 + 55 * T[T_PER];
    for (int i = 0, nw = 0, n1 = 0, n2 = 0; i < NCTA; i++) {
        const int grp = i >> 2;
        const bool f2 = grp % 3 == 2, both = grp == 8 || grp == 23, wo = !both, f1 = !f2 || both;
        p.role[i] = (wo ? 1 | nw / 20 << 3 | nw % 20 << 6 : 0) | (f1 ? 2 | n1 << 11 : 0) | (f2 ? 4 | n2 << 18 : 0);
        nw += wo; n1 += f1; n2 += f2;
    }
    TMaps tm;
    constexpr int R1 = FF * 2, R2 = D_MODEL * 2;
    for (int i = 0; i < 2; i++)
        make_map(encode, &tm.k + i, d_in[1 + i], {64, 96, 1, 1, NHEAD * SK / 32}, {128, TILE_BYTES, TILE_BYTES, TILE_BYTES}, {64, 96, 1, 1, 1}, CU_TENSOR_MAP_SWIZZLE_128B, 2);
    make_map(encode, &tm.wo, d_in[4], {D_MODEL, 2, 4, 2, NHEAD * DH / 16}, {R2, 4 * R2, 2 * R2, 16 * R2}, {32, 2, 4, 2, 8}, CU_TENSOR_MAP_SWIZZLE_64B, T[T_PWO]);
    make_map(encode, &tm.w1, d_in[6], {FF, 2, 4, 2, D_MODEL / 16}, {R1, 4 * R1, 2 * R1, 16 * R1}, {16, 2, 4, 2, 8}, CU_TENSOR_MAP_SWIZZLE_32B, T[T_PW13]);
    make_map(encode, &tm.w3, d_in[7], {FF, 2, 4, 2, D_MODEL / 16}, {R1, 4 * R1, 2 * R1, 16 * R1}, {16, 2, 4, 2, 8}, CU_TENSOR_MAP_SWIZZLE_32B, T[T_PW13]);
    make_map(encode, &tm.w2, d_in[8], {D_MODEL, 2, 4, 4, FF / 32}, {R2, 8 * R2, 2 * R2, 32 * R2}, {16, 2, 4, 4, 8}, CU_TENSOR_MAP_SWIZZLE_32B, T[T_PW2]);
    fused_decode_kernel<<<NCTA, NTHREADS, SM_TOTAL, cudaStreamPerThread>>>(p, tm);
}
```

```cpp
#include <cuda_runtime.h>
#include <cuda_bf16.h>
#include <cuda.h>
#include <stdint.h>
#include <initializer_list>

namespace {

constexpr int D_MODEL = 640;
constexpr int NHEAD = 32;
constexpr int DH = 192;
constexpr int SK = 32768;
constexpr int WIN = 4096;
constexpr int FF = 1536;

constexpr int NCTA = 128;
constexpr int NTHREADS = 256 + 64;
constexpr int TILE_BYTES = 32 * DH * 2;
constexpr int NSLOT = 16;
constexpr int NKT = 32;
constexpr int NQT = 5;
constexpr int QSLOT = NSLOT - NQT;
constexpr int NG = 6;
constexpr int NWP = 8, NP1 = 10, NF2 = 6;
constexpr int NITEM = NWP + NP1 + NF2;
constexpr int NF1 = 4, NA = 2, NB = 2;
constexpr int NTAIL = NWP + NF1 + NF2;

constexpr int INFLIGHT = 5;

constexpr uint32_t sbase = 1024;
constexpr int SM_W1 = NWP * 8192, SM_W3 = SM_W1 + 20480, SM_W2 = SM_W3 + 20480;
constexpr int SM_P = NSLOT * TILE_BYTES;
constexpr int SM_Q = SM_P + 2048;
constexpr int SM_RED = SM_Q + 384;
constexpr int SM_BC = SM_RED + 128 * 48;
constexpr int SM_ONE = SM_BC + 4096;
constexpr int SM_MAX = SM_ONE + 64;
constexpr int SM_SUM = SM_MAX + 32;
constexpr int SM_LN = SM_SUM + 32;
constexpr int SM_MISC = SM_LN + 64;
constexpr int SM_LATE = SM_MISC + 32;
constexpr int SM_BAR = SM_LATE + 32;
constexpr int SM_TOTAL = SM_BAR + 512;
static_assert(SM_TOTAL <= 232448, "shared memory");

struct __align__(128) Scratch {
    uint2 qbuf[NCTA * 96];
    uint4 mbuf[NCTA * 2];
    uint32_t ready[NCTA];
    uint32_t late[32];
    uint32_t epoch;
};
__device__ Scratch g_scratch;
constexpr int XA_ALIGN = 1 << 20;
constexpr uint32_t SENT = 0xffffffffu;
__device__ unsigned char g_xarea[2 * XA_ALIGN];
__host__ __device__ constexpr uint32_t xa_o(uint32_t h) { return (2 * h + ((h ^ (h >> 3) ^ (h >> 4)) & 1)) * 4096; }
__host__ __device__ constexpr uint32_t xa_h(uint32_t i) { return (1 << 18) + (i >> 2) * (3 << 16) + (i & 3) * (1 << 14); }
constexpr uint32_t XA_A = xa_h(NG);

constexpr uint32_t SPIN_LIMIT = 1u << 22;

__device__ __forceinline__ uint32_t smem_u32(const void* p) { return (uint32_t)__cvta_generic_to_shared(p); }
__device__ __forceinline__ uint32_t now_ns() { uint64_t t; asm volatile("mov.u64 %0, %globaltimer;" : "=l"(t)); return (uint32_t)t; }
__device__ __forceinline__ void mbar_init(uint32_t bar, uint32_t cnt) {
    asm volatile("mbarrier.init.shared::cta.b64 [%0], %1;" ::"r"(bar), "r"(cnt) : "memory");
}
__device__ __forceinline__ void mbar_expect_tx(uint32_t bar, uint32_t bytes) {
    asm volatile("mbarrier.arrive.expect_tx.shared::cta.b64 _, [%0], %1;" ::"r"(bar), "r"(bytes) : "memory");
}
__device__ __forceinline__ void mbar_arrive(uint32_t bar) {
    asm volatile("mbarrier.arrive.shared::cta.b64 _, [%0];" ::"r"(bar) : "memory");
}
__device__ __forceinline__ void mbar_arrive8(uint32_t bar) {
    asm volatile("mbarrier.arrive.shared::cta.b64 _, [%0], 8;" ::"r"(bar) : "memory");
}
__device__ __forceinline__ bool mbar_test(uint32_t bar, uint32_t parity) {
    uint32_t ok;
    asm volatile("{\n.reg .pred p;\nmbarrier.test_wait.parity.shared::cta.b64 p, [%1], %2;\nselp.u32 %0, 1, 0, p;\n}"
                 : "=r"(ok) : "r"(bar), "r"(parity) : "memory");
    return ok;
}
__device__ __forceinline__ void mbar_wait(uint32_t bar, uint32_t parity) {
    asm volatile("{\n.reg .pred p;\nW_%=:\nmbarrier.try_wait.parity.shared::cta.b64 p, [%0], %1;\n@!p bra.uni W_%=;\n}" ::"r"(bar), "r"(parity) : "memory");
}
__device__ __forceinline__ void mbar_wait_after(uint32_t bar, uint32_t dump, float v) {
    uint32_t ok;
    asm volatile("{\n.reg .pred p;\nmbarrier.try_wait.parity.shared::cta.b64 p, [%1], 0;\nselp.u32 %0, 1, 0, p;\n}" : "=r"(ok) : "r"(bar) : "memory");
    asm volatile("st.volatile.shared.f32 [%0], %1;" ::"r"(dump), "f"(v) : "memory");
    if (__builtin_expect(!ok, 0)) mbar_wait(bar, 0);
}
__device__ __forceinline__ void tma_load_at(uint32_t when, uint32_t dst, const CUtensorMap* tm, int c0, int c4, uint32_t bar, uint64_t pol) {
    asm volatile("{\n.reg .pred p, e;\n.reg .b64 t;\n.reg .b32 lo, hi;\nelect.sync _|e, -1;\n"
                 "W_%=:\nmov.u64 t, %globaltimer;\nmov.b64 {lo, hi}, t;\nsub.u32 lo, lo, %7;\nsetp.lt.s32 p, lo, 0;\n@p bra.uni W_%=;\n"
                 "@e cp.async.bulk.tensor.5d.shared::cluster.global.mbarrier::complete_tx::bytes.L2::cache_hint [%0], [%1, {%3, %5, %5, %5, %4}], [%2], %6;\n}"
                 ::"r"(dst), "l"(reinterpret_cast<uint64_t>(tm)), "r"(bar), "r"(c0), "r"(c4), "r"(0), "l"(pol), "r"(when) : "memory");
}
__device__ __forceinline__ void pin(uint32_t& v) { asm volatile("shfl.sync.bfly.b32 %0, %0, 0, 31, -1;" : "+r"(v) :: "memory"); }
__device__ __forceinline__ void pin_u(uint32_t& v) { asm volatile("shfl.sync.idx.b32 %0, %0, 0, 31, -1;" : "+r"(v) :: "memory"); }
template <class T> __device__ __forceinline__ void pin(T*& v) {
    asm volatile("{\n.reg .b32 a, b;\nmov.b64 {a, b}, %0;\nshfl.sync.bfly.b32 a, a, 0, 31, -1;\nshfl.sync.bfly.b32 b, b, 0, 31, -1;\nmov.b64 %0, {a, b};\n}" : "+l"(v) :: "memory");
}
__device__ __forceinline__ void sts16(uint32_t a, uint32_t v) { asm volatile("st.shared.u16 [%0], %1;" ::"r"(a), "h"((unsigned short)v) : "memory"); }
__device__ __forceinline__ void sts32(uint32_t a, float v) { asm volatile("st.shared.f32 [%0], %1;" ::"r"(a), "f"(v) : "memory"); }
__device__ __forceinline__ void sts32(uint32_t a, uint32_t v) { asm volatile("st.shared.u32 [%0], %1;" ::"r"(a), "r"(v) : "memory"); }
__device__ __forceinline__ void sts64(uint32_t a, uint32_t x, uint32_t y) { asm volatile("st.shared.v2.u32 [%0], {%1, %2};" ::"r"(a), "r"(x), "r"(y) : "memory"); }
__device__ __forceinline__ void sts128(uint32_t a, const uint4& v) { asm volatile("st.shared.v4.u32 [%0], {%1, %2, %3, %4};" ::"r"(a), "r"(v.x), "r"(v.y), "r"(v.z), "r"(v.w) : "memory"); }
__device__ __forceinline__ void cons_sync() { asm volatile("bar.sync 1, 256;" ::: "memory"); }
template <int ID> __device__ __forceinline__ void fin_arrive() { asm volatile("bar.arrive %0, 288;" ::"n"(ID) : "memory"); }
template <int ID> __device__ __forceinline__ void fin_sync() { asm volatile("bar.sync %0, 288;" ::"n"(ID) : "memory"); }

__device__ __forceinline__ uint4 lds128(uint32_t a) {
    uint4 v;
    asm volatile("ld.shared.v4.u32 {%0,%1,%2,%3}, [%4];" : "=r"(v.x), "=r"(v.y), "=r"(v.z), "=r"(v.w) : "r"(a) : "memory");
    return v;
}
__device__ __forceinline__ uint4 lds128v(uint32_t a) {
    uint4 v;
    asm volatile("ld.volatile.shared.v4.u32 {%0,%1,%2,%3}, [%4];" : "=r"(v.x), "=r"(v.y), "=r"(v.z), "=r"(v.w) : "r"(a) : "memory");
    return v;
}
__device__ __forceinline__ float4 lds128f(uint32_t a) {
    float4 v;
    asm volatile("ld.shared.v4.f32 {%0,%1,%2,%3}, [%4];" : "=f"(v.x), "=f"(v.y), "=f"(v.z), "=f"(v.w) : "r"(a) : "memory");
    return v;
}
__device__ __forceinline__ uint2 lds64(uint32_t a) {
    uint2 v;
    asm volatile("ld.shared.v2.u32 {%0,%1}, [%2];" : "=r"(v.x), "=r"(v.y) : "r"(a) : "memory");
    return v;
}
__device__ __forceinline__ uint32_t lds32(uint32_t a) {
    uint32_t v;
    asm volatile("ld.shared.u32 %0, [%1];" : "=r"(v) : "r"(a) : "memory");
    return v;
}
__device__ __forceinline__ float sum8(uint32_t a) {
    const float4 x = lds128f(a), y = lds128f(a + 16);
    return ((x.x + x.y) + (x.z + x.w)) + ((y.x + y.y) + (y.z + y.w));
}
__device__ __forceinline__ void ldsm_x4(uint32_t* r, uint32_t a) {
    asm volatile("ldmatrix.sync.aligned.m8n8.x4.shared.b16 {%0,%1,%2,%3}, [%4];"
                 : "=r"(r[0]), "=r"(r[1]), "=r"(r[2]), "=r"(r[3]) : "r"(a) : "memory");
}
__device__ __forceinline__ void ldsm_x4_t(uint32_t* r, uint32_t a) {
    asm volatile("ldmatrix.sync.aligned.m8n8.x4.trans.shared.b16 {%0,%1,%2,%3}, [%4];"
                 : "=r"(r[0]), "=r"(r[1]), "=r"(r[2]), "=r"(r[3]) : "r"(a) : "memory");
}
template <int STRIDE>
__device__ __forceinline__ void ldsm_if(uint32_t* r0, uint32_t* r1, uint32_t a, uint32_t bar, uint32_t& got) {
        asm volatile("{\n.reg .pred p, q;\nsetp.eq.u32 q, %8, 0;\nmbarrier.test_wait.parity.shared::cta.b64 p, [%10], 0;\nand.pred p, p, q;\n"
                     "@p ldmatrix.sync.aligned.m8n8.x4.trans.shared.b16 {%0,%1,%2,%3}, [%9];\n"
                     "@p ldmatrix.sync.aligned.m8n8.x4.trans.shared.b16 {%4,%5,%6,%7}, [%9+%11];\n@p mov.u32 %8, 1;\n}"
                     : "+r"(r0[0]), "+r"(r0[1]), "+r"(r0[2]), "+r"(r0[3]), "+r"(r1[0]), "+r"(r1[1]), "+r"(r1[2]), "+r"(r1[3]), "+r"(got)
                     : "r"(a), "r"(bar), "n"(STRIDE) : "memory");
}
__device__ __forceinline__ void mma_bf16(float* c, uint32_t a0, uint32_t a1, uint32_t a2, uint32_t a3, uint32_t b0, uint32_t b1) {
    asm volatile("mma.sync.aligned.m16n8k16.row.col.f32.bf16.bf16.f32 {%0,%1,%2,%3}, {%4,%5,%6,%7}, {%8,%9}, {%0,%1,%2,%3};"
                 : "+f"(c[0]), "+f"(c[1]), "+f"(c[2]), "+f"(c[3]) : "r"(a0), "r"(a1), "r"(a2), "r"(a3), "r"(b0), "r"(b1));
}
__device__ __forceinline__ void mma_bf16(float* c, const uint32_t* a, uint32_t b0, uint32_t b1) { mma_bf16(c, a[0], a[1], a[2], a[3], b0, b1); }
__device__ __forceinline__ void zero4(float* c) { c[0] = c[1] = c[2] = c[3] = 0.f; }
__device__ __forceinline__ float bf_lo(uint32_t u) { return __uint_as_float(u << 16); }
__device__ __forceinline__ float bf_hi(uint32_t u) { return __uint_as_float(u & 0xffff0000u); }
__device__ __forceinline__ uint32_t pack_bf(float hi, float lo) { uint32_t r; asm("cvt.rn.bf16x2.f32 %0, %1, %2;" : "=r"(r) : "f"(hi), "f"(lo)); return r; }
__device__ __forceinline__ uint32_t add_bf2(uint32_t a, uint32_t b) { uint32_t r; asm("add.rn.bf16x2 %0, %1, %2;" : "=r"(r) : "r"(a), "r"(b)); return r; }
__device__ __forceinline__ float bfr(float x) { return __uint_as_float(pack_bf(x, 0.f)); }

__device__ __forceinline__ uint32_t in_word(float v) { return __float_as_uint(v); }
__device__ __forceinline__ void st1(void* p, uint32_t v) {
    asm volatile("st.relaxed.gpu.global.u32 [%0], %1;" ::"l"(p), "r"(v) : "memory");
}
__device__ __forceinline__ void st16(void* p, uint32_t v) {
    asm volatile("st.relaxed.gpu.global.u16 [%0], %1;" ::"l"(p), "h"((unsigned short)v) : "memory");
}
__device__ __forceinline__ void st2(void* p, uint32_t a, uint32_t b) {
    asm volatile("st.relaxed.gpu.global.v2.u32 [%0], {%1, %2};" ::"l"(p), "r"(a), "r"(b) : "memory");
}
__device__ __forceinline__ void st4(void* p, uint32_t a, uint32_t b, uint32_t c, uint32_t d) {
    asm volatile("st.relaxed.gpu.global.v4.u32 [%0], {%1, %2, %3, %4};" ::"l"(p), "r"(a), "r"(b), "r"(c), "r"(d) : "memory");
}
__device__ __forceinline__ uint32_t ld1(const void* p) {
    uint32_t v;
    asm volatile("ld.relaxed.gpu.global.u32 %0, [%1];" : "=r"(v) : "l"(p) : "memory");
    return v;
}
__device__ __forceinline__ uint2 ld2(const void* p) {
    uint2 v;
    asm volatile("ld.relaxed.gpu.global.v2.u32 {%0, %1}, [%2];" : "=r"(v.x), "=r"(v.y) : "l"(p) : "memory");
    return v;
}
__device__ __forceinline__ uint4 ld4(const void* p) {
    uint4 v;
    asm volatile("ld.relaxed.gpu.global.v4.u32 {%0, %1, %2, %3}, [%4];" : "=r"(v.x), "=r"(v.y), "=r"(v.z), "=r"(v.w) : "l"(p) : "memory");
    return v;
}
__device__ __forceinline__ void ld2p(const void* p, uint2& v, bool on) {
    asm volatile("{\n.reg .pred q;\nsetp.ne.u32 q, %3, 0;\n@q ld.relaxed.gpu.global.v2.u32 {%0, %1}, [%2];\n}"
                 : "+r"(v.x), "+r"(v.y) : "l"(p), "r"((uint32_t)on) : "memory");
}
__device__ __forceinline__ void poll2(const void* p, uint2& v) {
    asm volatile("{\n.reg .pred q, r;\nsetp.nan.bf16x2 q|r, %0, %1;\nor.pred q, q, r;\n@q ld.relaxed.gpu.global.v2.u32 {%0, %1}, [%2];\n}"
                 : "+r"(v.x), "+r"(v.y) : "l"(p) : "memory");
}
__device__ __forceinline__ bool ok8(const uint4& v) {
    const uint32_t m = __vimax3_u16x2(__vimax3_u16x2(v.x, v.y, v.z), v.w, v.w);
    return __vimax3_u16x2(m, m << 16, m >> 16) != SENT;
}
__device__ __forceinline__ void poll4(const void* p, uint4& v) {
    asm volatile("{\n.reg .pred q;\n.reg .u32 m;\nmax.u32 m, %0, %1;\nmax.u32 m, m, %2;\nmax.u32 m, m, %3;\nsetp.eq.u32 q, m, 0xffffffff;\n"
                 "@q ld.relaxed.gpu.global.v4.u32 {%0, %1, %2, %3}, [%4];\n}"
                 : "+r"(v.x), "+r"(v.y), "+r"(v.z), "+r"(v.w) : "l"(p) : "memory");
}
__device__ __forceinline__ uint32_t max4(const uint4& v) { return max(max(v.x, v.y), max(v.z, v.w)); }
__device__ __forceinline__ void pkt_st2(uint4* p, float a, float b, uint32_t tag) {
    asm volatile("st.relaxed.gpu.global.v2.b64 [%0], {%1, %2};" ::"l"(p), "l"(((uint64_t)tag << 32) | __float_as_uint(a)), "l"(((uint64_t)tag << 32) | __float_as_uint(b)) : "memory");
}
__device__ __forceinline__ void pkt_ld2(const uint4* p, uint64_t& a, uint64_t& b) {
    asm volatile("ld.relaxed.gpu.global.v2.b64 {%0, %1}, [%2];" : "=l"(a), "=l"(b) : "l"(p) : "memory");
}
__device__ __forceinline__ bool tag_ok(uint64_t v, uint32_t tag) { return (uint32_t)(v >> 32) == tag; }
__device__ __forceinline__ float val_of(uint64_t v) { return __uint_as_float((uint32_t)v); }

__device__ __forceinline__ float warp_sum(float v) {
#pragma unroll
    for (int o = 16; o > 0; o >>= 1) v += __shfl_xor_sync(0xffffffffu, v, o);
    return v;
}
__device__ __forceinline__ float warp_max(float v) {
#pragma unroll
    for (int o = 16; o > 0; o >>= 1) v = fmaxf(v, __shfl_xor_sync(0xffffffffu, v, o));
    return v;
}
__device__ __forceinline__ float sqrt_fast(float x) { float r; asm("sqrt.approx.ftz.f32 %0, %1;" : "=f"(r) : "f"(x)); return r; }
__device__ __forceinline__ float rcp_fast(float x) { float r; asm("rcp.approx.ftz.f32 %0, %1;" : "=f"(r) : "f"(x)); return r; }
__device__ __forceinline__ float ex2(float x) { float r; asm("ex2.approx.ftz.f32 %0, %1;" : "=f"(r) : "f"(x)); return r; }
constexpr float L2E = 1.4426950408889634f;
__device__ __forceinline__ void ln_finish(float s1, float s2, float& mean_b, float& inv_den) {
    const float mean = s1 * (1.0f / D_MODEL);
    const float var = fmaxf(fmaf(-mean, mean, s2 * (1.0f / D_MODEL)), 0.f);
    mean_b = bfr(mean);
    inv_den = rcp_fast(bfr(sqrt_fast(bfr(bfr(var) + 1e-5f))));
}
__device__ __forceinline__ uint32_t ln_apply2(uint32_t u, float mean_b, float inv_den) {
    const uint32_t d = pack_bf(bf_hi(u) - mean_b, bf_lo(u) - mean_b);
    return pack_bf(bf_hi(d) * inv_den, bf_lo(d) * inv_den);
}
__device__ __forceinline__ void ln_acc(uint32_t u, float& s1, float& s2) {
    const float a = bf_lo(u), b = bf_hi(u);
    s1 += a + b;
    s2 = fmaf(a, a, fmaf(b, b, s2));
}
__device__ __forceinline__ float silu_b(float g) { return bfr(__fdividef(g, 1.0f + ex2(-g * L2E))); }

struct KParams {
    const __nv_bfloat16* wq;
    const __nv_bfloat16* x;
    __nv_bfloat16* out;
    Scratch* sc;
    unsigned char* xa;
    int t_k0, per, stag;
    int target;
    int t_q, t_fill;
    uint32_t item[32];
    uint32_t role[NCTA];
};
struct TMaps { CUtensorMap k, v, wo, w1, w3, w2; };

__global__ void __launch_bounds__(NTHREADS, 1)
fused_decode_kernel(const __grid_constant__ KParams p, const __grid_constant__ TMaps tm) {
    extern __shared__ __align__(1024) unsigned char smem[];
    const int tid = threadIdx.x;
    const int b = blockIdx.x;
    const int head = b >> 2, sp = b & 3;
    {
        const char* a = reinterpret_cast<const char*>(p.wq) + (uint32_t)((sp * 160 + (tid >> 2)) * (NHEAD * DH * 2) + head * (DH * 2) + (tid & 3) * 128);
        asm volatile("prefetch.global.L2 [%0];" ::"l"(a) : "memory");
    }
    if (tid < 256) {
        const uint32_t r = tid >> 3, ch = tid & 7;
        const char* src = reinterpret_cast<const char*>(p.wq) + ((sp * 160 + r) * (NHEAD * DH * 2) + head * (DH * 2) + ch * 16);
#pragma unroll
        for (int i = 0; i < NQT; i++) {
#pragma unroll
            for (int j = 0; j < 3; j++)
                asm volatile("cp.async.cg.shared.global [%0], [%1], 16;"
                             ::"r"(sbase + (QSLOT + i) * TILE_BYTES + (3 * r + j) * 128 + ((ch ^ ((3 * r + j) & 7)) << 4)),
                               "l"(src + (size_t)i * 32 * (NHEAD * DH * 2) + j * 128) : "memory");
        }
    }
    const uint32_t t0 = now_ns();
    const int warp = __shfl_sync(0xffffffffu, tid >> 5, 0), lane = tid & 31;
    const uint32_t role = p.role[b];
    const int kg = role >> 3 & 7, ng = role >> 6 & 31;
    const int u1 = role >> 11 & 127, u2 = role >> 18;
    const bool has_wo = role & 1, has_f1 = role & 2, has_f2 = role & 4;
    constexpr uint32_t bar_full = sbase + SM_BAR;
    constexpr uint32_t bar_empty = sbase + SM_BAR + 128;
    constexpr uint32_t bar_tail = sbase + SM_BAR + 256;
    constexpr uint32_t bar_scale = bar_tail + 8 * NTAIL;
    constexpr uint32_t bar_stat = bar_scale + 8;
    constexpr uint32_t bar_up = bar_scale + 16;

    if (warp == 8) {
        if (smem_u32(smem) != sbase) __trap();
        uint64_t pol;
        asm volatile("createpolicy.fractional.L2::evict_first.b64 %0, 1.0;" : "=l"(pol));
        sts32(sbase + SM_LATE + (lane & 7) * 4, 0u);
        if (lane == 0) {
#pragma unroll
            for (int i = 0; i < 32 + NTAIL + 3; i++)
                mbar_init(bar_full + 8 * i, (i >= 16 && i < 32) || i > 32 + NTAIL ? 8 : i == 32 + NWP ? NA : i == 33 + NWP ? 5 - NA : i == 34 + NWP ? NB : i == 35 + NWP ? 5 - NB : 1);
#pragma unroll
            for (int i = 0; i < 6; i++) asm volatile("prefetch.tensormap [%0];" ::"l"(reinterpret_cast<uint64_t>(&tm.k + i)) : "memory");
            asm volatile("fence.mbarrier_init.release.cluster;" ::: "memory");
        }
        __syncwarp();
        asm volatile("bar.arrive 2, 320;" ::: "memory");
        const uint32_t tu = __shfl_sync(0xffffffffu, t0, 0);
        if (b == 0 && lane < 8) st1(p.sc->late + lane, lane ? 0 : (tu & 0xffffffu) | 1u << 24);
        const int tile0 = (head * SK + (SK - WIN)) / 32 + sp;
        uint32_t tk = tu + p.t_k0 + sp * p.stag, tw = tk, acc = 0;
        int slip = 0, slip0 = 0, w = 0, d0 = 0;
#pragma unroll 1
        for (int n = 0; n < 2 * NKT; n++) {
            const int slot = n & (NSLOT - 1);
            mbar_wait(bar_empty + 8 * slot, (((n + NQT) >> 4) & 1) ^ 1);
            if (lane == 0) mbar_expect_tx(bar_full + 8 * slot, TILE_BYTES);
            bool more;
            do {
                const uint32_t t = now_ns();
                if (__all_sync(0xffffffffu, mbar_test(bar_full + 8 * (w & (NSLOT - 1)), (w >> 4) & 1))) {
                    acc += t - tw;
                    tw += p.per;
                    w++;
                    if ((w & 7) == 0) {
                        if (lane == 0) asm volatile("red.relaxed.gpu.global.add.u32 [%0], %1;" ::"l"(p.sc->late + (w >> 3)), "r"((1u << 24) + min(max(((int)acc >> 3) + d0, 0), 65535)) : "memory");
                        acc = 0;
                    }
                }
                more = __any_sync(0xffffffffu, (int)(t - tk) < slip - 60) || w <= n - INFLIGHT;
            } while (more);
            tma_load_at(tk + slip, sbase + slot * TILE_BYTES, &tm.k + (n >> 5), 0, tile0 + (n & (NKT - 1)) * 4, bar_full + 8 * slot, pol);
            tk += p.per;
            if ((n & 7) == 5 && lane < 2)
                asm volatile("cp.async.cg.shared.global [%0], [%1], 16;" ::"r"(sbase + SM_LATE + lane * 16), "l"(p.sc->late + lane * 4) : "memory");
            const uint32_t org = lds32(sbase + SM_LATE);
            if (org) d0 = (int)((tu - org) << 8) >> 8;
            uint32_t rep = lds32(sbase + SM_LATE + (n >> 3) * 4);
            const uint32_t rep0 = lds32(sbase + SM_LATE + (max(n - 8, 0) >> 3) * 4);
            if (!(rep >> 30)) rep = rep0;
            if (rep >> 30) slip = max((int)((float)(rep & 0xffffffu) * rcp_fast((float)(rep >> 24))) - p.target - d0, -700);
            if (n == 24) slip0 = slip;
        }
        slip += min(max((slip - slip0) * 90 >> 8, -200), 250);
        const int seg = (lane >= NWP) + (lane >= NWP + NP1), i = lane - (seg == 0 ? 0 : seg == 1 ? NWP : NWP + NP1);
        const bool todo = lane < NITEM && (role >> seg & 1);
        const uint32_t len = seg == 1 ? 4096 : 8192, dst = sbase + (seg == 0 ? 0 : seg == 1 ? SM_W1 : SM_W2) + i * len;
        const int w3 = seg == 1 && i >= 5;
        const uint32_t mi = seg == 2 ? 3 : seg + w3;
        const int c0 = seg == 0 ? ng * 32 : seg == 1 ? u1 * 16 : u2 * 16;
        const int c4 = (seg == 0 ? kg * 64 : w3 * -40) + i * 8;
        const uint32_t bar = bar_tail + 8 * (seg == 0 ? i : seg == 1 ? NWP + (i >= NA) + w3 + (i >= 5 + NB) : NWP + NF1 + i);
        const uint32_t tn = tu + slip + p.item[lane];
        if (todo) mbar_expect_tx(bar, len);
        const uint32_t c04 = c0 | c4 << 16, db = dst | (bar - bar_tail) << 18 | mi << 28;
#pragma unroll 1
        for (uint32_t left = __ballot_sync(0xffffffffu, todo); left; left &= left - 1) {
            const int k = __ffs(left) - 1;
            const uint32_t kc = __shfl_sync(0xffffffffu, c04, k), kd = __shfl_sync(0xffffffffu, db, k), kt = __shfl_sync(0xffffffffu, tn, k);
            mbar_wait(bar_empty + 8 * (k < NWP ? 5 : 12), k < NWP);
            tma_load_at(kt, kd & 0x3ffff, &tm.wo + (kd >> 28), kc & 0xffff, kc >> 16, bar_tail + (kd >> 18 & 0x3ff), pol);
        }
    } else if (warp == 9) {
        const uint32_t tag = ld1(&p.sc->epoch) + 1;
        const uint32_t aoff = XA_A + (u1 >> 1 & 7) * 384 + (u1 >> 4) * 64 + (u1 & 1) * 32, hoff = xa_h(kg) + (ng & 3) * 512 + (ng >> 2) * 32;
        sts32(sbase + SM_ONE + (lane & 15) * 4, 0x3f803f80u);
        const uint32_t ooff = xa_o(head) + sp * (DH * 4);
        unsigned char* slot[4] = {p.xa + (ooff + lane * 16), p.xa + ((ooff + 512 + (lane & 15) * 16) ^ (lane >> 4) << 12), p.xa + ((ooff + lane * 16) ^ 4096),
                                  p.xa + (lane < 16 ? (has_wo ? hoff + (lane >> 2 & 1) * 4096 + (lane >> 1 & 1) * 256 + (lane & 1) * 16 : ooff) : has_f1 ? aoff + (lane >> 1 & 1) * 4096 + (lane & 1) * 16 : ooff)};
#pragma unroll
        for (int i = 0; i < 2; i++) st4(p.sc->qbuf + b * 96 + i * 32 + lane * 2, 0, 0, 0, 0);
        sts32(sbase + SM_MISC, tag);
        asm volatile("bar.sync 2, 320;" ::: "memory");
        while (!mbar_test(bar_stat, 0)) __nanosleep(200);
        const float4 ma = lds128f(sbase + SM_MAX), mb = lds128f(sbase + SM_MAX + 16);
        const float m = fmaxf(fmaxf(fmaxf(ma.x, ma.y), fmaxf(ma.z, ma.w)), fmaxf(fmaxf(mb.x, mb.y), fmaxf(mb.z, mb.w)));
        while ((int)(now_ns() - (t0 + p.t_fill)) < 0) __nanosleep(200);
        pkt_st2(p.sc->mbuf + b * 2 + (lane & 1), m, sum8(sbase + SM_SUM), tag);
#pragma unroll
        for (int i = 0; i < 4; i++) st4(slot[i], SENT, SENT, SENT, SENT);
        uint32_t ack = SENT;
#pragma unroll
        for (int i = 0; i < 4; i++) { uint32_t v; asm volatile("atom.relaxed.gpu.global.exch.b32 %0, [%1], -1;" : "=r"(v) : "l"(slot[i]) : "memory"); ack &= v; }
        if (__any_sync(0xffffffffu, ack != SENT)) __trap();
        if (lane == 0) st1(p.sc->ready + b, tag);
        int vote = 0;
#pragma unroll 1
        for (int r = 0; r < 5 && (!vote || (int)(now_ns() - (t0 + p.t_fill)) < 3500); r++) {
            __nanosleep(100);
            uint32_t d;
            asm volatile("{\n.reg .pred p, q;\n.reg .b32 a, b, c0, c1;\nmov.b32 c0, 0;\nmov.b32 c1, 0;\n"
                         "atom.relaxed.gpu.global.exch.b32 a, [%1], -1;\natom.relaxed.gpu.global.exch.b32 b, [%2], -1;\n"
                         "setp.eq.u32 p, a, -1;\n@p mov.u32 c0, %%clock;\nsetp.eq.u32 q, b, -1;\n@q mov.u32 c1, %%clock;\nsub.u32 %0, c1, c0;\n}"
                         : "=r"(d) : "l"(r & 1 ? slot[2] : slot[0]), "l"(r & 1 ? slot[0] : slot[2]) : "memory");
            vote += (d > 90) == (r & 1) ? 1 : -1;
        }
        const uint32_t side = __shfl_sync(0xffffffffu, vote, 0) > 0;
        uint32_t n = 0;
        {
            uint64_t em, el;
            while (true) {
                const uint4 e = ld4(p.sc->ready + lane * 4);
                pkt_ld2(p.sc->mbuf + (head * 4 + (lane & 3)) * 2, em, el);
                if (__all_sync(0xffffffffu, e.x == tag && e.y == tag && e.z == tag && e.w == tag && tag_ok(em, tag) && tag_ok(el, tag))) break;
                __nanosleep(500);
                if (++n > SPIN_LIMIT) __trap();
            }
            float M = fmaxf(val_of(em), __shfl_xor_sync(0xffffffffu, val_of(em), 1));
            M = fmaxf(M, __shfl_xor_sync(0xffffffffu, M, 2));
            float L = ex2((val_of(em) - M) * L2E) * val_of(el);
            L += __shfl_xor_sync(0xffffffffu, L, 1);
            L += __shfl_xor_sync(0xffffffffu, L, 2);
            if (lane == 0) {
                sts64(sbase + SM_MISC + 8, __float_as_uint(__fdividef(ex2((m - M) * L2E), L)), side);
                mbar_arrive(bar_scale);
                if (b == 0) p.sc->epoch = tag;
            }
        }
        unsigned char* hdst = p.xa + (hoff + (side ^ 1) * 4096 + (lane >> 4) * 256 + (lane & 15) * 2);
        unsigned char* hdst2 = p.xa + (hoff + side * 4096 + (lane >> 4) * 256 + (lane & 15) * 2);
        unsigned char* adst = p.xa + (aoff + (lane >> 4) * 4096 + (lane & 15) * 2);
        __nv_bfloat16* odst = p.out + u2 * 16 + (lane & 15);
        uint32_t r0 = sbase + SM_RED + lane * 48, r1 = sbase + SM_RED + (lane & 15) * 48;
        uint32_t res;
        asm volatile("ld.global.nc.u16 %0, [%1];" : "=r"(res) : "l"(p.x + u2 * 16 + (lane & 15)));
        pin(hdst); pin(hdst2); pin(adst); pin(odst); pin(r0); pin(r1);
        if (has_wo) {
            fin_sync<3>();
            const uint32_t v = pack_bf(0.f, sum8(r0));
            st16(hdst, v); st16(hdst2, v);
        }
        if (has_f1) {
            fin_sync<4>();
            float mean_b, inv_den;
            ln_finish(sum8(sbase + SM_LN), sum8(sbase + SM_LN + 32), mean_b, inv_den);
            const float gr = fmaf(-mean_b, sum8(r1 + 48 * 48), sum8(r1 + 32 * 48)) * inv_den;
            mbar_wait_after(bar_up, r0, gr);
            const float gs = bfr(gr);
            const float up = bfr(fmaf(-mean_b, sum8(r1 + 80 * 48), sum8(r1 + 64 * 48)) * inv_den);
            st16(adst, pack_bf(0.f, silu_b(gs) * up));
            if (b == 0 && lane < 8) st1(p.sc->late + lane, 0);
        }
        if (has_f2) {
            mbar_wait(bar_tail + 8 * (NWP + NF1 + 3), 0);
            const unsigned char* hsrc = p.xa + ((lane >> 4) * (1 << 14) + side * 4096 + (u2 & 7) * 256 + (u2 >> 3) * 32 + (lane & 15) * 2);
            uint32_t e[3];
            do {
#pragma unroll
                for (int i = 0; i < 3; i++) asm volatile("ld.relaxed.gpu.global.u16 %0, [%1];" : "=r"(e[i]) : "l"(hsrc + xa_h(2 * i)) : "memory");
                if (++n > SPIN_LIMIT) __trap();
            } while (__any_sync(0xffffffffu, max(max(e[0], e[1]), e[2]) == 0xffffu));
            float f[3];
#pragma unroll
            for (int i = 0; i < 3; i++) f[i] = bf_lo(e[i]) + bf_lo(__shfl_xor_sync(0xffffffffu, e[i], 16));
            res = add_bf2(res, pack_bf(0.f, (f[0] + f[1]) + f[2]));
            pin(res);
            fin_sync<6>();
            asm volatile("st.global.u16 [%0], %1;" ::"l"(odst), "h"((unsigned short)add_bf2(res, pack_bf(0.f, sum8(r1 + 96 * 48)))) : "memory");
        }
    } else {
        const int g = lane >> 2, t = lane & 3;
        uint2 xres;
        {
            uint32_t xr;
            uint2 xu[5];
            const char* xb = reinterpret_cast<const char*>(p.x);
            asm volatile("ld.global.nc.u16 %0, [%1];" : "=r"(xr) : "l"(xb + (sp * 160 + min(tid, 159)) * 2));
#pragma unroll
            for (int i = 0; i < 5; i++) asm volatile("ld.global.nc.v2.u32 {%0, %1}, [%2];" : "=r"(xu[i].x), "=r"(xu[i].y) : "l"(xb + i * 256 + lane * 8));
            asm volatile("ld.global.nc.v2.u32 {%0, %1}, [%2];" : "=r"(xres.x), "=r"(xres.y) : "l"(xb + min(g, 4) * 256 + warp * 32 + t * 8));
            if (lane >= 20) xres.x = xres.y = 0;
            float s1 = 0.f, s2 = 0.f, mean_b, inv_den;
#pragma unroll
            for (int i = 0; i < 5; i++) { ln_acc(xu[i].x, s1, s2); ln_acc(xu[i].y, s1, s2); }
            ln_finish(warp_sum(s1), warp_sum(s2), mean_b, inv_den);
            sts16(sbase + SM_P + warp * 64 + ((lane >> 1 & 3) * 8 + (lane >> 3) * 2 + (lane & 1)) * 2, ln_apply2(xr, mean_b, inv_den));
            asm volatile("cp.async.wait_all;" ::: "memory");
            asm volatile("bar.sync 2, 320;" ::: "memory");
        }
        uint32_t va[3];
#pragma unroll
        for (int i = 0; i < 3; i++) {
            const int cc = 3 * warp + i, row = 3 * lane + (cc >> 3);
            va[i] = sbase + row * 128 + (((cc ^ row) & 7) << 4);
        }
        const int gi = g >= 3 ? g - 3 : g;
        unsigned char* odst = p.xa + ((xa_o(head) ^ (g >= 3 ? 4096 : 0)) + (sp * DH + warp * 24 + gi * 8 + t * 2) * 4);
        pin(odst);

#pragma unroll 1
        for (int ph = 0; ph < 2; ph++) {
            if (ph == 1) {
                uint4 qf[6];
#pragma unroll
                for (int i = 0; i < 6; i++) qf[i] = lds128(sbase + SM_Q + t * 96 + i * 16);
                uint32_t ka[3];
#pragma unroll
                for (int j = 0; j < 3; j++) {
                    const int row = 3 * (lane & 15) + j;
                    ka[j] = sbase + row * 128 + ((((lane >> 4) ^ row) & 7) << 4) + warp * TILE_BYTES;
                }
                float s[4] = {0.f, 0.f, 0.f, 0.f};
#pragma unroll 1
                for (int it = 0; it < 4; it++) {
                    const int slot = (it & 1) * 8 + warp;
                    const uint32_t so = (it & 1) * 8 * TILE_BYTES;
                    float c[2][2][4];
                    zero4(c[0][0]); zero4(c[0][1]); zero4(c[1][0]); zero4(c[1][1]);
                    mbar_wait(bar_full + 8 * slot, it >> 1);
#pragma unroll
                    for (int ks = 0; ks < 12; ks++) {
                        const uint32_t a = (ka[ks >> 2] + so) ^ ((ks & 3) << 5);
                        uint32_t f0[4], f1[4];
                        ldsm_x4(f0, a); ldsm_x4(f1, a + 16 * DH * 2);
                        const uint32_t b0 = ks & 1 ? qf[ks >> 1].z : qf[ks >> 1].x, b1 = ks & 1 ? qf[ks >> 1].w : qf[ks >> 1].y;
                        mma_bf16(c[0][ks & 1], f0, b0, b1); mma_bf16(c[1][ks & 1], f1, b0, b1);
                    }
                    if (lane == 0) mbar_arrive8(bar_empty + 8 * slot);
                    const float v = t & 2 ? (t & 1 ? c[1][0][2] + c[1][1][2] : c[1][0][0] + c[1][1][0]) : (t & 1 ? c[0][0][2] + c[0][1][2] : c[0][0][0] + c[0][1][0]);
                    s[0] = s[1]; s[1] = s[2]; s[2] = s[3];
                    s[3] = bfr(bfr(v) * 0.07216878364870322f);
                }
                const float mw = warp_max(fmaxf(fmaxf(s[0], s[1]), fmaxf(s[2], s[3])));
                if (lane == 0) sts32(sbase + SM_MAX + warp * 4, mw);
                cons_sync();
                const float4 ma = lds128f(sbase + SM_MAX), mb = lds128f(sbase + SM_MAX + 16);
                const float m = fmaxf(fmaxf(fmaxf(ma.x, ma.y), fmaxf(ma.z, ma.w)), fmaxf(fmaxf(mb.x, mb.y), fmaxf(mb.z, mb.w)));
                float l = 0.f;
#pragma unroll
                for (int it = 0; it < 4; it++) {
                    const float e = ex2((s[it] - m) * L2E);
                    l += e;
                    sts16(sbase + SM_P + (it * 8 + warp) * 64 + ((g >> 1) * 8 + t * 2 + (g & 1)) * 2, pack_bf(0.f, e));
                }
                l = warp_sum(l);
                if (lane == 0) { sts32(sbase + SM_SUM + warp * 4, l); mbar_arrive(bar_stat); }
                cons_sync();
            }
            float acc[2][3][4];
#pragma unroll
            for (int i = 0; i < 3; i++) { zero4(acc[0][i]); zero4(acc[1][i]); }
            const int nt = ph ? NKT : NQT;
            float scale = 1.f;
#pragma unroll 1
            for (int n = 0; n < nt; n++) {
                const int slot = ph ? (n & (NSLOT - 1)) : QSLOT + n;
                const uint4 w = lds128(sbase + SM_P + n * 64 + t * 16);
                if (n == NKT - 1) { mbar_wait(bar_scale, 0); scale = __uint_as_float(lds32(sbase + SM_MISC + 8)); }
                if (ph) mbar_wait(bar_full + 8 * slot, (n >> 4) & 1);
                uint32_t f[3][4];
#pragma unroll
                for (int i = 0; i < 3; i++) ldsm_x4_t(f[i], va[i] + slot * TILE_BYTES);
#pragma unroll
                for (int i = 0; i < 3; i++) {
                    mma_bf16(acc[0][i], w.x, w.x, w.y, w.y, f[i][0], f[i][1]);
                    mma_bf16(acc[1][i], w.z, w.z, w.w, w.w, f[i][2], f[i][3]);
                }
                if (lane == 0) mbar_arrive(bar_empty + 8 * slot);
            }
            const float v0 = (gi == 0 ? acc[0][0][0] + acc[1][0][0] : gi == 1 ? acc[0][1][0] + acc[1][1][0] : acc[0][2][0] + acc[1][2][0]) * scale;
            const float v1 = (gi == 0 ? acc[0][0][1] + acc[1][0][1] : gi == 1 ? acc[0][1][1] + acc[1][1][1] : acc[0][2][1] + acc[1][2][1]) * scale;
            if (ph == 1) {
                if (g < 6) st2(odst, in_word(v0), in_word(v1));
                break;
            }
            const uint32_t t4 = (lds32(sbase + SM_MISC) & 7) + 1;
            if (g < 3) st2(p.sc->qbuf + b * 96 + warp * 12 + lane, (__float_as_uint(v0) & ~15u) | t4, (__float_as_uint(v1) & ~15u) | t4);
            if (warp < 3) {
                uint2 e[4];
                uint32_t n = 0, bad;
#pragma unroll 1
                do {
                    do __nanosleep(200); while ((int)(now_ns() - (t0 + p.t_q)) < 0);
                    bad = 0;
#pragma unroll
                    for (int i = 0; i < 4; i++) e[i] = ld2(p.sc->qbuf + (head * 4 + i) * 96 + tid);
#pragma unroll
                    for (int i = 0; i < 4; i++) { e[i].x ^= t4; e[i].y ^= t4; bad |= e[i].x | e[i].y; }
                    if (++n > SPIN_LIMIT) __trap();
                } while (__any_sync(0xffffffffu, bad & 15));
#define S_(c) ((__uint_as_float(e[0].c) + __uint_as_float(e[1].c)) + (__uint_as_float(e[2].c) + __uint_as_float(e[3].c)))
                sts32(sbase + SM_Q + (t * 24 + (tid >> 2)) * 4, pack_bf(S_(y), S_(x)));
#undef S_
            }
            cons_sync();
        }
        const uint32_t side = lds32(sbase + SM_MISC + 12) * 4096;
        const uint32_t d16 = kg * 64 + g * 8 + warp, oh = d16 / 12;
        const unsigned char* osrc = p.xa + ((xa_o(oh) ^ side) + ((d16 - oh * 12) * 16 + t * 4) * 4);
        const int r16 = (lane & 7) + ((lane >> 4) << 3), mi = lane >> 3 & 1;
        const uint32_t f32 = sbase + r16 * 32 + ((mi ^ (lane >> 2 & 1)) << 4);
        uint32_t rdst = sbase + SM_RED + (t * 8 + g) * 48 + warp * 4;
        uint32_t bl = sbase + SM_BC + warp * 512 + t * 80, bs = bl + g * 8;
        uint32_t hl = g < 4 ? bl : sbase + SM_ONE;
        uint32_t w1a = f32 + SM_W1 + warp * 512, w2a = f32 + SM_W2 + warp * 1024;
        uint32_t lnd = lane < 2 ? sbase + SM_LN + lane * 32 + warp * 4 : sbase + SM_BC + warp * 512 + 384 + lane * 4;
        const unsigned char* hs = p.xa + (side + warp * 256 + lane * 8);
        const unsigned char* as = p.xa + (XA_A + side + warp * 384 + min(lane, 23) * 16);
        uint32_t al = sbase + SM_BC + warp * 512 + t * 16, at = sbase + SM_BC + warp * 512 + lane * 16;
        uint32_t fl = role, ln = lane;
        pin_u(fl); pin(ln);
        const bool f1 = fl & 2, f2 = fl & 4, odd = ln & 1, first = ln == 0;
        constexpr uint32_t b2 = bar_tail + 8 * (NWP + NF1);
        pin(rdst); pin(bs); pin(hl); pin(w1a); pin(w2a); pin(lnd); pin(hs); pin(as); pin(al); pin(at);
#define F_(i, c) __uint_as_float(e[i].c)
        if (has_wo) {
            uint4 e[4];
#pragma unroll
            for (int i = 0; i < 4; i++) e[i].x = e[i].y = e[i].z = e[i].w = SENT;
            uint32_t n = 0;
            mbar_wait(bar_tail + 8 * 0, 0);
#pragma unroll 1
            do {
                if (n) __nanosleep(100);
#pragma unroll
                for (int i = 0; i < 4; i++) poll4(osrc + i * (DH * 4), e[i]);
                if (++n > SPIN_LIMIT) __trap();
            } while (__any_sync(0xffffffffu, max(max(max4(e[0]), max4(e[1])), max(max4(e[2]), max4(e[3]))) == SENT));
            sts64(bs, pack_bf((F_(0, y) + F_(1, y)) + (F_(2, y) + F_(3, y)), (F_(0, x) + F_(1, x)) + (F_(2, x) + F_(3, x))),
                      pack_bf((F_(0, w) + F_(1, w)) + (F_(2, w) + F_(3, w)), (F_(0, z) + F_(1, z)) + (F_(2, z) + F_(3, z))));
            __syncwarp();
#pragma unroll
            for (int i = 0; i < 4; i++) e[i] = lds128(bl + i * 16);
            const uint32_t wa = sbase + (warp * 16 + r16) * 64 + ((mi ^ (r16 >> 1 & 3)) << 4), wb = wa ^ 32;
            float c0[4], c1[4];
            zero4(c0); zero4(c1);
#pragma unroll
            for (int j = 0; j < NWP; j++) {
                mbar_wait(bar_tail + 8 * j, 0);
                uint32_t f0[4], f1[4];
                ldsm_x4_t(f0, wa + j * 8192); ldsm_x4_t(f1, wb + j * 8192);
                const uint32_t b0 = j & 1 ? e[j >> 1].z : e[j >> 1].x, b1 = j & 1 ? e[j >> 1].w : e[j >> 1].y;
                mma_bf16(c0, f0, b0, b1); mma_bf16(c1, f1, b0, b1);
            }
            sts32(rdst, t & 2 ? (t & 1 ? c1[2] : c1[0]) : (t & 1 ? c0[2] : c0[0]));
            fin_arrive<3>();
        }
        if (f1) {
            constexpr uint32_t b1 = bar_tail + 8 * NWP;
            uint32_t a1[5][4], a3[5][4];
            uint2 e[NG];
#pragma unroll
            for (int i = 0; i < NG; i++) e[i].x = e[i].y = 0;
            uint32_t got = 0, n = 0;
#pragma unroll
            for (int i = 0; i < NB; i++) a3[i][0] = a3[i][1] = a3[i][2] = a3[i][3] = 0;
            mbar_wait(b1, 0);
#pragma unroll
            for (int i = 0; i < NG; i++) ld2p(hs + xa_h(i), e[i], lane < 20);
            mbar_wait(b1 + 8, 0);
#pragma unroll
            for (int i = 0; i < 5; i++) ldsm_x4_t(a1[i], w1a + i * 4096);
            uint4 hb0, hb1;
            uint2 hb2;
            float sv[4];
#pragma unroll 1
            while (true) {
#define S_(f, c) (((f(e[0].c) + f(e[1].c)) + (f(e[2].c) + f(e[3].c))) + (f(e[4].c) + f(e[5].c)))
                const float sx = S_(bf_lo, x), sy = S_(bf_hi, x), sz = S_(bf_lo, y), sw = S_(bf_hi, y), sa = (sx + sy) + (sz + sw);
#undef S_
                const uint32_t h0 = add_bf2(xres.x, pack_bf(sy, sx)), h1 = add_bf2(xres.y, pack_bf(sw, sz));
                sts64(bs, h0, h1);
                __syncwarp();
                hb0 = lds128(hl); hb1 = lds128(hl + 16); hb2 = lds64(hl + 32);
                const float a = bf_lo(h0), b = bf_hi(h0), c = bf_lo(h1), d = bf_hi(h1);
                const float s1 = (a + b) + (c + d), s2 = fmaf(a, a, b * b) + fmaf(c, c, d * d);
                sv[0] = odd ? s2 : s1;
                sv[1] = __shfl_xor_sync(0xffffffffu, odd ? s1 : s2, 1);
                sv[2] = __shfl_xor_sync(0xffffffffu, sv[0], 2);
                sv[3] = __shfl_xor_sync(0xffffffffu, odd ? s1 : s2, 3);
                bool miss = __any_sync(0xffffffffu, sa != sa);
                if (miss) {
                    const uint4 mx = make_uint4(__vimax3_u16x2(e[0].x, e[0].y, e[1].x), __vimax3_u16x2(e[1].y, e[2].x, e[2].y),
                                                __vimax3_u16x2(e[3].x, e[3].y, e[4].x), __vimax3_u16x2(e[4].y, e[5].x, e[5].y));
#pragma unroll
                    for (int i = 0; i < NG; i++) poll2(hs + xa_h(i), e[i]);
                    ldsm_if<4096>(a3[0], a3[1], w1a + (SM_W3 - SM_W1), b1 + 16, got);
                    if (++n > SPIN_LIMIT) __trap();
                    miss = __any_sync(0xffffffffu, !ok8(mx));
                }
                if (!miss) break;
            }
            float cg[3][4], cu[3][4];
#pragma unroll
            for (int i = 0; i < 3; i++) { zero4(cg[i]); zero4(cu[i]); }
            const uint32_t hb[5][2] = {{hb0.x, hb0.y}, {hb0.z, hb0.w}, {hb1.x, hb1.y}, {hb1.z, hb1.w}, {hb2.x, hb2.y}};
            const float st = (sv[0] + sv[1]) + (sv[2] + sv[3]);
#pragma unroll
            for (int i = 0; i < 4; i++) sv[i] = __shfl_down_sync(0xffffffffu, st, 4 * i + 4);
#pragma unroll
            for (int i = 0; i < 5; i++) mma_bf16(cg[i % 3], a1[i], hb[i][0], hb[i][1]);
            sts32(lnd, ((st + sv[0]) + sv[1]) + (sv[2] + sv[3]));
            sts32(rdst + 32 * 48, odd ? (cg[0][2] + cg[2][2]) + cg[1][2] : (cg[0][0] + cg[2][0]) + cg[1][0]);
            fin_arrive<4>();
            if (__any_sync(0xffffffffu, !got)) {
                mbar_wait(b1 + 16, 0);
#pragma unroll
                for (int i = 0; i < NB; i++) ldsm_x4_t(a3[i], w1a + (SM_W3 - SM_W1) + i * 4096);
            }
            mbar_wait(b1 + 24, 0);
#pragma unroll
            for (int i = NB; i < 5; i++) ldsm_x4_t(a3[i], w1a + (SM_W3 - SM_W1) + i * 4096);
#pragma unroll
            for (int i = 0; i < 5; i++) mma_bf16(cu[i % 3], a3[i], hb[i][0], hb[i][1]);
            sts32(rdst + 64 * 48, odd ? (cu[0][2] + cu[2][2]) + cu[1][2] : (cu[0][0] + cu[2][0]) + cu[1][0]);
            __syncwarp();
            if (first) mbar_arrive(bar_up);
        }
        if (f2) {
            uint32_t a2[NF2][2][4];
#pragma unroll
            for (int i = 0; i < 4; i++) a2[NF2 - 1][0][i] = a2[NF2 - 1][1][i] = 0;
#pragma unroll
            for (int j = 0; j < NF2 - 1; j++) {
                mbar_wait(b2 + 8 * j, 0);
                ldsm_x4_t(a2[j][0], w2a + j * 8192); ldsm_x4_t(a2[j][1], w2a + j * 8192 + 512);
            }
            uint32_t n = 0, got = 0;
            uint4 e[NF2];
#pragma unroll 1
            while (true) {
                const uint4 pa = ld4(as);
                ldsm_if<512>(a2[NF2 - 1][0], a2[NF2 - 1][1], w2a + (NF2 - 1) * 8192, b2 + 8 * (NF2 - 1), got);
                if (++n > SPIN_LIMIT) __trap();
                sts128(at, pa);
                __syncwarp();
#pragma unroll
                for (int j = 0; j < 3; j++) e[j] = lds128v(al + j * 64);
                if (__all_sync(0xffffffffu, ok8(pa))) break;
            }
#pragma unroll
            for (int j = 3; j < NF2; j++) e[j] = lds128v(al + j * 64);
            float c[6][4];
#pragma unroll
            for (int j = 0; j < 6; j++) zero4(c[j]);
#pragma unroll
            for (int j = 0; j < NF2; j++) { mma_bf16(c[(j % 3) * 2], a2[j][0], e[j].x, e[j].y); mma_bf16(c[(j % 3) * 2 + 1], a2[j][1], e[j].z, e[j].w); }
            if (__any_sync(0xffffffffu, !got)) {
                constexpr int j = NF2 - 1;
                mbar_wait(b2 + 8 * j, 0);
                ldsm_x4_t(a2[j][0], w2a + j * 8192); ldsm_x4_t(a2[j][1], w2a + j * 8192 + 512);
                mma_bf16(c[4], a2[j][0], e[j].x, e[j].y); mma_bf16(c[5], a2[j][1], e[j].z, e[j].w);
            }
            sts32(rdst + 96 * 48, odd ? (((c[0][2] + c[1][2]) + (c[2][2] + c[3][2])) + c[4][2]) + c[5][2] : (((c[0][0] + c[1][0]) + (c[2][0] + c[3][0])) + c[4][0]) + c[5][0]);
            fin_arrive<6>();
        }
#undef F_
    }
}

typedef CUresult (*EncodeTiledFn)(CUtensorMap*, CUtensorMapDataType, cuuint32_t, void*, const cuuint64_t*, const cuuint64_t*,
                                  const cuuint32_t*, const cuuint32_t*, CUtensorMapInterleave, CUtensorMapSwizzle,
                                  CUtensorMapL2promotion, CUtensorMapFloatOOBfill);

void make_map(EncodeTiledFn fn, CUtensorMap* tm, const void* w, const int (&d)[5], const int (&st)[4], const int (&bx)[5],
              CUtensorMapSwizzle sw, int promo) {
    cuuint64_t dims[5], strides[4];
    cuuint32_t box[5], estr[5];
    for (int i = 0; i < 5; i++) { dims[i] = (cuuint64_t)d[i]; box[i] = (cuuint32_t)bx[i]; estr[i] = 1; }
    for (int i = 0; i < 4; i++) strides[i] = (cuuint64_t)st[i];
    fn(tm, CU_TENSOR_MAP_DATA_TYPE_BFLOAT16, 5, const_cast<void*>(w), dims, strides, box, estr, CU_TENSOR_MAP_INTERLEAVE_NONE, sw,
       (CUtensorMapL2promotion)promo, CU_TENSOR_MAP_FLOAT_OOB_FILL_NONE);
}

enum { T_PER, T_LEAD, T_STAG, T_TD, T_PERO, T_F1D, T_PERF, T_F2, T_PER2, T_Q, T_PWO, T_PW13, T_PW2, T_TG, T_N };
int g_tune[T_N] = {478, 1320, 110, 175, 289, 190, 117, 1330, 125, 6000, 1, 2, 2, 1700};

}

extern "C" void kernel_launch(void* const* d_in, const int* in_sizes, int n_in, void* d_out, int out_size) {
    (void)in_sizes; (void)n_in; (void)out_size;
    static EncodeTiledFn encode = nullptr;
    static Scratch* scratch = nullptr;
    static unsigned char* xarea = nullptr;
    if (!encode) {
        void* sp = nullptr;
        cudaGetSymbolAddress(&sp, g_scratch);
        scratch = reinterpret_cast<Scratch*>(sp);
        cudaGetSymbolAddress(&sp, g_xarea);
        xarea = reinterpret_cast<unsigned char*>((reinterpret_cast<uintptr_t>(sp) + XA_ALIGN - 1) / XA_ALIGN * XA_ALIGN);
        void* fn = nullptr;
        cudaDriverEntryPointQueryResult st;
        cudaGetDriverEntryPoint("cuTensorMapEncodeTiled", &fn, cudaEnableDefault, &st);
        encode = reinterpret_cast<EncodeTiledFn>(fn);
        cudaFuncSetAttribute(fused_decode_kernel, cudaFuncAttributeMaxDynamicSharedMemorySize, SM_TOTAL);
        int dev = 0, khz = 0, bits = 0;
        cudaGetDevice(&dev);
        if (cudaDeviceGetAttribute(&khz, cudaDevAttrMemoryClockRate, dev) == cudaSuccess &&
            cudaDeviceGetAttribute(&bits, cudaDevAttrGlobalMemoryBusWidth, dev) == cudaSuccess && khz > 0 && bits > 0) {
            const double f = 2619000.0 * 5120.0 / ((double)khz * bits);
            for (int i : {T_PER, T_STAG, T_PERO, T_PERF, T_F2, T_Q}) g_tune[i] = (int)(g_tune[i] * f + 0.5);
        }
        (void)cudaGetLastError();
    }
    const int* T = g_tune;
    KParams p;
    p.x = (const __nv_bfloat16*)d_in[0];
    p.wq = (const __nv_bfloat16*)d_in[3];
    p.out = (__nv_bfloat16*)d_out;
    p.sc = scratch;
    p.xa = xarea;
    p.per = T[T_PER];
    p.stag = T[T_STAG];
    p.t_k0 = (NQT + 1) * T[T_PER] - T[T_LEAD];
    {
        int t = p.t_k0 + 2 * NKT * T[T_PER] + T[T_STAG] * 3 / 2 + T[T_TD];
        for (int i = 0; i < NWP; i++, t += T[T_PERO]) p.item[i] = t;
        for (int i = 0, t1 = t + T[T_F1D]; i < NP1; i++, t1 += T[T_PERF]) p.item[NWP + i] = t1;
        for (int i = 0, t2 = t + T[T_F2]; i < NF2; i++, t2 += T[T_PER2]) p.item[NWP + NP1 + i] = t2;
        for (int i = NITEM; i < 32; i++) p.item[i] = 0;
    }
    p.target = T[T_TG]; p.t_q = T[T_Q]; p.t_fill = p.t_k0 + 55 * T[T_PER];
    for (int i = 0, nw = 0, n1 = 0, n2 = 0; i < NCTA; i++) {
        const int grp = i >> 2;
        const bool f2 = grp % 3 == 2, both = grp == 8 || grp == 23, wo = !both, f1 = !f2 || both;
        p.role[i] = (wo ? 1 | nw / 20 << 3 | nw % 20 << 6 : 0) | (f1 ? 2 | n1 << 11 : 0) | (f2 ? 4 | n2 << 18 : 0);
        nw += wo; n1 += f1; n2 += f2;
    }
    TMaps tm;
    constexpr int R1 = FF * 2, R2 = D_MODEL * 2;
    for (int i = 0; i < 2; i++)
        make_map(encode, &tm.k + i, d_in[1 + i], {64, 96, 1, 1, NHEAD * SK / 32}, {128, TILE_BYTES, TILE_BYTES, TILE_BYTES}, {64, 96, 1, 1, 1}, CU_TENSOR_MAP_SWIZZLE_128B, 2);
    make_map(encode, &tm.wo, d_in[4], {D_MODEL, 2, 4, 2, NHEAD * DH / 16}, {R2, 4 * R2, 2 * R2, 16 * R2}, {32, 2, 4, 2, 8}, CU_TENSOR_MAP_SWIZZLE_64B, T[T_PWO]);
    make_map(encode, &tm.w1, d_in[6], {FF, 2, 4, 2, D_MODEL / 16}, {R1, 4 * R1, 2 * R1, 16 * R1}, {16, 2, 4, 2, 8}, CU_TENSOR_MAP_SWIZZLE_32B, T[T_PW13]);
    make_map(encode, &tm.w3, d_in[7], {FF, 2, 4, 2, D_MODEL / 16}, {R1, 4 * R1, 2 * R1, 16 * R1}, {16, 2, 4, 2, 8}, CU_TENSOR_MAP_SWIZZLE_32B, T[T_PW13]);
    make_map(encode, &tm.w2, d_in[8], {D_MODEL, 2, 4, 4, FF / 32}, {R2, 8 * R2, 2 * R2, 32 * R2}, {16, 2, 4, 4, 8}, CU_TENSOR_MAP_SWIZZLE_32B, T[T_PW2]);
    fused_decode_kernel<<<NCTA, NTHREADS, SM_TOTAL, cudaStreamPerThread>>>(p, tm);
}
```

```cpp
#include <cuda_runtime.h>
#include <cuda_bf16.h>
#include <cuda.h>
#include <stdint.h>
#include <initializer_list>

namespace {

constexpr int D_MODEL = 640;
constexpr int NHEAD = 32;
constexpr int DH = 192;
constexpr int SK = 32768;
constexpr int WIN = 4096;
constexpr int FF = 1536;

constexpr int NCTA = 128;
constexpr int NTHREADS = 256 + 64;
constexpr int TILE_BYTES = 32 * DH * 2;
constexpr int NSLOT = 16;
constexpr int NKT = 32;
constexpr int NQT = 5;
constexpr int QSLOT = NSLOT - NQT;
constexpr int NG = 6;
constexpr int NWP = 8, NP1 = 10, NF2 = 6;
constexpr int NITEM = NWP + NP1 + NF2;
constexpr int NF1 = 4, NA = 2, NB = 2;
constexpr int NTAIL = NWP + NF1 + NF2;

constexpr int INFLIGHT = 5;

constexpr uint32_t sbase = 1024;
constexpr int SM_W1 = NWP * 8192, SM_W3 = SM_W1 + 20480, SM_W2 = SM_W3 + 20480;
constexpr int SM_P = NSLOT * TILE_BYTES;
constexpr int SM_Q = SM_P + 2048;
constexpr int SM_RED = SM_Q + 384;
constexpr int SM_BC = SM_RED + 128 * 48;
constexpr int SM_ONE = SM_BC + 4096;
constexpr int SM_MAX = SM_ONE + 64;
constexpr int SM_SUM = SM_MAX + 32;
constexpr int SM_LN = SM_SUM + 32;
constexpr int SM_MISC = SM_LN + 64;
constexpr int SM_LATE = SM_MISC + 32;
constexpr int SM_BAR = SM_LATE + 32;
constexpr int SM_TOTAL = SM_BAR + 512;
static_assert(SM_TOTAL <= 232448, "shared memory");

struct __align__(128) Scratch {
    uint2 qbuf[NCTA * 96];
    uint4 mbuf[NCTA * 2];
    uint32_t ready[NCTA];
    uint32_t late[32];
    uint32_t epoch;
};
__device__ Scratch g_scratch;
constexpr int XA_ALIGN = 1 << 20;
constexpr uint32_t SENT = 0xffffffffu;
__device__ unsigned char g_xarea[2 * XA_ALIGN];
__device__ __forceinline__ uint32_t xa_o(uint32_t d) {
    const uint32_t k = (d >> 6) * 4 + (d >> 1 & 3);
    return (2 * k + ((k ^ (k >> 3) ^ (k >> 4)) & 1)) * 4096 + (d & 1) * 2048 + (d >> 3 & 7) * 64;
}
__host__ __device__ constexpr uint32_t xa_h(uint32_t i) { return (1 << 18) + (i >> 2) * (3 << 16) + (i & 3) * (1 << 14); }
constexpr uint32_t XA_A = xa_h(NG);

constexpr uint32_t SPIN_LIMIT = 1u << 22;

__device__ __forceinline__ uint32_t smem_u32(const void* p) { return (uint32_t)__cvta_generic_to_shared(p); }
__device__ __forceinline__ uint32_t now_ns() { uint64_t t; asm volatile("mov.u64 %0, %globaltimer;" : "=l"(t)); return (uint32_t)t; }
__device__ __forceinline__ void mbar_init(uint32_t bar, uint32_t cnt) {
    asm volatile("mbarrier.init.shared::cta.b64 [%0], %1;" ::"r"(bar), "r"(cnt) : "memory");
}
__device__ __forceinline__ void mbar_expect_tx(uint32_t bar, uint32_t bytes) {
    asm volatile("mbarrier.arrive.expect_tx.shared::cta.b64 _, [%0], %1;" ::"r"(bar), "r"(bytes) : "memory");
}
__device__ __forceinline__ void mbar_arrive(uint32_t bar) {
    asm volatile("mbarrier.arrive.shared::cta.b64 _, [%0];" ::"r"(bar) : "memory");
}
__device__ __forceinline__ void mbar_arrive8(uint32_t bar) {
    asm volatile("mbarrier.arrive.shared::cta.b64 _, [%0], 8;" ::"r"(bar) : "memory");
}
__device__ __forceinline__ bool mbar_test(uint32_t bar, uint32_t parity) {
    uint32_t ok;
    asm volatile("{\n.reg .pred p;\nmbarrier.test_wait.parity.shared::cta.b64 p, [%1], %2;\nselp.u32 %0, 1, 0, p;\n}"
                 : "=r"(ok) : "r"(bar), "r"(parity) : "memory");
    return ok;
}
__device__ __forceinline__ void mbar_wait(uint32_t bar, uint32_t parity) {
    asm volatile("{\n.reg .pred p;\nW_%=:\nmbarrier.try_wait.parity.shared::cta.b64 p, [%0], %1;\n@!p bra.uni W_%=;\n}" ::"r"(bar), "r"(parity) : "memory");
}
__device__ __forceinline__ void mbar_wait_after(uint32_t bar, uint32_t dump, float v) {
    uint32_t ok;
    asm volatile("{\n.reg .pred p;\nmbarrier.try_wait.parity.shared::cta.b64 p, [%1], 0;\nselp.u32 %0, 1, 0, p;\n}" : "=r"(ok) : "r"(bar) : "memory");
    asm volatile("st.volatile.shared.f32 [%0], %1;" ::"r"(dump), "f"(v) : "memory");
    if (__builtin_expect(!ok, 0)) mbar_wait(bar, 0);
}
__device__ __forceinline__ void tma_load_at(uint32_t when, uint32_t dst, const CUtensorMap* tm, int c0, int c4, uint32_t bar, uint64_t pol) {
    asm volatile("{\n.reg .pred p, e;\n.reg .b64 t;\n.reg .b32 lo, hi;\nelect.sync _|e, -1;\n"
                 "W_%=:\nmov.u64 t, %globaltimer;\nmov.b64 {lo, hi}, t;\nsub.u32 lo, lo, %7;\nsetp.lt.s32 p, lo, 0;\n@p bra.uni W_%=;\n"
                 "@e cp.async.bulk.tensor.5d.shared::cluster.global.mbarrier::complete_tx::bytes.L2::cache_hint [%0], [%1, {%3, %5, %5, %5, %4}], [%2], %6;\n}"
                 ::"r"(dst), "l"(reinterpret_cast<uint64_t>(tm)), "r"(bar), "r"(c0), "r"(c4), "r"(0), "l"(pol), "r"(when) : "memory");
}
__device__ __forceinline__ void pin(uint32_t& v) { asm volatile("shfl.sync.bfly.b32 %0, %0, 0, 31, -1;" : "+r"(v) :: "memory"); }
__device__ __forceinline__ void pin_u(uint32_t& v) { asm volatile("shfl.sync.idx.b32 %0, %0, 0, 31, -1;" : "+r"(v) :: "memory"); }
template <class T> __device__ __forceinline__ void pin(T*& v) {
    asm volatile("{\n.reg .b32 a, b;\nmov.b64 {a, b}, %0;\nshfl.sync.bfly.b32 a, a, 0, 31, -1;\nshfl.sync.bfly.b32 b, b, 0, 31, -1;\nmov.b64 %0, {a, b};\n}" : "+l"(v) :: "memory");
}
__device__ __forceinline__ void sts16(uint32_t a, uint32_t v) { asm volatile("st.shared.u16 [%0], %1;" ::"r"(a), "h"((unsigned short)v) : "memory"); }
__device__ __forceinline__ void sts32(uint32_t a, float v) { asm volatile("st.shared.f32 [%0], %1;" ::"r"(a), "f"(v) : "memory"); }
__device__ __forceinline__ void sts32(uint32_t a, uint32_t v) { asm volatile("st.shared.u32 [%0], %1;" ::"r"(a), "r"(v) : "memory"); }
__device__ __forceinline__ void sts64(uint32_t a, uint32_t x, uint32_t y) { asm volatile("st.shared.v2.u32 [%0], {%1, %2};" ::"r"(a), "r"(x), "r"(y) : "memory"); }
__device__ __forceinline__ void sts128(uint32_t a, const uint4& v) { asm volatile("st.shared.v4.u32 [%0], {%1, %2, %3, %4};" ::"r"(a), "r"(v.x), "r"(v.y), "r"(v.z), "r"(v.w) : "memory"); }
__device__ __forceinline__ void cons_sync() { asm volatile("bar.sync 1, 256;" ::: "memory"); }
template <int ID> __device__ __forceinline__ void fin_arrive() { asm volatile("bar.arrive %0, 288;" ::"n"(ID) : "memory"); }
template <int ID> __device__ __forceinline__ void fin_sync() { asm volatile("bar.sync %0, 288;" ::"n"(ID) : "memory"); }

__device__ __forceinline__ uint4 lds128(uint32_t a) {
    uint4 v;
    asm volatile("ld.shared.v4.u32 {%0,%1,%2,%3}, [%4];" : "=r"(v.x), "=r"(v.y), "=r"(v.z), "=r"(v.w) : "r"(a) : "memory");
    return v;
}
__device__ __forceinline__ uint4 lds128v(uint32_t a) {
    uint4 v;
    asm volatile("ld.volatile.shared.v4.u32 {%0,%1,%2,%3}, [%4];" : "=r"(v.x), "=r"(v.y), "=r"(v.z), "=r"(v.w) : "r"(a) : "memory");
    return v;
}
__device__ __forceinline__ float4 lds128f(uint32_t a) {
    float4 v;
    asm volatile("ld.shared.v4.f32 {%0,%1,%2,%3}, [%4];" : "=f"(v.x), "=f"(v.y), "=f"(v.z), "=f"(v.w) : "r"(a) : "memory");
    return v;
}
__device__ __forceinline__ uint2 lds64(uint32_t a) {
    uint2 v;
    asm volatile("ld.shared.v2.u32 {%0,%1}, [%2];" : "=r"(v.x), "=r"(v.y) : "r"(a) : "memory");
    return v;
}
__device__ __forceinline__ uint32_t lds32(uint32_t a) {
    uint32_t v;
    asm volatile("ld.shared.u32 %0, [%1];" : "=r"(v) : "r"(a) : "memory");
    return v;
}
__device__ __forceinline__ float sum8(uint32_t a) {
    const float4 x = lds128f(a), y = lds128f(a + 16);
    return ((x.x + x.y) + (x.z + x.w)) + ((y.x + y.y) + (y.z + y.w));
}
__device__ __forceinline__ void ldsm_x4(uint32_t* r, uint32_t a) {
    asm volatile("ldmatrix.sync.aligned.m8n8.x4.shared.b16 {%0,%1,%2,%3}, [%4];"
                 : "=r"(r[0]), "=r"(r[1]), "=r"(r[2]), "=r"(r[3]) : "r"(a) : "memory");
}
__device__ __forceinline__ void ldsm_x4_t(uint32_t* r, uint32_t a) {
    asm volatile("ldmatrix.sync.aligned.m8n8.x4.trans.shared.b16 {%0,%1,%2,%3}, [%4];"
                 : "=r"(r[0]), "=r"(r[1]), "=r"(r[2]), "=r"(r[3]) : "r"(a) : "memory");
}
template <int STRIDE>
__device__ __forceinline__ void ldsm_if(uint32_t* r0, uint32_t* r1, uint32_t a, uint32_t bar, uint32_t& got) {
        asm volatile("{\n.reg .pred p, q;\nsetp.eq.u32 q, %8, 0;\nmbarrier.test_wait.parity.shared::cta.b64 p, [%10], 0;\nand.pred p, p, q;\n"
                     "@p ldmatrix.sync.aligned.m8n8.x4.trans.shared.b16 {%0,%1,%2,%3}, [%9];\n"
                     "@p ldmatrix.sync.aligned.m8n8.x4.trans.shared.b16 {%4,%5,%6,%7}, [%9+%11];\n@p mov.u32 %8, 1;\n}"
                     : "+r"(r0[0]), "+r"(r0[1]), "+r"(r0[2]), "+r"(r0[3]), "+r"(r1[0]), "+r"(r1[1]), "+r"(r1[2]), "+r"(r1[3]), "+r"(got)
                     : "r"(a), "r"(bar), "n"(STRIDE) : "memory");
}
__device__ __forceinline__ void mma_bf16(float* c, uint32_t a0, uint32_t a1, uint32_t a2, uint32_t a3, uint32_t b0, uint32_t b1) {
    asm volatile("mma.sync.aligned.m16n8k16.row.col.f32.bf16.bf16.f32 {%0,%1,%2,%3}, {%4,%5,%6,%7}, {%8,%9}, {%0,%1,%2,%3};"
                 : "+f"(c[0]), "+f"(c[1]), "+f"(c[2]), "+f"(c[3]) : "r"(a0), "r"(a1), "r"(a2), "r"(a3), "r"(b0), "r"(b1));
}
__device__ __forceinline__ void mma_bf16(float* c, const uint32_t* a, uint32_t b0, uint32_t b1) { mma_bf16(c, a[0], a[1], a[2], a[3], b0, b1); }
__device__ __forceinline__ void zero4(float* c) { c[0] = c[1] = c[2] = c[3] = 0.f; }
__device__ __forceinline__ float bf_lo(uint32_t u) { return __uint_as_float(u << 16); }
__device__ __forceinline__ float bf_hi(uint32_t u) { return __uint_as_float(u & 0xffff0000u); }
__device__ __forceinline__ uint32_t pack_bf(float hi, float lo) { uint32_t r; asm("cvt.rn.bf16x2.f32 %0, %1, %2;" : "=r"(r) : "f"(hi), "f"(lo)); return r; }
__device__ __forceinline__ uint32_t add_bf2(uint32_t a, uint32_t b) { uint32_t r; asm("add.rn.bf16x2 %0, %1, %2;" : "=r"(r) : "r"(a), "r"(b)); return r; }
__device__ __forceinline__ float bfr(float x) { return __uint_as_float(pack_bf(x, 0.f)); }

__device__ __forceinline__ uint32_t in_word(float v) { return __float_as_uint(v); }
__device__ __forceinline__ void st1(void* p, uint32_t v) {
    asm volatile("st.relaxed.gpu.global.u32 [%0], %1;" ::"l"(p), "r"(v) : "memory");
}
__device__ __forceinline__ void st16(void* p, uint32_t v) {
    asm volatile("st.relaxed.gpu.global.u16 [%0], %1;" ::"l"(p), "h"((unsigned short)v) : "memory");
}
__device__ __forceinline__ void st2(void* p, uint32_t a, uint32_t b) {
    asm volatile("st.relaxed.gpu.global.v2.u32 [%0], {%1, %2};" ::"l"(p), "r"(a), "r"(b) : "memory");
}
__device__ __forceinline__ void st4(void* p, uint32_t a, uint32_t b, uint32_t c, uint32_t d) {
    asm volatile("st.relaxed.gpu.global.v4.u32 [%0], {%1, %2, %3, %4};" ::"l"(p), "r"(a), "r"(b), "r"(c), "r"(d) : "memory");
}
__device__ __forceinline__ uint32_t ld1(const void* p) {
    uint32_t v;
    asm volatile("ld.relaxed.gpu.global.u32 %0, [%1];" : "=r"(v) : "l"(p) : "memory");
    return v;
}
__device__ __forceinline__ uint2 ld2(const void* p) {
    uint2 v;
    asm volatile("ld.relaxed.gpu.global.v2.u32 {%0, %1}, [%2];" : "=r"(v.x), "=r"(v.y) : "l"(p) : "memory");
    return v;
}
__device__ __forceinline__ uint4 ld4(const void* p) {
    uint4 v;
    asm volatile("ld.relaxed.gpu.global.v4.u32 {%0, %1, %2, %3}, [%4];" : "=r"(v.x), "=r"(v.y), "=r"(v.z), "=r"(v.w) : "l"(p) : "memory");
    return v;
}
__device__ __forceinline__ void ld4p(const void* p, uint4& v, bool on) {
    asm volatile("{\n.reg .pred q;\nsetp.ne.u32 q, %5, 0;\n@q ld.relaxed.gpu.global.v4.u32 {%0, %1, %2, %3}, [%4];\n}"
                 : "+r"(v.x), "+r"(v.y), "+r"(v.z), "+r"(v.w) : "l"(p), "r"((uint32_t)on) : "memory");
}
__device__ __forceinline__ bool ok8(const uint4& v) {
    const uint32_t m = __vimax3_u16x2(__vimax3_u16x2(v.x, v.y, v.z), v.w, v.w);
    return __vimax3_u16x2(m, m << 16, m >> 16) != SENT;
}
__device__ __forceinline__ void poll4(const void* p, uint4& v) {
    asm volatile("{\n.reg .pred q;\n.reg .u32 m;\nmax.u32 m, %0, %1;\nmax.u32 m, m, %2;\nmax.u32 m, m, %3;\nsetp.eq.u32 q, m, 0xffffffff;\n"
                 "@q ld.relaxed.gpu.global.v4.u32 {%0, %1, %2, %3}, [%4];\n}"
                 : "+r"(v.x), "+r"(v.y), "+r"(v.z), "+r"(v.w) : "l"(p) : "memory");
}
__device__ __forceinline__ uint32_t max4(const uint4& v) { return max(max(v.x, v.y), max(v.z, v.w)); }
__device__ __forceinline__ void pkt_st2(uint4* p, float a, float b, uint32_t tag) {
    asm volatile("st.relaxed.gpu.global.v2.b64 [%0], {%1, %2};" ::"l"(p), "l"(((uint64_t)tag << 32) | __float_as_uint(a)), "l"(((uint64_t)tag << 32) | __float_as_uint(b)) : "memory");
}
__device__ __forceinline__ void pkt_ld2(const uint4* p, uint64_t& a, uint64_t& b) {
    asm volatile("ld.relaxed.gpu.global.v2.b64 {%0, %1}, [%2];" : "=l"(a), "=l"(b) : "l"(p) : "memory");
}
__device__ __forceinline__ bool tag_ok(uint64_t v, uint32_t tag) { return (uint32_t)(v >> 32) == tag; }
__device__ __forceinline__ float val_of(uint64_t v) { return __uint_as_float((uint32_t)v); }

__device__ __forceinline__ float warp_sum(float v) {
#pragma unroll
    for (int o = 16; o > 0; o >>= 1) v += __shfl_xor_sync(0xffffffffu, v, o);
    return v;
}
__device__ __forceinline__ float warp_max(float v) {
#pragma unroll
    for (int o = 16; o > 0; o >>= 1) v = fmaxf(v, __shfl_xor_sync(0xffffffffu, v, o));
    return v;
}
__device__ __forceinline__ float sqrt_fast(float x) { float r; asm("sqrt.approx.ftz.f32 %0, %1;" : "=f"(r) : "f"(x)); return r; }
__device__ __forceinline__ float rcp_fast(float x) { float r; asm("rcp.approx.ftz.f32 %0, %1;" : "=f"(r) : "f"(x)); return r; }
__device__ __forceinline__ float ex2(float x) { float r; asm("ex2.approx.ftz.f32 %0, %1;" : "=f"(r) : "f"(x)); return r; }
constexpr float L2E = 1.4426950408889634f;
__device__ __forceinline__ void ln_finish(float s1, float s2, float& mean_b, float& inv_den) {
    const float mean = s1 * (1.0f / D_MODEL);
    const float var = fmaxf(fmaf(-mean, mean, s2 * (1.0f / D_MODEL)), 0.f);
    mean_b = bfr(mean);
    inv_den = rcp_fast(bfr(sqrt_fast(bfr(bfr(var) + 1e-5f))));
}
__device__ __forceinline__ uint32_t ln_apply2(uint32_t u, float mean_b, float inv_den) {
    const uint32_t d = pack_bf(bf_hi(u) - mean_b, bf_lo(u) - mean_b);
    return pack_bf(bf_hi(d) * inv_den, bf_lo(d) * inv_den);
}
__device__ __forceinline__ void ln_acc(uint32_t u, float& s1, float& s2) {
    const float a = bf_lo(u), b = bf_hi(u);
    s1 += a + b;
    s2 = fmaf(a, a, fmaf(b, b, s2));
}
__device__ __forceinline__ float silu_b(float g) { return bfr(__fdividef(g, 1.0f + ex2(-g * L2E))); }

struct KParams {
    const __nv_bfloat16* wq;
    const __nv_bfloat16* x;
    __nv_bfloat16* out;
    Scratch* sc;
    unsigned char* xa;
    int t_k0, per, stag;
    int target;
    int t_q, t_fill;
    float gain, tgain, tg0, dz;
    int kvmul, infl;
    uint32_t item[32];
    uint32_t role[NCTA];
};
struct TMaps { CUtensorMap k, v, wo, w1, w3, w2; };

__global__ void __launch_bounds__(NTHREADS, 1)
fused_decode_kernel(const __grid_constant__ KParams p, const __grid_constant__ TMaps tm) {
    extern __shared__ __align__(1024) unsigned char smem[];
    const int tid = threadIdx.x;
    const int b = blockIdx.x;
    const int head = b >> 2, sp = b & 3;
    {
        const char* a = reinterpret_cast<const char*>(p.wq) + (uint32_t)((sp * 160 + (tid >> 2)) * (NHEAD * DH * 2) + head * (DH * 2) + (tid & 3) * 128);
        asm volatile("prefetch.global.L2 [%0];" ::"l"(a) : "memory");
    }
    if (tid < 256) {
        const uint32_t r = tid >> 3, ch = tid & 7;
        const char* src = reinterpret_cast<const char*>(p.wq) + ((sp * 160 + r) * (NHEAD * DH * 2) + head * (DH * 2) + ch * 16);
#pragma unroll
        for (int i = 0; i < NQT; i++) {
#pragma unroll
            for (int j = 0; j < 3; j++)
                asm volatile("cp.async.cg.shared.global [%0], [%1], 16;"
                             ::"r"(sbase + (QSLOT + i) * TILE_BYTES + (3 * r + j) * 128 + ((ch ^ ((3 * r + j) & 7)) << 4)),
                               "l"(src + (size_t)i * 32 * (NHEAD * DH * 2) + j * 128) : "memory");
        }
    }
    const uint32_t t0 = now_ns();
    const int warp = __shfl_sync(0xffffffffu, tid >> 5, 0), lane = tid & 31;
    const uint32_t role = p.role[b];
    const int kg = role >> 3 & 7, ng = role >> 6 & 31;
    const int u1 = role >> 11 & 127, u2 = role >> 18;
    const bool has_wo = role & 1, has_f1 = role & 2, has_f2 = role & 4;
    constexpr uint32_t bar_full = sbase + SM_BAR;
    constexpr uint32_t bar_empty = sbase + SM_BAR + 128;
    constexpr uint32_t bar_tail = sbase + SM_BAR + 256;
    constexpr uint32_t bar_scale = bar_tail + 8 * NTAIL;
    constexpr uint32_t bar_stat = bar_scale + 8;
    constexpr uint32_t bar_up = bar_scale + 16;

    if (warp == 8) {
        if (smem_u32(smem) != sbase) __trap();
        uint64_t pol;
        asm volatile("createpolicy.fractional.L2::evict_first.b64 %0, 1.0;" : "=l"(pol));
        sts32(sbase + SM_LATE + (lane & 7) * 4, 0u);
        if (lane == 0) {
#pragma unroll
            for (int i = 0; i < 32 + NTAIL + 3; i++)
                mbar_init(bar_full + 8 * i, (i >= 16 && i < 32) || i > 32 + NTAIL ? 8 : i == 32 + NWP ? NA : i == 33 + NWP ? 5 - NA : i == 34 + NWP ? NB : i == 35 + NWP ? 5 - NB : 1);
#pragma unroll
            for (int i = 0; i < 6; i++) asm volatile("prefetch.tensormap [%0];" ::"l"(reinterpret_cast<uint64_t>(&tm.k + i)) : "memory");
            asm volatile("fence.mbarrier_init.release.cluster;" ::: "memory");
        }
        __syncwarp();
        asm volatile("bar.arrive 2, 320;" ::: "memory");
        const uint32_t tu = __shfl_sync(0xffffffffu, t0, 0);
        if (b == 0 && lane < 8) st1(p.sc->late + lane, lane ? 0 : (tu & 0xffffffu) | 1u << 24);
        const int tile0 = (head * SK + (SK - WIN)) / 32 * p.kvmul + sp;
        uint32_t tk = tu + p.t_k0 + sp * p.stag, tw = tk, acc = 0;
        int slip = 0, base = 0, w = 0, d0 = 0;
        float a2 = 0.f, drift = 0.f;
#pragma unroll 1
        for (int n = 0; n < 2 * NKT; n++) {
            const int slot = n & (NSLOT - 1);
            mbar_wait(bar_empty + 8 * slot, (((n + NQT) >> 4) & 1) ^ 1);
            if (lane == 0) mbar_expect_tx(bar_full + 8 * slot, TILE_BYTES);
            bool more;
            do {
                const uint32_t t = now_ns();
                if (__all_sync(0xffffffffu, mbar_test(bar_full + 8 * (w & (NSLOT - 1)), (w >> 4) & 1))) {
                    acc += t - tw;
                    tw += p.per;
                    w++;
                    if ((w & 7) == 0) {
                        if (lane == 0) asm volatile("red.relaxed.gpu.global.add.u32 [%0], %1;" ::"l"(p.sc->late + (w >> 3)), "r"((1u << 24) + min(max(((int)acc >> 3) + d0, 0), 65535)) : "memory");
                        acc = 0;
                    }
                }
                more = __any_sync(0xffffffffu, (int)(t - tk) < slip - 60) || w <= n - p.infl;
            } while (more);
            tma_load_at(tk + slip, sbase + slot * TILE_BYTES, &tm.k + (n >> 5), 0, tile0 + (n & (NKT - 1)) * 4 * p.kvmul, bar_full + 8 * slot, pol);
            tk += p.per;
            if ((n & 7) == 5 && lane < 2)
                asm volatile("cp.async.cg.shared.global [%0], [%1], 16;" ::"r"(sbase + SM_LATE + lane * 16), "l"(p.sc->late + lane * 4) : "memory");
            const uint32_t org = lds32(sbase + SM_LATE);
            if (org) d0 = (int)((tu - org) << 8) >> 8;
            int k = n >> 3;
            uint32_t rep = lds32(sbase + SM_LATE + k * 4);
            const uint32_t rep0 = lds32(sbase + SM_LATE + max(k - 1, 0) * 4);
            if (!(rep >> 30)) { rep = rep0; k--; }
            if (rep >> 30) {
                const float a = (float)(rep & 0xffffffu) * rcp_fast((float)(rep >> 24));
                if (k <= 2) a2 = a; else drift = fminf(fmaxf((a - a2) * rcp_fast((float)(8 * k - 16)), -12.f), 12.f);
                base = max((int)a - p.target - d0, -900);
                slip = base + (int)(fmaxf(drift - p.dz, 0.f) * p.gain * (float)(n + 5 - 8 * k));
            }
        }
        const int seg = (lane >= NWP) + (lane >= NWP + NP1), i = lane - (seg == 0 ? 0 : seg == 1 ? NWP : NWP + NP1);
        const bool todo = lane < NITEM && (role >> seg & 1);
        const uint32_t len = seg == 1 ? 4096 : 8192, dst = sbase + (seg == 0 ? 0 : seg == 1 ? SM_W1 : SM_W2) + i * len;
        const int w3 = seg == 1 && i >= 5;
        const uint32_t mi = seg == 2 ? 3 : seg + w3;
        const int c0 = seg == 0 ? ng * 32 : seg == 1 ? u1 * 16 : u2 * 16;
        const int c4 = (seg == 0 ? kg * 64 : w3 * -40) + i * 8;
        const uint32_t bar = bar_tail + 8 * (seg == 0 ? i : seg == 1 ? NWP + (i >= NA) + w3 + (i >= 5 + NB) : NWP + NF1 + i);
        const uint32_t tn = tu + base + p.item[lane] + (int)(drift * fmaf(p.tgain, (float)(int)(p.item[lane] - p.item[0]), p.tg0));
        if (todo) mbar_expect_tx(bar, len);
        const uint32_t c04 = c0 | c4 << 16, db = dst | (bar - bar_tail) << 18 | mi << 28;
#pragma unroll 1
        for (uint32_t left = __ballot_sync(0xffffffffu, todo); left; left &= left - 1) {
            const int k = __ffs(left) - 1;
            const uint32_t kc = __shfl_sync(0xffffffffu, c04, k), kd = __shfl_sync(0xffffffffu, db, k), kt = __shfl_sync(0xffffffffu, tn, k);
            mbar_wait(bar_empty + 8 * (k < NWP ? 5 : 12), k < NWP);
            tma_load_at(kt, kd & 0x3ffff, &tm.wo + (kd >> 28), kc & 0xffff, kc >> 16, bar_tail + (kd >> 18 & 0x3ff), pol);
        }
    } else if (warp == 9) {
        const uint32_t tag = ld1(&p.sc->epoch) + 1;
        const uint32_t aoff = XA_A + (u1 >> 1 & 7) * 384 + (u1 >> 4) * 64 + (u1 & 1) * 32, hoff = xa_h(kg) + (ng & 3) * 1024 + (ng >> 2) * 64;
        sts32(sbase + SM_ONE + (lane & 15) * 4, 0x3f803f80u);
        const uint32_t ooff = xa_o(head * 12 + (lane >> 2)) + sp * 512 + (lane & 3) * 16;
        unsigned char* slot[4] = {p.xa + ooff, p.xa + ((xa_o(head * 12 + 8 + (lane >> 2 & 3)) + sp * 512 + (lane & 3) * 16) ^ (lane >> 4) << 12), p.xa + (ooff ^ 4096),
                                  p.xa + (lane < 16 ? (has_wo ? hoff + (lane >> 3) * 4096 + (lane >> 2 & 1) * 512 + (lane & 3) * 16 : ooff) : has_f1 ? aoff + (lane >> 1 & 1) * 4096 + (lane & 1) * 16 : ooff)};
#pragma unroll
        for (int i = 0; i < 2; i++) st4(p.sc->qbuf + b * 96 + i * 32 + lane * 2, 0, 0, 0, 0);
        sts32(sbase + SM_MISC, tag);
        asm volatile("bar.sync 2, 320;" ::: "memory");
        while (!mbar_test(bar_stat, 0)) __nanosleep(200);
        const float4 ma = lds128f(sbase + SM_MAX), mb = lds128f(sbase + SM_MAX + 16);
        const float m = fmaxf(fmaxf(fmaxf(ma.x, ma.y), fmaxf(ma.z, ma.w)), fmaxf(fmaxf(mb.x, mb.y), fmaxf(mb.z, mb.w)));
        while ((int)(now_ns() - (t0 + p.t_fill)) < 0) __nanosleep(200);
        pkt_st2(p.sc->mbuf + b * 2 + (lane & 1), m, sum8(sbase + SM_SUM), tag);
#pragma unroll
        for (int i = 0; i < 4; i++) st4(slot[i], SENT, SENT, SENT, SENT);
        uint32_t ack = SENT;
#pragma unroll
        for (int i = 0; i < 4; i++) { uint32_t v; asm volatile("atom.relaxed.gpu.global.exch.b32 %0, [%1], -1;" : "=r"(v) : "l"(slot[i]) : "memory"); ack &= v; }
        if (__any_sync(0xffffffffu, ack != SENT)) __trap();
        if (lane == 0) st1(p.sc->ready + b, tag);
        int vote = 0;
#pragma unroll 1
        for (int r = 0; r < 5 && (!vote || (int)(now_ns() - (t0 + p.t_fill)) < 3500); r++) {
            __nanosleep(100);
            uint32_t d;
            asm volatile("{\n.reg .pred p, q;\n.reg .b32 a, b, c0, c1;\nmov.b32 c0, 0;\nmov.b32 c1, 0;\n"
                         "atom.relaxed.gpu.global.exch.b32 a, [%1], -1;\natom.relaxed.gpu.global.exch.b32 b, [%2], -1;\n"
                         "setp.eq.u32 p, a, -1;\n@p mov.u32 c0, %%clock;\nsetp.eq.u32 q, b, -1;\n@q mov.u32 c1, %%clock;\nsub.u32 %0, c1, c0;\n}"
                         : "=r"(d) : "l"(r & 1 ? slot[2] : slot[0]), "l"(r & 1 ? slot[0] : slot[2]) : "memory");
            vote += (d > 90) == (r & 1) ? 1 : -1;
        }
        const uint32_t side = __shfl_sync(0xffffffffu, vote, 0) > 0;
        uint32_t n = 0;
        {
            uint64_t em, el;
            while (true) {
                const uint4 e = ld4(p.sc->ready + lane * 4);
                pkt_ld2(p.sc->mbuf + (head * 4 + (lane & 3)) * 2, em, el);
                if (__all_sync(0xffffffffu, e.x == tag && e.y == tag && e.z == tag && e.w == tag && tag_ok(em, tag) && tag_ok(el, tag))) break;
                __nanosleep(500);
                if (++n > SPIN_LIMIT) __trap();
            }
            float M = fmaxf(val_of(em), __shfl_xor_sync(0xffffffffu, val_of(em), 1));
            M = fmaxf(M, __shfl_xor_sync(0xffffffffu, M, 2));
            float L = ex2((val_of(em) - M) * L2E) * val_of(el);
            L += __shfl_xor_sync(0xffffffffu, L, 1);
            L += __shfl_xor_sync(0xffffffffu, L, 2);
            if (lane == 0) {
                sts64(sbase + SM_MISC + 8, __float_as_uint(__fdividef(ex2((m - M) * L2E), L)), side);
                mbar_arrive(bar_scale);
                if (b == 0) p.sc->epoch = tag;
            }
        }
        unsigned char* hdst = p.xa + (hoff + (side ^ 1) * 4096 + (lane >> 4) * 512 + (lane & 15) * 4);
        unsigned char* hdst2 = p.xa + (hoff + side * 4096 + (lane >> 4) * 512 + (lane & 15) * 4);
        unsigned char* adst = p.xa + (aoff + (lane >> 4) * 4096 + (lane & 15) * 2);
        __nv_bfloat16* odst = p.out + u2 * 16 + (lane & 15);
        uint32_t r0 = sbase + SM_RED + lane * 48, r1 = sbase + SM_RED + (lane & 15) * 48;
        uint32_t res;
        asm volatile("ld.global.nc.u16 %0, [%1];" : "=r"(res) : "l"(p.x + u2 * 16 + (lane & 15)));
        pin(hdst); pin(hdst2); pin(adst); pin(odst); pin(r0); pin(r1);
        if (has_wo) {
            fin_sync<3>();
            const uint32_t v = in_word(sum8(r0));
            st1(hdst, v); st1(hdst2, v);
        }
        if (has_f1) {
            fin_sync<4>();
            float mean_b, inv_den;
            ln_finish(sum8(sbase + SM_LN), sum8(sbase + SM_LN + 32), mean_b, inv_den);
            const float gr = fmaf(-mean_b, sum8(r1 + 48 * 48), sum8(r1 + 32 * 48)) * inv_den;
            mbar_wait_after(bar_up, r0, gr);
            const float gs = bfr(gr);
            const float up = bfr(fmaf(-mean_b, sum8(r1 + 80 * 48), sum8(r1 + 64 * 48)) * inv_den);
            st16(adst, pack_bf(0.f, silu_b(gs) * up));
            if (b == 0 && lane < 8) st1(p.sc->late + lane, 0);
        }
        if (has_f2) {
            mbar_wait(bar_tail + 8 * (NWP + NF1 + 3), 0);
            const unsigned char* hsrc = p.xa + ((lane >> 4) * (1 << 14) + side * 4096 + (u2 & 7) * 512 + (u2 >> 3) * 64 + (lane & 15) * 4);
            uint32_t e[3];
            do {
#pragma unroll
                for (int i = 0; i < 3; i++) e[i] = ld1(hsrc + xa_h(2 * i));
                if (++n > SPIN_LIMIT) __trap();
            } while (__any_sync(0xffffffffu, max(max(e[0], e[1]), e[2]) == SENT));
            float f[3];
#pragma unroll
            for (int i = 0; i < 3; i++) f[i] = __uint_as_float(e[i]) + __uint_as_float(__shfl_xor_sync(0xffffffffu, e[i], 16));
            res = add_bf2(res, pack_bf(0.f, (f[0] + f[1]) + f[2]));
            pin(res);
            fin_sync<6>();
            asm volatile("st.global.u16 [%0], %1;" ::"l"(odst), "h"((unsigned short)add_bf2(res, pack_bf(0.f, sum8(r1 + 96 * 48)))) : "memory");
        }
    } else {
        const int g = lane >> 2, t = lane & 3;
        uint2 xres;
        {
            uint32_t xr;
            uint2 xu[5];
            const char* xb = reinterpret_cast<const char*>(p.x);
            asm volatile("ld.global.nc.u16 %0, [%1];" : "=r"(xr) : "l"(xb + (sp * 160 + min(tid, 159)) * 2));
#pragma unroll
            for (int i = 0; i < 5; i++) asm volatile("ld.global.nc.v2.u32 {%0, %1}, [%2];" : "=r"(xu[i].x), "=r"(xu[i].y) : "l"(xb + i * 256 + lane * 8));
            asm volatile("ld.global.nc.v2.u32 {%0, %1}, [%2];" : "=r"(xres.x), "=r"(xres.y) : "l"(xb + min(g, 4) * 256 + warp * 32 + t * 8));
            if (lane >= 20) xres.x = xres.y = 0;
            float s1 = 0.f, s2 = 0.f, mean_b, inv_den;
#pragma unroll
            for (int i = 0; i < 5; i++) { ln_acc(xu[i].x, s1, s2); ln_acc(xu[i].y, s1, s2); }
            ln_finish(warp_sum(s1), warp_sum(s2), mean_b, inv_den);
            sts16(sbase + SM_P + warp * 64 + ((lane >> 1 & 3) * 8 + (lane >> 3) * 2 + (lane & 1)) * 2, ln_apply2(xr, mean_b, inv_den));
            asm volatile("cp.async.wait_all;" ::: "memory");
            asm volatile("bar.sync 2, 320;" ::: "memory");
        }
        uint32_t va[3];
#pragma unroll
        for (int i = 0; i < 3; i++) {
            const int cc = 3 * warp + i, row = 3 * lane + (cc >> 3);
            va[i] = sbase + row * 128 + (((cc ^ row) & 7) << 4);
        }
        const int gi = g >= 3 ? g - 3 : g;
        unsigned char* odst = p.xa + ((xa_o(head * 12 + ((warp * 3 + gi) >> 1)) ^ (g >= 3 ? 4096 : 0)) + sp * 512 + ((warp + gi) & 1) * 32 + t * 8);
        pin(odst);

#pragma unroll 1
        for (int ph = 0; ph < 2; ph++) {
            if (ph == 1) {
                uint4 qf[6];
#pragma unroll
                for (int i = 0; i < 6; i++) qf[i] = lds128(sbase + SM_Q + t * 96 + i * 16);
                uint32_t ka[3];
#pragma unroll
                for (int j = 0; j < 3; j++) {
                    const int row = 3 * (lane & 15) + j;
                    ka[j] = sbase + row * 128 + ((((lane >> 4) ^ row) & 7) << 4) + warp * TILE_BYTES;
                }
                float s[4] = {0.f, 0.f, 0.f, 0.f};
#pragma unroll 1
                for (int it = 0; it < 4; it++) {
                    const int slot = (it & 1) * 8 + warp;
                    const uint32_t so = (it & 1) * 8 * TILE_BYTES;
                    float c[2][2][4];
                    zero4(c[0][0]); zero4(c[0][1]); zero4(c[1][0]); zero4(c[1][1]);
                    mbar_wait(bar_full + 8 * slot, it >> 1);
#pragma unroll
                    for (int ks = 0; ks < 12; ks++) {
                        const uint32_t a = (ka[ks >> 2] + so) ^ ((ks & 3) << 5);
                        uint32_t f0[4], f1[4];
                        ldsm_x4(f0, a); ldsm_x4(f1, a + 16 * DH * 2);
                        const uint32_t b0 = ks & 1 ? qf[ks >> 1].z : qf[ks >> 1].x, b1 = ks & 1 ? qf[ks >> 1].w : qf[ks >> 1].y;
                        mma_bf16(c[0][ks & 1], f0, b0, b1); mma_bf16(c[1][ks & 1], f1, b0, b1);
                    }
                    if (lane == 0) mbar_arrive8(bar_empty + 8 * slot);
                    const float v = t & 2 ? (t & 1 ? c[1][0][2] + c[1][1][2] : c[1][0][0] + c[1][1][0]) : (t & 1 ? c[0][0][2] + c[0][1][2] : c[0][0][0] + c[0][1][0]);
                    s[0] = s[1]; s[1] = s[2]; s[2] = s[3];
                    s[3] = bfr(bfr(v) * 0.07216878364870322f);
                }
                const float mw = warp_max(fmaxf(fmaxf(s[0], s[1]), fmaxf(s[2], s[3])));
                if (lane == 0) sts32(sbase + SM_MAX + warp * 4, mw);
                cons_sync();
                const float4 ma = lds128f(sbase + SM_MAX), mb = lds128f(sbase + SM_MAX + 16);
                const float m = fmaxf(fmaxf(fmaxf(ma.x, ma.y), fmaxf(ma.z, ma.w)), fmaxf(fmaxf(mb.x, mb.y), fmaxf(mb.z, mb.w)));
                float l = 0.f;
#pragma unroll
                for (int it = 0; it < 4; it++) {
                    const float e = ex2((s[it] - m) * L2E);
                    l += e;
                    sts16(sbase + SM_P + (it * 8 + warp) * 64 + ((g >> 1) * 8 + t * 2 + (g & 1)) * 2, pack_bf(0.f, e));
                }
                l = warp_sum(l);
                if (lane == 0) { sts32(sbase + SM_SUM + warp * 4, l); mbar_arrive(bar_stat); }
                cons_sync();
            }
            float acc[2][3][4];
#pragma unroll
            for (int i = 0; i < 3; i++) { zero4(acc[0][i]); zero4(acc[1][i]); }
            const int nt = ph ? NKT : NQT;
            float scale = 1.f;
#pragma unroll 1
            for (int n = 0; n < nt; n++) {
                const int slot = ph ? (n & (NSLOT - 1)) : QSLOT + n;
                const uint4 w = lds128(sbase + SM_P + n * 64 + t * 16);
                if (n == NKT - 1) { mbar_wait(bar_scale, 0); scale = __uint_as_float(lds32(sbase + SM_MISC + 8)); }
                if (ph) mbar_wait(bar_full + 8 * slot, (n >> 4) & 1);
                uint32_t f[3][4];
#pragma unroll
                for (int i = 0; i < 3; i++) ldsm_x4_t(f[i], va[i] + slot * TILE_BYTES);
#pragma unroll
                for (int i = 0; i < 3; i++) {
                    mma_bf16(acc[0][i], w.x, w.x, w.y, w.y, f[i][0], f[i][1]);
                    mma_bf16(acc[1][i], w.z, w.z, w.w, w.w, f[i][2], f[i][3]);
                }
                if (lane == 0) mbar_arrive(bar_empty + 8 * slot);
            }
            const float v0 = (gi == 0 ? acc[0][0][0] + acc[1][0][0] : gi == 1 ? acc[0][1][0] + acc[1][1][0] : acc[0][2][0] + acc[1][2][0]) * scale;
            const float v1 = (gi == 0 ? acc[0][0][1] + acc[1][0][1] : gi == 1 ? acc[0][1][1] + acc[1][1][1] : acc[0][2][1] + acc[1][2][1]) * scale;
            if (ph == 1) {
                if (g < 6) st2(odst, in_word(v0), in_word(v1));
                break;
            }
            const uint32_t t4 = (lds32(sbase + SM_MISC) & 7) + 1;
            if (g < 3) st2(p.sc->qbuf + b * 96 + warp * 12 + lane, (__float_as_uint(v0) & ~15u) | t4, (__float_as_uint(v1) & ~15u) | t4);
            if (warp < 3) {
                uint2 e[4];
                uint32_t n = 0, bad;
#pragma unroll 1
                do {
                    do __nanosleep(200); while ((int)(now_ns() - (t0 + p.t_q)) < 0);
                    bad = 0;
#pragma unroll
                    for (int i = 0; i < 4; i++) e[i] = ld2(p.sc->qbuf + (head * 4 + i) * 96 + tid);
#pragma unroll
                    for (int i = 0; i < 4; i++) { e[i].x ^= t4; e[i].y ^= t4; bad |= e[i].x | e[i].y; }
                    if (++n > SPIN_LIMIT) __trap();
                } while (__any_sync(0xffffffffu, bad & 15));
#define S_(c) ((__uint_as_float(e[0].c) + __uint_as_float(e[1].c)) + (__uint_as_float(e[2].c) + __uint_as_float(e[3].c)))
                sts32(sbase + SM_Q + (t * 24 + (tid >> 2)) * 4, pack_bf(S_(y), S_(x)));
#undef S_
            }
            cons_sync();
        }
        const uint32_t side = lds32(sbase + SM_MISC + 12) * 4096;
        const unsigned char* osrc = p.xa + ((xa_o(kg * 64 + warp) ^ side) + lane * 16);
        const int r16 = (lane & 7) + ((lane >> 4) << 3), mi = lane >> 3 & 1;
        const uint32_t f32 = sbase + r16 * 32 + ((mi ^ (lane >> 2 & 1)) << 4);
        uint32_t rdst = sbase + SM_RED + (t * 8 + g) * 48 + warp * 4;
        uint32_t bl = sbase + SM_BC + warp * 512 + t * 80, bs = bl + g * 8;
        uint32_t hl = g < 4 ? bl : sbase + SM_ONE;
        uint32_t w1a = f32 + SM_W1 + warp * 512, w2a = f32 + SM_W2 + warp * 1024;
        uint32_t lnd = lane < 2 ? sbase + SM_LN + lane * 32 + warp * 4 : sbase + SM_BC + warp * 512 + 384 + lane * 4;
        const unsigned char* hs = p.xa + (side + warp * 512 + lane * 16);
        const unsigned char* as = p.xa + (XA_A + side + warp * 384 + min(lane, 23) * 16);
        uint32_t al = sbase + SM_BC + warp * 512 + t * 16, at = sbase + SM_BC + warp * 512 + lane * 16;
        uint32_t fl = role, ln = lane;
        pin_u(fl); pin(ln);
        const bool f1 = fl & 2, f2 = fl & 4, odd = ln & 1, first = ln == 0;
        constexpr uint32_t b2 = bar_tail + 8 * (NWP + NF1);
        pin(rdst); pin(bs); pin(hl); pin(w1a); pin(w2a); pin(lnd); pin(hs); pin(as); pin(al); pin(at);
#define F_(i, c) __uint_as_float(e[i].c)
        if (has_wo) {
            uint4 e[4];
#pragma unroll
            for (int i = 0; i < 4; i++) e[i].x = e[i].y = e[i].z = e[i].w = SENT;
            uint32_t n = 0;
            mbar_wait(bar_tail + 8 * 1, 0);
#pragma unroll 1
            do {
                if (n) __nanosleep(100);
#pragma unroll
                for (int i = 0; i < 4; i++) poll4(osrc + i * 512, e[i]);
                if (++n > SPIN_LIMIT) __trap();
            } while (__any_sync(0xffffffffu, max(max(max4(e[0]), max4(e[1])), max(max4(e[2]), max4(e[3]))) == SENT));
            sts64(bs, pack_bf((F_(0, y) + F_(1, y)) + (F_(2, y) + F_(3, y)), (F_(0, x) + F_(1, x)) + (F_(2, x) + F_(3, x))),
                      pack_bf((F_(0, w) + F_(1, w)) + (F_(2, w) + F_(3, w)), (F_(0, z) + F_(1, z)) + (F_(2, z) + F_(3, z))));
            __syncwarp();
#pragma unroll
            for (int i = 0; i < 4; i++) e[i] = lds128(bl + i * 16);
            const uint32_t wa = sbase + (warp * 16 + r16) * 64 + ((mi ^ (r16 >> 1 & 3)) << 4), wb = wa ^ 32;
            float c0[4], c1[4];
            zero4(c0); zero4(c1);
#pragma unroll
            for (int j = 0; j < NWP; j++) {
                mbar_wait(bar_tail + 8 * j, 0);
                uint32_t f0[4], f1[4];
                ldsm_x4_t(f0, wa + j * 8192); ldsm_x4_t(f1, wb + j * 8192);
                const uint32_t b0 = j & 1 ? e[j >> 1].z : e[j >> 1].x, b1 = j & 1 ? e[j >> 1].w : e[j >> 1].y;
                mma_bf16(c0, f0, b0, b1); mma_bf16(c1, f1, b0, b1);
            }
            sts32(rdst, t & 2 ? (t & 1 ? c1[2] : c1[0]) : (t & 1 ? c0[2] : c0[0]));
            fin_arrive<3>();
        }
        if (f1) {
            constexpr uint32_t b1 = bar_tail + 8 * NWP;
            uint32_t a1[5][4], a3[5][4];
            uint4 e[NG];
#pragma unroll
            for (int i = 0; i < NG; i++) e[i].x = e[i].y = e[i].z = e[i].w = 0;
            uint32_t got = 0, n = 0;
#pragma unroll
            for (int i = 0; i < NB; i++) a3[i][0] = a3[i][1] = a3[i][2] = a3[i][3] = 0;
            mbar_wait(b1, 0);
#pragma unroll
            for (int i = 0; i < NG; i++) ld4p(hs + xa_h(i), e[i], lane < 20);
            mbar_wait(b1 + 8, 0);
#pragma unroll
            for (int i = 0; i < 5; i++) ldsm_x4_t(a1[i], w1a + i * 4096);
            uint4 hb0, hb1;
            uint2 hb2;
            float sv[4];
#pragma unroll 1
            while (true) {
#define S_(f, c) (((f(e[0].c) + f(e[1].c)) + (f(e[2].c) + f(e[3].c))) + (f(e[4].c) + f(e[5].c)))
                const float sx = S_(__uint_as_float, x), sy = S_(__uint_as_float, y), sz = S_(__uint_as_float, z), sw = S_(__uint_as_float, w), sa = (sx + sy) + (sz + sw);
#undef S_
                const uint32_t h0 = add_bf2(xres.x, pack_bf(sy, sx)), h1 = add_bf2(xres.y, pack_bf(sw, sz));
                sts64(bs, h0, h1);
                __syncwarp();
                hb0 = lds128(hl); hb1 = lds128(hl + 16); hb2 = lds64(hl + 32);
                const float a = bf_lo(h0), b = bf_hi(h0), c = bf_lo(h1), d = bf_hi(h1);
                const float s1 = (a + b) + (c + d), s2 = fmaf(a, a, b * b) + fmaf(c, c, d * d);
                sv[0] = odd ? s2 : s1;
                sv[1] = __shfl_xor_sync(0xffffffffu, odd ? s1 : s2, 1);
                sv[2] = __shfl_xor_sync(0xffffffffu, sv[0], 2);
                sv[3] = __shfl_xor_sync(0xffffffffu, odd ? s1 : s2, 3);
                bool miss = __any_sync(0xffffffffu, sa != sa);
                if (miss) {
                    miss = false;
#pragma unroll
                    for (int i = 0; i < NG; i++) {
                        const bool m = max4(e[i]) == SENT;
                        ld4p(hs + xa_h(i), e[i], m);
                        miss = miss || m;
                    }
                    ldsm_if<4096>(a3[0], a3[1], w1a + (SM_W3 - SM_W1), b1 + 16, got);
                    if (++n > SPIN_LIMIT) __trap();
                    miss = __any_sync(0xffffffffu, miss);
                }
                if (!miss) break;
            }
            float cg[3][4], cu[3][4];
#pragma unroll
            for (int i = 0; i < 3; i++) { zero4(cg[i]); zero4(cu[i]); }
            const uint32_t hb[5][2] = {{hb0.x, hb0.y}, {hb0.z, hb0.w}, {hb1.x, hb1.y}, {hb1.z, hb1.w}, {hb2.x, hb2.y}};
            const float st = (sv[0] + sv[1]) + (sv[2] + sv[3]);
#pragma unroll
            for (int i = 0; i < 4; i++) sv[i] = __shfl_down_sync(0xffffffffu, st, 4 * i + 4);
#pragma unroll
            for (int i = 0; i < 5; i++) mma_bf16(cg[i % 3], a1[i], hb[i][0], hb[i][1]);
            sts32(lnd, ((st + sv[0]) + sv[1]) + (sv[2] + sv[3]));
            sts32(rdst + 32 * 48, odd ? (cg[0][2] + cg[2][2]) + cg[1][2] : (cg[0][0] + cg[2][0]) + cg[1][0]);
            fin_arrive<4>();
            if (__any_sync(0xffffffffu, !got)) {
                mbar_wait(b1 + 16, 0);
#pragma unroll
                for (int i = 0; i < NB; i++) ldsm_x4_t(a3[i], w1a + (SM_W3 - SM_W1) + i * 4096);
            }
            mbar_wait(b1 + 24, 0);
#pragma unroll
            for (int i = NB; i < 5; i++) ldsm_x4_t(a3[i], w1a + (SM_W3 - SM_W1) + i * 4096);
#pragma unroll
            for (int i = 0; i < 5; i++) mma_bf16(cu[i % 3], a3[i], hb[i][0], hb[i][1]);
            sts32(rdst + 64 * 48, odd ? (cu[0][2] + cu[2][2]) + cu[1][2] : (cu[0][0] + cu[2][0]) + cu[1][0]);
            __syncwarp();
            if (first) mbar_arrive(bar_up);
        }
        if (f2) {
            uint32_t a2[NF2][2][4];
#pragma unroll
            for (int i = 0; i < 4; i++) a2[NF2 - 1][0][i] = a2[NF2 - 1][1][i] = 0;
#pragma unroll
            for (int j = 0; j < NF2 - 1; j++) {
                mbar_wait(b2 + 8 * j, 0);
                ldsm_x4_t(a2[j][0], w2a + j * 8192); ldsm_x4_t(a2[j][1], w2a + j * 8192 + 512);
            }
            uint32_t n = 0, got = 0;
            uint4 e[NF2];
#pragma unroll 1
            while (true) {
                const uint4 pa = ld4(as);
                ldsm_if<512>(a2[NF2 - 1][0], a2[NF2 - 1][1], w2a + (NF2 - 1) * 8192, b2 + 8 * (NF2 - 1), got);
                if (++n > SPIN_LIMIT) __trap();
                sts128(at, pa);
                __syncwarp();
#pragma unroll
                for (int j = 0; j < 3; j++) e[j] = lds128v(al + j * 64);
                if (__all_sync(0xffffffffu, ok8(pa))) break;
            }
#pragma unroll
            for (int j = 3; j < NF2; j++) e[j] = lds128v(al + j * 64);
            float c[6][4];
#pragma unroll
            for (int j = 0; j < 6; j++) zero4(c[j]);
#pragma unroll
            for (int j = 0; j < NF2; j++) { mma_bf16(c[(j % 3) * 2], a2[j][0], e[j].x, e[j].y); mma_bf16(c[(j % 3) * 2 + 1], a2[j][1], e[j].z, e[j].w); }
            if (__any_sync(0xffffffffu, !got)) {
                constexpr int j = NF2 - 1;
                mbar_wait(b2 + 8 * j, 0);
                ldsm_x4_t(a2[j][0], w2a + j * 8192); ldsm_x4_t(a2[j][1], w2a + j * 8192 + 512);
                mma_bf16(c[4], a2[j][0], e[j].x, e[j].y); mma_bf16(c[5], a2[j][1], e[j].z, e[j].w);
            }
            sts32(rdst + 96 * 48, odd ? (((c[0][2] + c[1][2]) + (c[2][2] + c[3][2])) + c[4][2]) + c[5][2] : (((c[0][0] + c[1][0]) + (c[2][0] + c[3][0])) + c[4][0]) + c[5][0]);
            fin_arrive<6>();
        }
#undef F_
    }
}

typedef CUresult (*EncodeTiledFn)(CUtensorMap*, CUtensorMapDataType, cuuint32_t, void*, const cuuint64_t*, const cuuint64_t*,
                                  const cuuint32_t*, const cuuint32_t*, CUtensorMapInterleave, CUtensorMapSwizzle,
                                  CUtensorMapL2promotion, CUtensorMapFloatOOBfill);

void make_map(EncodeTiledFn fn, CUtensorMap* tm, const void* w, const int (&d)[5], const int (&st)[4], const int (&bx)[5],
              CUtensorMapSwizzle sw, int promo) {
    cuuint64_t dims[5], strides[4];
    cuuint32_t box[5], estr[5];
    for (int i = 0; i < 5; i++) { dims[i] = (cuuint64_t)d[i]; box[i] = (cuuint32_t)bx[i]; estr[i] = 1; }
    for (int i = 0; i < 4; i++) strides[i] = (cuuint64_t)st[i];
    fn(tm, CU_TENSOR_MAP_DATA_TYPE_BFLOAT16, 5, const_cast<void*>(w), dims, strides, box, estr, CU_TENSOR_MAP_INTERLEAVE_NONE, sw,
       (CUtensorMapL2promotion)promo, CU_TENSOR_MAP_FLOAT_OOB_FILL_NONE);
}

enum { T_PER, T_LEAD, T_STAG, T_TD, T_PERO, T_F1D, T_PERF, T_F2, T_PER2, T_Q, T_PWO, T_PW13, T_PW2, T_TG, T_GA, T_TGA, T_TG0, T_FINE, T_INFL, T_DZ, T_N };
int g_tune[T_N] = {478, 1230, 115, 135, 289, 190, 117, 1340, 125, 6000, 2, 2, 2, 1660, 250, 250, 75, 4, 5, 30};

}

extern "C" void kernel_launch(void* const* d_in, const int* in_sizes, int n_in, void* d_out, int out_size) {
    (void)in_sizes; (void)n_in; (void)out_size;
    static EncodeTiledFn encode = nullptr;
    static Scratch* scratch = nullptr;
    static unsigned char* xarea = nullptr;
    if (!encode) {
        void* sp = nullptr;
        cudaGetSymbolAddress(&sp, g_scratch);
        scratch = reinterpret_cast<Scratch*>(sp);
        cudaGetSymbolAddress(&sp, g_xarea);
        xarea = reinterpret_cast<unsigned char*>((reinterpret_cast<uintptr_t>(sp) + XA_ALIGN - 1) / XA_ALIGN * XA_ALIGN);
        void* fn = nullptr;
        cudaDriverEntryPointQueryResult st;
        cudaGetDriverEntryPoint("cuTensorMapEncodeTiled", &fn, cudaEnableDefault, &st);
        encode = reinterpret_cast<EncodeTiledFn>(fn);
        cudaFuncSetAttribute(fused_decode_kernel, cudaFuncAttributeMaxDynamicSharedMemorySize, SM_TOTAL);
        int dev = 0, khz = 0, bits = 0;
        cudaGetDevice(&dev);
        if (cudaDeviceGetAttribute(&khz, cudaDevAttrMemoryClockRate, dev) == cudaSuccess &&
            cudaDeviceGetAttribute(&bits, cudaDevAttrGlobalMemoryBusWidth, dev) == cudaSuccess && khz > 0 && bits > 0) {
            const double f = 2619000.0 * 5120.0 / ((double)khz * bits);
            for (int i : {T_PER, T_STAG, T_PERO, T_PERF, T_F2, T_Q}) g_tune[i] = (int)(g_tune[i] * f + 0.5);
        }
        (void)cudaGetLastError();
    }
    const int* T = g_tune;
    KParams p;
    p.x = (const __nv_bfloat16*)d_in[0];
    p.wq = (const __nv_bfloat16*)d_in[3];
    p.out = (__nv_bfloat16*)d_out;
    p.sc = scratch;
    p.xa = xarea;
    p.per = T[T_PER];
    p.stag = T[T_STAG];
    p.t_k0 = (NQT + 1) * T[T_PER] - T[T_LEAD];
    {
        int t = p.t_k0 + 2 * NKT * T[T_PER] + T[T_STAG] * 3 / 2 + T[T_TD];
        for (int i = 0; i < NWP; i++, t += T[T_PERO]) p.item[i] = t;
        for (int i = 0, t1 = t + T[T_F1D]; i < NP1; i++, t1 += T[T_PERF]) p.item[NWP + i] = t1;
        for (int i = 0, t2 = t + T[T_F2]; i < NF2; i++, t2 += T[T_PER2]) p.item[NWP + NP1 + i] = t2;
        for (int i = NITEM; i < 32; i++) p.item[i] = 0;
    }
    p.target = T[T_TG]; p.t_q = T[T_Q]; p.gain = T[T_GA] / 100.f; p.tgain = T[T_TGA] / 47800.f; p.tg0 = T[T_TG0] / 10.f; p.dz = T[T_DZ] / 10.f; p.kvmul = T[T_FINE]; p.infl = T[T_INFL]; p.t_fill = p.t_k0 + 55 * T[T_PER];
    for (int i = 0, nw = 0, n1 = 0, n2 = 0; i < NCTA; i++) {
        const int grp = i >> 2;
        const bool f2 = grp % 3 == 2, both = grp == 8 || grp == 23, wo = !both, f1 = !f2 || both;
        p.role[i] = (wo ? 1 | nw / 20 << 3 | nw % 20 << 6 : 0) | (f1 ? 2 | n1 << 11 : 0) | (f2 ? 4 | n2 << 18 : 0);
        nw += wo; n1 += f1; n2 += f2;
    }
    TMaps tm;
    constexpr int R1 = FF * 2, R2 = D_MODEL * 2;
    for (int i = 0; i < 2; i++)
        make_map(encode, &tm.k + i, d_in[1 + i], {64, 96 / p.kvmul, p.kvmul, 1, NHEAD * SK / 32 * p.kvmul}, {128, 4 * TILE_BYTES / p.kvmul, TILE_BYTES, TILE_BYTES / p.kvmul}, {64, 96 / p.kvmul, p.kvmul, 1, 1}, CU_TENSOR_MAP_SWIZZLE_128B, 2);
    make_map(encode, &tm.wo, d_in[4], {D_MODEL, 2, 4, 2, NHEAD * DH / 16}, {R2, 4 * R2, 2 * R2, 16 * R2}, {32, 2, 4, 2, 8}, CU_TENSOR_MAP_SWIZZLE_64B, T[T_PWO]);
    make_map(encode, &tm.w1, d_in[6], {FF, 2, 4, 2, D_MODEL / 16}, {R1, 4 * R1, 2 * R1, 16 * R1}, {16, 2, 4, 2, 8}, CU_TENSOR_MAP_SWIZZLE_32B, T[T_PW13]);
    make_map(encode, &tm.w3, d_in[7], {FF, 2, 4, 2, D_MODEL / 16}, {R1, 4 * R1, 2 * R1, 16 * R1}, {16, 2, 4, 2, 8}, CU_TENSOR_MAP_SWIZZLE_32B, T[T_PW13]);
    make_map(encode, &tm.w2, d_in[8], {D_MODEL, 2, 4, 4, FF / 32}, {R2, 8 * R2, 2 * R2, 32 * R2}, {16, 2, 4, 4, 8}, CU_TENSOR_MAP_SWIZZLE_32B, T[T_PW2]);
    fused_decode_kernel<<<NCTA, NTHREADS, SM_TOTAL, cudaStreamPerThread>>>(p, tm);
}
```

```cpp
#include <cuda_runtime.h>
#include <cuda_bf16.h>
#include <cuda.h>
#include <stdint.h>
#include <initializer_list>

namespace {

constexpr int D_MODEL = 640;
constexpr int NHEAD = 32;
constexpr int DH = 192;
constexpr int SK = 32768;
constexpr int WIN = 4096;
constexpr int FF = 1536;

constexpr int NCTA = 128;
constexpr int NTHREADS = 256 + 64 + 192;
constexpr int TILE_BYTES = 32 * DH * 2;
constexpr int NSLOT = 16;
constexpr int NKT = 32;
constexpr int NQT = 5;
constexpr int QSLOT = NSLOT - NQT;
constexpr int NG = 6;
constexpr int NWP = 8, NP1 = 10, NF2 = 6;
constexpr int NITEM = NWP + NP1 + NF2;
constexpr int NF1 = 4, NA = 2, NB = 2;
constexpr int NTAIL = NWP + NF1 + NF2;

constexpr int INFLIGHT = 5;

constexpr uint32_t sbase = 1024;
constexpr int SM_W1 = NWP * 8192, SM_W3 = SM_W1 + 20480, SM_W2 = SM_W3 + 20480;
constexpr int SM_P = NSLOT * TILE_BYTES;
constexpr int SM_Q = SM_P + 2048;
constexpr int SM_RED = SM_Q + 12288;
constexpr int SM_BC = SM_RED + 128 * 48;
constexpr int SM_ONE = SM_BC + 4096;
constexpr int SM_ST = SM_ONE + 64;
constexpr int SM_WT = SM_ST + 256;
constexpr int SM_RO = SM_WT + 512;
constexpr int SM_LN = SM_RO + 48 * 80;
constexpr int SM_MISC = SM_LN + 64;
constexpr int SM_LATE = SM_MISC + 32;
constexpr int SM_BAR = SM_LATE + 32;
constexpr int SM_TOTAL = SM_BAR + 512;
static_assert(SM_TOTAL <= 232448, "shared memory");

struct __align__(128) Scratch {
    uint2 qbuf[NCTA * 96];
    uint2 qall[NHEAD * 96];
    uint2 mbuf[NCTA * NHEAD];
    uint32_t ready[NCTA];
    uint32_t late[32];
    uint32_t epoch;
};
__device__ Scratch g_scratch;
constexpr int XA_ALIGN = 2 << 20;
constexpr uint32_t SENT = 0xffffffffu;
__device__ unsigned char g_xarea[XA_ALIGN + (9 << 20)];
__device__ __forceinline__ uint32_t xa_o(uint32_t d) { return (d >> 7) * 16384 + (d >> 6 & 1) * 2048 + (d & 7) * 256 + (d >> 3 & 7) * 32; }
constexpr int NLATE = 4;
__device__ __forceinline__ uint32_t xa_p(uint32_t h, uint32_t q, uint32_t j) {
    const uint32_t k = ((NHEAD - 1 - h) * 4 + q) * 8 + j;
    return (1 << 20) + (2 * k + ((k ^ (k >> 3) ^ (k >> 4) ^ (k >> 6)) & 1)) * 4096;
}
__host__ __device__ constexpr uint32_t xa_h(uint32_t i) { return (1 << 18) + (i >> 2) * (3 << 16) + (i & 3) * (1 << 14); }
constexpr uint32_t XA_A = xa_h(NG);

constexpr uint32_t SPIN_LIMIT = 1u << 22;

__device__ __forceinline__ uint32_t smem_u32(const void* p) { return (uint32_t)__cvta_generic_to_shared(p); }
__device__ __forceinline__ uint32_t now_ns() { uint64_t t; asm volatile("mov.u64 %0, %globaltimer;" : "=l"(t)); return (uint32_t)t; }
__device__ __forceinline__ void mbar_init(uint32_t bar, uint32_t cnt) {
    asm volatile("mbarrier.init.shared::cta.b64 [%0], %1;" ::"r"(bar), "r"(cnt) : "memory");
}
__device__ __forceinline__ void mbar_expect_tx(uint32_t bar, uint32_t bytes) {
    asm volatile("mbarrier.arrive.expect_tx.shared::cta.b64 _, [%0], %1;" ::"r"(bar), "r"(bytes) : "memory");
}
__device__ __forceinline__ void mbar_arrive(uint32_t bar) {
    asm volatile("mbarrier.arrive.shared::cta.b64 _, [%0];" ::"r"(bar) : "memory");
}
__device__ __forceinline__ void mbar_arrive8(uint32_t bar) {
    asm volatile("mbarrier.arrive.shared::cta.b64 _, [%0], 8;" ::"r"(bar) : "memory");
}
__device__ __forceinline__ bool mbar_test(uint32_t bar, uint32_t parity) {
    uint32_t ok;
    asm volatile("{\n.reg .pred p;\nmbarrier.test_wait.parity.shared::cta.b64 p, [%1], %2;\nselp.u32 %0, 1, 0, p;\n}"
                 : "=r"(ok) : "r"(bar), "r"(parity) : "memory");
    return ok;
}
__device__ __forceinline__ void mbar_wait(uint32_t bar, uint32_t parity) {
    asm volatile("{\n.reg .pred p;\nW_%=:\nmbarrier.try_wait.parity.shared::cta.b64 p, [%0], %1;\n@!p bra.uni W_%=;\n}" ::"r"(bar), "r"(parity) : "memory");
}
__device__ __forceinline__ void mbar_wait_after(uint32_t bar, uint32_t dump, float v) {
    uint32_t ok;
    asm volatile("{\n.reg .pred p;\nmbarrier.try_wait.parity.shared::cta.b64 p, [%1], 0;\nselp.u32 %0, 1, 0, p;\n}" : "=r"(ok) : "r"(bar) : "memory");
    asm volatile("st.volatile.shared.f32 [%0], %1;" ::"r"(dump), "f"(v) : "memory");
    if (__builtin_expect(!ok, 0)) mbar_wait(bar, 0);
}
__device__ __forceinline__ void tma_load_at(uint32_t when, uint32_t dst, const CUtensorMap* tm, int c0, int c4, uint32_t bar, uint64_t pol) {
    asm volatile("{\n.reg .pred p, e;\n.reg .b64 t;\n.reg .b32 lo, hi;\nelect.sync _|e, -1;\n"
                 "W_%=:\nmov.u64 t, %globaltimer;\nmov.b64 {lo, hi}, t;\nsub.u32 lo, lo, %7;\nsetp.lt.s32 p, lo, 0;\n@p bra.uni W_%=;\n"
                 "@e cp.async.bulk.tensor.5d.shared::cluster.global.mbarrier::complete_tx::bytes.L2::cache_hint [%0], [%1, {%3, %5, %5, %5, %4}], [%2], %6;\n}"
                 ::"r"(dst), "l"(reinterpret_cast<uint64_t>(tm)), "r"(bar), "r"(c0), "r"(c4), "r"(0), "l"(pol), "r"(when) : "memory");
}
__device__ __forceinline__ void pin(uint32_t& v) { asm volatile("shfl.sync.bfly.b32 %0, %0, 0, 31, -1;" : "+r"(v) :: "memory"); }
__device__ __forceinline__ void pin_u(uint32_t& v) { asm volatile("shfl.sync.idx.b32 %0, %0, 0, 31, -1;" : "+r"(v) :: "memory"); }
template <class T> __device__ __forceinline__ void pin(T*& v) {
    asm volatile("{\n.reg .b32 a, b;\nmov.b64 {a, b}, %0;\nshfl.sync.bfly.b32 a, a, 0, 31, -1;\nshfl.sync.bfly.b32 b, b, 0, 31, -1;\nmov.b64 %0, {a, b};\n}" : "+l"(v) :: "memory");
}
__device__ __forceinline__ void sts16(uint32_t a, uint32_t v) { asm volatile("st.shared.u16 [%0], %1;" ::"r"(a), "h"((unsigned short)v) : "memory"); }
__device__ __forceinline__ void sts32(uint32_t a, float v) { asm volatile("st.shared.f32 [%0], %1;" ::"r"(a), "f"(v) : "memory"); }
__device__ __forceinline__ void sts32(uint32_t a, uint32_t v) { asm volatile("st.shared.u32 [%0], %1;" ::"r"(a), "r"(v) : "memory"); }
__device__ __forceinline__ void sts64(uint32_t a, uint32_t x, uint32_t y) { asm volatile("st.shared.v2.u32 [%0], {%1, %2};" ::"r"(a), "r"(x), "r"(y) : "memory"); }
__device__ __forceinline__ void sts128(uint32_t a, const uint4& v) { asm volatile("st.shared.v4.u32 [%0], {%1, %2, %3, %4};" ::"r"(a), "r"(v.x), "r"(v.y), "r"(v.z), "r"(v.w) : "memory"); }
__device__ __forceinline__ void cons_sync() { asm volatile("bar.sync 1, 256;" ::: "memory"); }
template <int ID> __device__ __forceinline__ void fin_arrive() { asm volatile("bar.arrive %0, 288;" ::"n"(ID) : "memory"); }
template <int ID> __device__ __forceinline__ void fin_sync() { asm volatile("bar.sync %0, 288;" ::"n"(ID) : "memory"); }

__device__ __forceinline__ uint4 lds128(uint32_t a) {
    uint4 v;
    asm volatile("ld.shared.v4.u32 {%0,%1,%2,%3}, [%4];" : "=r"(v.x), "=r"(v.y), "=r"(v.z), "=r"(v.w) : "r"(a) : "memory");
    return v;
}
__device__ __forceinline__ uint4 lds128v(uint32_t a) {
    uint4 v;
    asm volatile("ld.volatile.shared.v4.u32 {%0,%1,%2,%3}, [%4];" : "=r"(v.x), "=r"(v.y), "=r"(v.z), "=r"(v.w) : "r"(a) : "memory");
    return v;
}
__device__ __forceinline__ float4 lds128f(uint32_t a) {
    float4 v;
    asm volatile("ld.shared.v4.f32 {%0,%1,%2,%3}, [%4];" : "=f"(v.x), "=f"(v.y), "=f"(v.z), "=f"(v.w) : "r"(a) : "memory");
    return v;
}
__device__ __forceinline__ uint2 lds64(uint32_t a) {
    uint2 v;
    asm volatile("ld.shared.v2.u32 {%0,%1}, [%2];" : "=r"(v.x), "=r"(v.y) : "r"(a) : "memory");
    return v;
}
__device__ __forceinline__ uint32_t lds32(uint32_t a) {
    uint32_t v;
    asm volatile("ld.shared.u32 %0, [%1];" : "=r"(v) : "r"(a) : "memory");
    return v;
}
__device__ __forceinline__ float sum8(uint32_t a) {
    const float4 x = lds128f(a), y = lds128f(a + 16);
    return ((x.x + x.y) + (x.z + x.w)) + ((y.x + y.y) + (y.z + y.w));
}
__device__ __forceinline__ void ldsm_x4(uint32_t* r, uint32_t a) {
    asm volatile("ldmatrix.sync.aligned.m8n8.x4.shared.b16 {%0,%1,%2,%3}, [%4];"
                 : "=r"(r[0]), "=r"(r[1]), "=r"(r[2]), "=r"(r[3]) : "r"(a) : "memory");
}
__device__ __forceinline__ void ldsm_x4_t(uint32_t* r, uint32_t a) {
    asm volatile("ldmatrix.sync.aligned.m8n8.x4.trans.shared.b16 {%0,%1,%2,%3}, [%4];"
                 : "=r"(r[0]), "=r"(r[1]), "=r"(r[2]), "=r"(r[3]) : "r"(a) : "memory");
}
template <int STRIDE>
__device__ __forceinline__ void ldsm_if(uint32_t* r0, uint32_t* r1, uint32_t a, uint32_t bar, uint32_t& got) {
        asm volatile("{\n.reg .pred p, q;\nsetp.eq.u32 q, %8, 0;\nmbarrier.test_wait.parity.shared::cta.b64 p, [%10], 0;\nand.pred p, p, q;\n"
                     "@p ldmatrix.sync.aligned.m8n8.x4.trans.shared.b16 {%0,%1,%2,%3}, [%9];\n"
                     "@p ldmatrix.sync.aligned.m8n8.x4.trans.shared.b16 {%4,%5,%6,%7}, [%9+%11];\n@p mov.u32 %8, 1;\n}"
                     : "+r"(r0[0]), "+r"(r0[1]), "+r"(r0[2]), "+r"(r0[3]), "+r"(r1[0]), "+r"(r1[1]), "+r"(r1[2]), "+r"(r1[3]), "+r"(got)
                     : "r"(a), "r"(bar), "n"(STRIDE) : "memory");
}
__device__ __forceinline__ void mma_bf16(float* c, uint32_t a0, uint32_t a1, uint32_t a2, uint32_t a3, uint32_t b0, uint32_t b1) {
    asm volatile("mma.sync.aligned.m16n8k16.row.col.f32.bf16.bf16.f32 {%0,%1,%2,%3}, {%4,%5,%6,%7}, {%8,%9}, {%0,%1,%2,%3};"
                 : "+f"(c[0]), "+f"(c[1]), "+f"(c[2]), "+f"(c[3]) : "r"(a0), "r"(a1), "r"(a2), "r"(a3), "r"(b0), "r"(b1));
}
__device__ __forceinline__ void mma_bf16(float* c, const uint32_t* a, uint32_t b0, uint32_t b1) { mma_bf16(c, a[0], a[1], a[2], a[3], b0, b1); }
__device__ __forceinline__ void zero4(float* c) { c[0] = c[1] = c[2] = c[3] = 0.f; }
__device__ __forceinline__ float bf_lo(uint32_t u) { return __uint_as_float(u << 16); }
__device__ __forceinline__ float bf_hi(uint32_t u) { return __uint_as_float(u & 0xffff0000u); }
__device__ __forceinline__ uint32_t pack_bf(float hi, float lo) { uint32_t r; asm("cvt.rn.bf16x2.f32 %0, %1, %2;" : "=r"(r) : "f"(hi), "f"(lo)); return r; }
__device__ __forceinline__ uint32_t add_bf2(uint32_t a, uint32_t b) { uint32_t r; asm("add.rn.bf16x2 %0, %1, %2;" : "=r"(r) : "r"(a), "r"(b)); return r; }
__device__ __forceinline__ float bfr(float x) { return __uint_as_float(pack_bf(x, 0.f)); }

__device__ __forceinline__ uint32_t in_word(float v) { return __float_as_uint(v); }
__device__ __forceinline__ void st1(void* p, uint32_t v) {
    asm volatile("st.relaxed.gpu.global.u32 [%0], %1;" ::"l"(p), "r"(v) : "memory");
}
__device__ __forceinline__ void st16(void* p, uint32_t v) {
    asm volatile("st.relaxed.gpu.global.u16 [%0], %1;" ::"l"(p), "h"((unsigned short)v) : "memory");
}
__device__ __forceinline__ void st2(void* p, uint32_t a, uint32_t b) {
    asm volatile("st.relaxed.gpu.global.v2.u32 [%0], {%1, %2};" ::"l"(p), "r"(a), "r"(b) : "memory");
}
__device__ __forceinline__ void st4(void* p, uint32_t a, uint32_t b, uint32_t c, uint32_t d) {
    asm volatile("st.relaxed.gpu.global.v4.u32 [%0], {%1, %2, %3, %4};" ::"l"(p), "r"(a), "r"(b), "r"(c), "r"(d) : "memory");
}
__device__ __forceinline__ uint32_t ld1(const void* p) {
    uint32_t v;
    asm volatile("ld.relaxed.gpu.global.u32 %0, [%1];" : "=r"(v) : "l"(p) : "memory");
    return v;
}
__device__ __forceinline__ uint2 ld2(const void* p) {
    uint2 v;
    asm volatile("ld.relaxed.gpu.global.v2.u32 {%0, %1}, [%2];" : "=r"(v.x), "=r"(v.y) : "l"(p) : "memory");
    return v;
}
__device__ __forceinline__ uint4 ld4(const void* p) {
    uint4 v;
    asm volatile("ld.relaxed.gpu.global.v4.u32 {%0, %1, %2, %3}, [%4];" : "=r"(v.x), "=r"(v.y), "=r"(v.z), "=r"(v.w) : "l"(p) : "memory");
    return v;
}
__device__ __forceinline__ void ld4p(const void* p, uint4& v, bool on) {
    asm volatile("{\n.reg .pred q;\nsetp.ne.u32 q, %5, 0;\n@q ld.relaxed.gpu.global.v4.u32 {%0, %1, %2, %3}, [%4];\n}"
                 : "+r"(v.x), "+r"(v.y), "+r"(v.z), "+r"(v.w) : "l"(p), "r"((uint32_t)on) : "memory");
}
__device__ __forceinline__ bool ok8(const uint4& v) {
    const uint32_t m = __vimax3_u16x2(__vimax3_u16x2(v.x, v.y, v.z), v.w, v.w);
    return __vimax3_u16x2(m, m << 16, m >> 16) != SENT;
}
__device__ __forceinline__ uint32_t max4(const uint4& v) { return max(max(v.x, v.y), max(v.z, v.w)); }
__device__ __forceinline__ void pkt_ld2(const uint4* p, uint64_t& a, uint64_t& b) {
    asm volatile("ld.relaxed.gpu.global.v2.b64 {%0, %1}, [%2];" : "=l"(a), "=l"(b) : "l"(p) : "memory");
}
__device__ __forceinline__ bool tag_ok(uint64_t v, uint32_t tag) { return (uint32_t)(v >> 32) == tag; }
__device__ __forceinline__ float val_of(uint64_t v) { return __uint_as_float((uint32_t)v); }

__device__ __forceinline__ float warp_sum(float v) {
#pragma unroll
    for (int o = 16; o > 0; o >>= 1) v += __shfl_xor_sync(0xffffffffu, v, o);
    return v;
}
__device__ __forceinline__ float warp_max(float v) {
#pragma unroll
    for (int o = 16; o > 0; o >>= 1) v = fmaxf(v, __shfl_xor_sync(0xffffffffu, v, o));
    return v;
}
__device__ __forceinline__ float sqrt_fast(float x) { float r; asm("sqrt.approx.ftz.f32 %0, %1;" : "=f"(r) : "f"(x)); return r; }
__device__ __forceinline__ float rcp_fast(float x) { float r; asm("rcp.approx.ftz.f32 %0, %1;" : "=f"(r) : "f"(x)); return r; }
__device__ __forceinline__ float ex2(float x) { float r; asm("ex2.approx.ftz.f32 %0, %1;" : "=f"(r) : "f"(x)); return r; }
constexpr float L2E = 1.4426950408889634f;
__device__ __forceinline__ void ln_finish(float s1, float s2, float& mean_b, float& inv_den) {
    const float mean = s1 * (1.0f / D_MODEL);
    const float var = fmaxf(fmaf(-mean, mean, s2 * (1.0f / D_MODEL)), 0.f);
    mean_b = bfr(mean);
    inv_den = rcp_fast(bfr(sqrt_fast(bfr(bfr(var) + 1e-5f))));
}
__device__ __forceinline__ uint32_t ln_apply2(uint32_t u, float mean_b, float inv_den) {
    const uint32_t d = pack_bf(bf_hi(u) - mean_b, bf_lo(u) - mean_b);
    return pack_bf(bf_hi(d) * inv_den, bf_lo(d) * inv_den);
}
__device__ __forceinline__ void ln_acc(uint32_t u, float& s1, float& s2) {
    const float a = bf_lo(u), b = bf_hi(u);
    s1 += a + b;
    s2 = fmaf(a, a, fmaf(b, b, s2));
}
__device__ __forceinline__ float silu_b(float g) { return bfr(__fdividef(g, 1.0f + ex2(-g * L2E))); }

struct KParams {
    const __nv_bfloat16* wq;
    const __nv_bfloat16* x;
    __nv_bfloat16* out;
    Scratch* sc;
    unsigned char* xa;
    int t_k0, per, stag;
    int target;
    int t_q, t_fill, t_q2, t_stat, rdelay, rlast;
    float gain, tgain, tg0, dz;
    int stagh, infl;
    uint32_t item[32];
    uint32_t role[NCTA];
};
struct TMaps { CUtensorMap k, v, wo, w1, w3, w2; };

__global__ void __launch_bounds__(NTHREADS, 1)
fused_decode_kernel(const __grid_constant__ KParams p, const __grid_constant__ TMaps tm) {
    extern __shared__ __align__(1024) unsigned char smem[];
    const int tid = threadIdx.x;
    const int b = blockIdx.x;
    const int head = b >> 2, sp = b & 3;
    {
        const char* a = reinterpret_cast<const char*>(p.wq) + (uint32_t)((sp * 160 + (tid >> 2)) * (NHEAD * DH * 2) + head * (DH * 2) + (tid & 3) * 128);
        if (tid < 320) asm volatile("prefetch.global.L2 [%0];" ::"l"(a) : "memory");
    }
    if (tid < 256) {
        const uint32_t r = tid >> 3, ch = tid & 7;
        const char* src = reinterpret_cast<const char*>(p.wq) + ((sp * 160 + r) * (NHEAD * DH * 2) + head * (DH * 2) + ch * 16);
#pragma unroll
        for (int i = 0; i < NQT; i++) {
#pragma unroll
            for (int j = 0; j < 3; j++)
                asm volatile("cp.async.cg.shared.global [%0], [%1], 16;"
                             ::"r"(sbase + (QSLOT + i) * TILE_BYTES + (3 * r + j) * 128 + ((ch ^ ((3 * r + j) & 7)) << 4)),
                               "l"(src + (size_t)i * 32 * (NHEAD * DH * 2) + j * 128) : "memory");
        }
    }
    const uint32_t t0 = now_ns();
    const int warp = __shfl_sync(0xffffffffu, tid >> 5, 0), lane = tid & 31;
    const uint32_t role = p.role[b];
    const int kg = role >> 3 & 7, ng = role >> 6 & 31;
    const int u1 = role >> 11 & 127, u2 = role >> 18;
    const bool has_wo = role & 1, has_f1 = role & 2, has_f2 = role & 4;
    constexpr uint32_t bar_full = sbase + SM_BAR;
    constexpr uint32_t bar_empty = sbase + SM_BAR + 128;
    constexpr uint32_t bar_tail = sbase + SM_BAR + 256;
    constexpr uint32_t bar_side = bar_tail + 8 * NTAIL;
    constexpr uint32_t bar_wt = bar_side + 8;
    constexpr uint32_t bar_go = bar_side + 16;
    constexpr uint32_t bar_stat = bar_side + 24;
    constexpr uint32_t bar_up = bar_side + 32;

    if (warp == 8) {
        if (smem_u32(smem) != sbase) __trap();
        uint64_t pol;
        asm volatile("createpolicy.fractional.L2::evict_first.b64 %0, 1.0;" : "=l"(pol));
        sts32(sbase + SM_LATE + (lane & 7) * 4, 0u);
        if (lane == 0) {
#pragma unroll
            for (int i = 0; i < 32 + NTAIL + 5; i++)
                mbar_init(bar_full + 8 * i, (i >= 16 && i < 32) || i > 34 + NTAIL ? 8 : i == 32 + NWP ? NA : i == 33 + NWP ? 5 - NA : i == 34 + NWP ? NB : i == 35 + NWP ? 5 - NB : 1);
#pragma unroll
            for (int i = 0; i < 6; i++) asm volatile("prefetch.tensormap [%0];" ::"l"(reinterpret_cast<uint64_t>(&tm.k + i)) : "memory");
            asm volatile("fence.mbarrier_init.release.cluster;" ::: "memory");
        }
        __syncwarp();
        asm volatile("bar.arrive 2, 512;" ::: "memory");
        const uint32_t tu = __shfl_sync(0xffffffffu, t0, 0);
        if (b == 0 && lane < 8) st1(p.sc->late + lane, lane ? 0 : (tu & 0xffffffu) | 1u << 24);
        const int tile0 = (SK - WIN) / 32 + b;
        uint32_t tk = tu + p.t_k0 + sp * p.stag + head * p.stagh, tw = tk, acc = 0;
        int slip = 0, base = 0, w = 0, d0 = 0;
        float a2 = 0.f, drift = 0.f;
#pragma unroll 1
        for (int n = 0; n < 2 * NKT; n++) {
            const int slot = n & (NSLOT - 1);
            mbar_wait(bar_empty + 8 * slot, (((n + NQT) >> 4) & 1) ^ 1);
            if (lane == 0) mbar_expect_tx(bar_full + 8 * slot, TILE_BYTES);
            bool more;
            do {
                const uint32_t t = now_ns();
                if (__all_sync(0xffffffffu, mbar_test(bar_full + 8 * (w & (NSLOT - 1)), (w >> 4) & 1))) {
                    acc += t - tw;
                    tw += p.per;
                    w++;
                    if ((w & 7) == 0) {
                        if (lane == 0) asm volatile("red.relaxed.gpu.global.add.u32 [%0], %1;" ::"l"(p.sc->late + (w >> 3)), "r"((1u << 24) + min(max(((int)acc >> 3) + d0, 0), 65535)) : "memory");
                        acc = 0;
                    }
                }
                more = __any_sync(0xffffffffu, (int)(t - tk) < slip - 60) || w <= n - p.infl;
            } while (more);
            tma_load_at(tk + slip, sbase + slot * TILE_BYTES, &tm.k + (n >> 5), 0, tile0 + (n & (NKT - 1)) * (SK / 32), bar_full + 8 * slot, pol);
            tk += p.per;
            if ((n & 7) == 5 && lane < 2)
                asm volatile("cp.async.cg.shared.global [%0], [%1], 16;" ::"r"(sbase + SM_LATE + lane * 16), "l"(p.sc->late + lane * 4) : "memory");
            const uint32_t org = lds32(sbase + SM_LATE);
            if (org) d0 = (int)((tu - org) << 8) >> 8;
            int k = n >> 3;
            uint32_t rep = lds32(sbase + SM_LATE + k * 4);
            const uint32_t rep0 = lds32(sbase + SM_LATE + max(k - 1, 0) * 4);
            if (!(rep >> 30)) { rep = rep0; k--; }
            if (rep >> 30) {
                const float a = (float)(rep & 0xffffffu) * rcp_fast((float)(rep >> 24));
                if (k <= 2) a2 = a; else drift = fminf(fmaxf((a - a2) * rcp_fast((float)(8 * k - 16)), -12.f), 12.f);
                base = max((int)a - p.target - d0, -900);
                slip = base + (int)(fmaxf(drift - p.dz, 0.f) * p.gain * (float)(n + 5 - 8 * k));
            }
        }
        const int seg = (lane >= NWP) + (lane >= NWP + NP1), i = lane - (seg == 0 ? 0 : seg == 1 ? NWP : NWP + NP1);
        const bool todo = lane < NITEM && (role >> seg & 1);
        const uint32_t len = seg == 1 ? 4096 : 8192, dst = sbase + (seg == 0 ? 0 : seg == 1 ? SM_W1 : SM_W2) + i * len;
        const int w3 = seg == 1 && i >= 5;
        const uint32_t mi = seg == 2 ? 3 : seg + w3;
        const int c0 = seg == 0 ? ng * 32 : seg == 1 ? u1 * 16 : u2 * 16;
        const int c4 = (seg == 0 ? kg * 64 : w3 * -40) + i * 8;
        const uint32_t bar = bar_tail + 8 * (seg == 0 ? i : seg == 1 ? NWP + (i >= NA) + w3 + (i >= 5 + NB) : NWP + NF1 + i);
        const uint32_t tn = tu + base + p.item[lane] + (int)(drift * fmaf(p.tgain, (float)(int)(p.item[lane] - p.item[0]), p.tg0));
        if (todo) mbar_expect_tx(bar, len);
        const uint32_t c04 = c0 | c4 << 16, db = dst | (bar - bar_tail) << 18 | mi << 28;
#pragma unroll 1
        for (uint32_t left = __ballot_sync(0xffffffffu, todo); left; left &= left - 1) {
            const int k = __ffs(left) - 1;
            const uint32_t kc = __shfl_sync(0xffffffffu, c04, k), kd = __shfl_sync(0xffffffffu, db, k), kt = __shfl_sync(0xffffffffu, tn, k);
            mbar_wait(bar_empty + 8 * (k < NWP ? 5 : 12), k < NWP);
            tma_load_at(kt, kd & 0x3ffff, &tm.wo + (kd >> 28), kc & 0xffff, kc >> 16, bar_tail + (kd >> 18 & 0x3ff), pol);
        }
    } else if (warp >= 10) {
        asm volatile("bar.sync 2, 512;" ::: "memory");
        const uint32_t t4 = (lds32(sbase + SM_MISC) & 7) + 1, id = tid - 320, sg = id / 12;
        while (!mbar_test(bar_wt, 0)) __nanosleep(500);
        const float4 wa = lds128f(sbase + SM_WT + sg * 32), wb = lds128f(sbase + SM_WT + sg * 32 + 16);
        const float wt[8] = {wa.x, wa.y, wa.z, wa.w, wb.x, wb.y, wb.z, wb.w};
        uint32_t sd = sp & 1;
        if (head >= NHEAD - NLATE) {
            while (!mbar_test(bar_side, 0)) __nanosleep(200);
            sd = lds32(sbase + SM_MISC + 4);
        }
        const uint32_t o0 = (xa_p(head, sp, 0) ^ sd << 12) + id * 16;
        const unsigned char* a0 = p.xa + o0;
        const unsigned char* a1 = p.xa + (o0 ^ 4096);
        uint32_t dst = sbase + SM_RO + (id - sg * 12) * 320 + sg * 4;
        pin(a0); pin(a1); pin(dst);
        mbar_wait(bar_go, 0);
        uint4 e[8];
#pragma unroll
        for (int j = 0; j < 8; j++) e[j] = ld4((j & 1 ? a1 : a0) + j * 8192);
        uint32_t k = 0;
        bool miss;
#pragma unroll 1
        do {
            miss = false;
#pragma unroll
            for (int j = 0; j < 8; j++) {
                const bool m = (((e[j].x ^ t4) | (e[j].y ^ t4) | (e[j].z ^ t4) | (e[j].w ^ t4)) & 15) != 0;
                ld4p((j & 1 ? a1 : a0) + j * 8192, e[j], m);
                miss = miss || m;
            }
            if (++k > SPIN_LIMIT) __trap();
        } while (__any_sync(0xffffffffu, miss));
        float o[4] = {0.f, 0.f, 0.f, 0.f};
#pragma unroll
        for (int j = 0; j < 8; j++) {
            o[0] = fmaf(wt[j], __uint_as_float(e[j].x ^ t4), o[0]); o[1] = fmaf(wt[j], __uint_as_float(e[j].y ^ t4), o[1]);
            o[2] = fmaf(wt[j], __uint_as_float(e[j].z ^ t4), o[2]); o[3] = fmaf(wt[j], __uint_as_float(e[j].w ^ t4), o[3]);
        }
#pragma unroll
        for (int i = 0; i < 4; i++) sts32(dst + i * 80, o[i]);
        asm volatile("bar.arrive 5, 224;" ::: "memory");
    } else if (warp == 9) {
        const uint32_t tag = ld1(&p.sc->epoch) + 1;
        const uint32_t aoff = XA_A + (u1 >> 1 & 7) * 384 + (u1 >> 4) * 64 + (u1 & 1) * 32, hoff = xa_h(kg) + (ng & 3) * 1024 + (ng >> 2) * 64;
        sts32(sbase + SM_ONE + (lane & 15) * 4, 0x3f803f80u);
        const uint32_t l24 = min(lane, 23), ooff = xa_o(head * 12 + sp * 3 + (l24 >> 3));
        unsigned char* slot[3] = {p.xa + (ooff + (l24 & 7) * 4), p.xa + (ooff + (l24 & 7) * 4 + 4096),
                                  p.xa + (lane < 16 ? (has_wo ? hoff + (lane >> 3) * 4096 + (lane >> 2 & 1) * 512 + (lane & 3) * 16 : ooff) : has_f1 ? aoff + (lane >> 1 & 1) * 4096 + (lane & 1) * 16 : ooff)};
#pragma unroll
        for (int i = 0; i < 2; i++) st4(p.sc->qbuf + b * 96 + i * 32 + lane * 2, 0, 0, 0, 0);
        uint2* qdst = p.sc->qall + ((head & 7) * 4 + (head >> 3)) * 96 + sp * 24 + l24;
        st2(qdst, 0, 0);
        sts32(sbase + SM_MISC, tag);
        asm volatile("bar.sync 2, 512;" ::: "memory");
        uint32_t n = 0;
        {
            const uint32_t t4 = (tag & 7) + 1;
            uint2 e[4];
            uint32_t bad;
#pragma unroll 1
            do {
                do __nanosleep(100); while ((int)(now_ns() - (t0 + p.t_q)) < 0);
                bad = 0;
#pragma unroll
                for (int i = 0; i < 4; i++) e[i] = ld2(p.sc->qbuf + (head * 4 + i) * 96 + l24 * 4 + sp);
#pragma unroll
                for (int i = 0; i < 4; i++) { e[i].x ^= t4; e[i].y ^= t4; bad |= e[i].x | e[i].y; }
                if (++n > SPIN_LIMIT) __trap();
            } while (__any_sync(0xffffffffu, bad & 15));
#define S_(c) ((__uint_as_float(e[0].c) + __uint_as_float(e[1].c)) + (__uint_as_float(e[2].c) + __uint_as_float(e[3].c)))
            asm volatile("st.relaxed.gpu.global.b64 [%0], %1;" ::"l"(qdst), "l"((uint64_t)tag << 32 | pack_bf(S_(y), S_(x))) : "memory");
#undef S_
        }
        {
            while (!mbar_test(bar_stat, 0)) __nanosleep(200);
            const uint2 st = lds64(sbase + SM_ST + lane * 8);
            asm volatile("st.relaxed.gpu.global.b64 [%0], %1;" ::"l"(p.sc->mbuf + b * NHEAD + lane), "l"((uint64_t)st.y << 32 | st.x) : "memory");
            const uint32_t t1 = now_ns() + p.t_stat, t16 = (tag & 0x7fff) + 1;
            uint64_t e[4];
            do {
                do __nanosleep(200); while ((int)(now_ns() - t1) < 0);
#pragma unroll
                for (int i = 0; i < 4; i++) asm volatile("ld.relaxed.gpu.global.b64 %0, [%1];" : "=l"(e[i]) : "l"(p.sc->mbuf + (lane + 32 * i) * NHEAD + head) : "memory");
#pragma unroll
                for (int i = 0; i < 4; i++) e[i] ^= t16;
                if (++n > SPIN_LIMIT) __trap();
            } while (__any_sync(0xffffffffu, (e[0] | e[1] | e[2] | e[3]) & 0xffff));
            const float M = warp_max(fmaxf(fmaxf(val_of(e[0]), val_of(e[1])), fmaxf(val_of(e[2]), val_of(e[3]))));
            float x[4], L = 0.f;
#pragma unroll
            for (int i = 0; i < 4; i++) { x[i] = ex2((val_of(e[i]) - M) * L2E); L = fmaf(x[i], val_of(e[i] >> 32), L); }
            L = rcp_fast(warp_sum(L));
#pragma unroll
            for (int i = 0; i < 4; i++) sts32(sbase + SM_WT + (lane & 15) * 32 + (lane >> 4) * 4 + i * 8, x[i] * L);
            __syncwarp();
            if (lane == 0) mbar_arrive(bar_wt);
        }
        while ((int)(now_ns() - (t0 + p.t_fill)) < 0) __nanosleep(200);
        st1(slot[0], SENT); st1(slot[1], SENT); st4(slot[2], SENT, SENT, SENT, SENT);
        uint32_t ack = SENT;
#pragma unroll
        for (int i = 0; i < 3; i++) { uint32_t v; asm volatile("atom.relaxed.gpu.global.exch.b32 %0, [%1], -1;" : "=r"(v) : "l"(slot[i]) : "memory"); ack &= v; }
        if (__any_sync(0xffffffffu, ack != SENT)) __trap();
        if (lane == 0) st1(p.sc->ready + b, tag);
        unsigned char* pr = p.xa + (xa_o(head * 12 + sp * 3) + (lane & 7) * 4);
        int vote = 0;
#pragma unroll 1
        for (int r = 0; r < 5 && (!vote || (int)(now_ns() - (t0 + p.t_fill)) < 3500); r++) {
            __nanosleep(100);
            uint32_t d;
            asm volatile("{\n.reg .pred p, q;\n.reg .b32 a, b, c0, c1;\nmov.b32 c0, 0;\nmov.b32 c1, 0;\n"
                         "atom.relaxed.gpu.global.exch.b32 a, [%1], -1;\natom.relaxed.gpu.global.exch.b32 b, [%2], -1;\n"
                         "setp.eq.u32 p, a, -1;\n@p mov.u32 c0, %%clock;\nsetp.eq.u32 q, b, -1;\n@q mov.u32 c1, %%clock;\nsub.u32 %0, c1, c0;\n}"
                         : "=r"(d) : "l"(pr + (r & 1) * 4096), "l"(pr + (~r & 1) * 4096) : "memory");
            vote += (d > 90) == (r & 1) ? 1 : -1;
        }
        const uint32_t side = __shfl_sync(0xffffffffu, vote, 0) > 0;
        while (true) {
            const uint4 e = ld4(p.sc->ready + lane * 4);
            if (__all_sync(0xffffffffu, e.x == tag && e.y == tag && e.z == tag && e.w == tag)) break;
            __nanosleep(500);
            if (++n > SPIN_LIMIT) __trap();
        }
        if (lane == 0) {
            sts32(sbase + SM_MISC + 4, side);
            mbar_arrive(bar_side);
            if (b == 0) p.sc->epoch = tag;
        }
        unsigned char* hdst = p.xa + (hoff + (side ^ 1) * 4096 + (lane >> 4) * 512 + (lane & 15) * 4);
        unsigned char* hdst2 = p.xa + (hoff + side * 4096 + (lane >> 4) * 512 + (lane & 15) * 4);
        unsigned char* adst = p.xa + (aoff + (lane >> 4) * 4096 + (lane & 15) * 2);
        __nv_bfloat16* odst = p.out + u2 * 16 + (lane & 15);
        uint32_t r0 = sbase + SM_RED + lane * 48, r1 = sbase + SM_RED + (lane & 15) * 48;
        uint32_t res;
        asm volatile("ld.global.nc.u16 %0, [%1];" : "=r"(res) : "l"(p.x + u2 * 16 + (lane & 15)));
        pin(hdst); pin(hdst2); pin(adst); pin(odst); pin(r0); pin(r1);
        {
            uint32_t ro = sbase + SM_RO + l24 * 160;
            pin(ro);
            asm volatile("bar.sync 5, 224;" ::: "memory");
            const uint32_t v = pack_bf(sum8(ro + 80) + sum8(ro + 112), sum8(ro) + sum8(ro + 32));
            st1(slot[0], v); st1(slot[1], v);
        }
        if (has_wo) {
            fin_sync<3>();
            const uint32_t v = in_word(sum8(r0));
            st1(hdst, v); st1(hdst2, v);
        }
        if (has_f1) {
            fin_sync<4>();
            float mean_b, inv_den;
            ln_finish(sum8(sbase + SM_LN), sum8(sbase + SM_LN + 32), mean_b, inv_den);
            const float gr = fmaf(-mean_b, sum8(r1 + 48 * 48), sum8(r1 + 32 * 48)) * inv_den;
            mbar_wait_after(bar_up, r0, gr);
            const float gs = bfr(gr);
            const float up = bfr(fmaf(-mean_b, sum8(r1 + 80 * 48), sum8(r1 + 64 * 48)) * inv_den);
            st16(adst, pack_bf(0.f, silu_b(gs) * up));
            if (b == 0 && lane < 8) st1(p.sc->late + lane, 0);
        }
        if (has_f2) {
            mbar_wait(bar_tail + 8 * (NWP + NF1 + 3), 0);
            const unsigned char* hsrc = p.xa + ((lane >> 4) * (1 << 14) + side * 4096 + (u2 & 7) * 512 + (u2 >> 3) * 64 + (lane & 15) * 4);
            uint32_t e[3];
            do {
#pragma unroll
                for (int i = 0; i < 3; i++) e[i] = ld1(hsrc + xa_h(2 * i));
                if (++n > SPIN_LIMIT) __trap();
            } while (__any_sync(0xffffffffu, max(max(e[0], e[1]), e[2]) == SENT));
            float f[3];
#pragma unroll
            for (int i = 0; i < 3; i++) f[i] = __uint_as_float(e[i]) + __uint_as_float(__shfl_xor_sync(0xffffffffu, e[i], 16));
            res = add_bf2(res, pack_bf(0.f, (f[0] + f[1]) + f[2]));
            pin(res);
            fin_sync<6>();
            asm volatile("st.global.u16 [%0], %1;" ::"l"(odst), "h"((unsigned short)add_bf2(res, pack_bf(0.f, sum8(r1 + 96 * 48)))) : "memory");
        }
    } else {
        const int g = lane >> 2, t = lane & 3;
        uint2 xres;
        {
            uint32_t xr;
            uint2 xu[5];
            const char* xb = reinterpret_cast<const char*>(p.x);
            asm volatile("ld.global.nc.u16 %0, [%1];" : "=r"(xr) : "l"(xb + (sp * 160 + min(tid, 159)) * 2));
#pragma unroll
            for (int i = 0; i < 5; i++) asm volatile("ld.global.nc.v2.u32 {%0, %1}, [%2];" : "=r"(xu[i].x), "=r"(xu[i].y) : "l"(xb + i * 256 + lane * 8));
            asm volatile("ld.global.nc.v2.u32 {%0, %1}, [%2];" : "=r"(xres.x), "=r"(xres.y) : "l"(xb + min(g, 4) * 256 + warp * 32 + t * 8));
            if (lane >= 20) xres.x = xres.y = 0;
            float s1 = 0.f, s2 = 0.f, mean_b, inv_den;
#pragma unroll
            for (int i = 0; i < 5; i++) { ln_acc(xu[i].x, s1, s2); ln_acc(xu[i].y, s1, s2); }
            ln_finish(warp_sum(s1), warp_sum(s2), mean_b, inv_den);
            sts16(sbase + SM_P + warp * 64 + ((lane >> 1 & 3) * 8 + (lane >> 3) * 2 + (lane & 1)) * 2, ln_apply2(xr, mean_b, inv_den));
            asm volatile("cp.async.wait_all;" ::: "memory");
            asm volatile("bar.sync 2, 512;" ::: "memory");
        }
        uint32_t va[3];
#pragma unroll
        for (int i = 0; i < 3; i++) {
            const int cc = 3 * warp + i, row = 3 * lane + (cc >> 3);
            va[i] = sbase + row * 128 + (((cc ^ row) & 7) << 4);
        }
        const uint32_t tag = lds32(sbase + SM_MISC);
        const int gi = g >= 3 ? g - 3 : g;
        const uint32_t t4 = (tag & 7) + 1;
        auto pdst = [&](int n) {
            return p.xa + ((xa_p(n, warp >> 1, b >> 4) ^ (n >= NHEAD - NLATE ? g >= 3 : warp >> 1 & 1) << 12) + (b & 15) * 192 + (warp & 1) * 96 + gi * 32 + t * 8);
        };

#pragma unroll 1
        for (int ph = 0; ph < 2; ph++) {
            if (ph == 1) {
                uint32_t ka[3];
#pragma unroll
                for (int j = 0; j < 3; j++) {
                    const int row = 3 * (lane & 15) + j;
                    ka[j] = sbase + row * 128 + ((((lane >> 4) ^ row) & 7) << 4) + warp * TILE_BYTES;
                }
                const uint32_t t16 = (tag & 0x7fff) + 1;
#pragma unroll 1
                for (int it = 0; it < 4; it++) {
                    uint4 qf[6];
#pragma unroll
                    for (int i = 0; i < 6; i++) qf[i] = lds128(sbase + SM_Q + warp * 1536 + it * 384 + t * 96 + i * 16);
                    const int slot = (it & 1) * 8 + warp;
                    const uint32_t so = (it & 1) * 8 * TILE_BYTES;
                    float c[2][2][4];
                    zero4(c[0][0]); zero4(c[0][1]); zero4(c[1][0]); zero4(c[1][1]);
                    mbar_wait(bar_full + 8 * slot, it >> 1);
#pragma unroll
                    for (int ks = 0; ks < 12; ks++) {
                        const uint32_t a = (ka[ks >> 2] + so) ^ ((ks & 3) << 5);
                        uint32_t f0[4], f1[4];
                        ldsm_x4(f0, a); ldsm_x4(f1, a + 16 * DH * 2);
                        const uint32_t b0 = ks & 1 ? qf[ks >> 1].z : qf[ks >> 1].x, b1 = ks & 1 ? qf[ks >> 1].w : qf[ks >> 1].y;
                        mma_bf16(c[0][ks & 1], f0, b0, b1); mma_bf16(c[1][ks & 1], f1, b0, b1);
                    }
                    if (lane == 0) mbar_arrive8(bar_empty + 8 * slot);
                    const float v = t & 2 ? (t & 1 ? c[1][0][2] + c[1][1][2] : c[1][0][0] + c[1][1][0]) : (t & 1 ? c[0][0][2] + c[0][1][2] : c[0][0][0] + c[0][1][0]);
                    const float sc = bfr(bfr(v) * 0.07216878364870322f), m = warp_max(sc), e = ex2((sc - m) * L2E), l = warp_sum(e);
                    sts16(sbase + SM_P + (it * 8 + warp) * 64 + ((g >> 1) * 8 + t * 2 + (g & 1)) * 2, pack_bf(0.f, e));
                    sts64(sbase + SM_ST + (it * 8 + warp) * 8, (__float_as_uint(m) & 0xffff0000u) | t16, __float_as_uint(l));
                }
                if (lane == 0) mbar_arrive(bar_stat);
                cons_sync();
            }
            float acc[3][4];
#pragma unroll
            for (int i = 0; i < 3; i++) zero4(acc[i]);
            const int nt = ph ? NKT : NQT, nr = min(head + (head >= NHEAD - NLATE ? p.rlast : p.rdelay), NKT - 1);
            uint32_t v0, v1;
#pragma unroll 1
            for (int n = 0; n < nt; n++) {
                const int slot = ph ? (n & (NSLOT - 1)) : QSLOT + n;
                const uint4 w = lds128(sbase + SM_P + n * 64 + t * 16);
                unsigned char* dst = pdst(n);
                if (ph) mbar_wait(bar_full + 8 * slot, (n >> 4) & 1);
                uint32_t f[3][4];
#pragma unroll
                for (int i = 0; i < 3; i++) ldsm_x4_t(f[i], va[i] + slot * TILE_BYTES);
#pragma unroll
                for (int i = 0; i < 3; i++) mma_bf16(acc[i], w.x, w.x, w.y, w.y, f[i][0], f[i][1]);
#pragma unroll
                for (int i = 0; i < 3; i++) mma_bf16(acc[i], w.z, w.z, w.w, w.w, f[i][2], f[i][3]);
                if (lane == 0) mbar_arrive(bar_empty + 8 * slot);
                v0 = (__float_as_uint(gi == 0 ? acc[0][0] : gi == 1 ? acc[1][0] : acc[2][0]) & ~15u) | t4;
                v1 = (__float_as_uint(gi == 0 ? acc[0][1] : gi == 1 ? acc[1][1] : acc[2][1]) & ~15u) | t4;
                if (!ph) continue;
                if (g < (n >= NHEAD - NLATE ? 6 : 3)) st2(dst, v0, v1);
#pragma unroll
                for (int i = 0; i < 3; i++) zero4(acc[i]);
                if (n >= 20 && n < 20 + NLATE && g < 6) st2(pdst(n + NHEAD - NLATE - 20), 0, 0);
                if (n == nr && tid == 0) mbar_arrive(bar_go);
            }
            if (ph == 1) break;
            if (g < 3) st2(p.sc->qbuf + b * 96 + warp * 12 + lane, v0, v1);
            {
                uint64_t e[6][2];
                uint32_t n = 0;
                bool ok;
#pragma unroll 1
                do {
                    do __nanosleep(100); while ((int)(now_ns() - (t0 + p.t_q2)) < 0);
                    ok = true;
#pragma unroll
                    for (int i = 0; i < 6; i++) pkt_ld2(reinterpret_cast<const uint4*>(p.sc->qall) + warp * 192 + i * 32 + lane, e[i][0], e[i][1]);
#pragma unroll
                    for (int i = 0; i < 6; i++) ok = ok && tag_ok(e[i][0], tag) && tag_ok(e[i][1], tag);
                    if (++n > SPIN_LIMIT) __trap();
                } while (!__all_sync(0xffffffffu, ok));
#pragma unroll
                for (int i = 0; i < 6; i++) sts64(sbase + SM_Q + warp * 1536 + i * 256 + lane * 8, (uint32_t)e[i][0], (uint32_t)e[i][1]);
            }
            cons_sync();
        }
        mbar_wait(bar_side, 0);
        const uint32_t side = lds32(sbase + SM_MISC + 4) * 4096;
        const unsigned char* osrc = p.xa + (xa_o(kg * 64 + warp) + side + lane * 8);
        const int r16 = (lane & 7) + ((lane >> 4) << 3), mi = lane >> 3 & 1;
        const uint32_t f32 = sbase + r16 * 32 + ((mi ^ (lane >> 2 & 1)) << 4);
        uint32_t rdst = sbase + SM_RED + (t * 8 + g) * 48 + warp * 4;
        uint32_t bl = sbase + SM_BC + warp * 512 + t * 80, bs = bl + g * 8;
        uint32_t hl = g < 4 ? bl : sbase + SM_ONE;
        uint32_t w1a = f32 + SM_W1 + warp * 512, w2a = f32 + SM_W2 + warp * 1024;
        uint32_t lnd = lane < 2 ? sbase + SM_LN + lane * 32 + warp * 4 : sbase + SM_BC + warp * 512 + 384 + lane * 4;
        const unsigned char* hs = p.xa + (side + warp * 512 + lane * 16);
        const unsigned char* as = p.xa + (XA_A + side + warp * 384 + min(lane, 23) * 16);
        uint32_t al = sbase + SM_BC + warp * 512 + t * 16, at = sbase + SM_BC + warp * 512 + lane * 16;
        uint32_t fl = role, ln = lane;
        pin_u(fl); pin(ln);
        const bool f1 = fl & 2, f2 = fl & 4, odd = ln & 1, first = ln == 0;
        constexpr uint32_t b2 = bar_tail + 8 * (NWP + NF1);
        pin(rdst); pin(bs); pin(hl); pin(w1a); pin(w2a); pin(lnd); pin(hs); pin(as); pin(al); pin(at);
#define F_(i, c) __uint_as_float(e[i].c)
        if (has_wo) {
            uint4 e[4];
            uint32_t n = 0;
            uint2 o;
            const uint32_t wa = sbase + (warp * 16 + r16) * 64 + ((mi ^ (r16 >> 1 & 3)) << 4), wb = wa ^ 32;
            float c0[4], c1[4];
            zero4(c0); zero4(c1);
            mbar_wait(bar_tail + 8 * 2, 0);
            uint32_t miss = ~0u;
#pragma unroll
            for (int h = 0; h < 2; h++) {
                const uint32_t need = h ? ~0u : (1u << 4 * 6) - 1;
                if (miss & need) {
#pragma unroll 1
                    do {
                        o = ld2(osrc);
                        if (++n > SPIN_LIMIT) __trap();
                        miss = __ballot_sync(0xffffffffu, max(o.x, o.y) == SENT);
                    } while (miss & need);
                    sts64(bs, o.x, o.y);
                    __syncwarp();
#pragma unroll
                    for (int i = h ? 6 / 2 : 0; i < 4; i++) e[i] = lds128(bl + i * 16);
                }
#pragma unroll
                for (int j = h ? 6 : 0; j < (h ? NWP : 6); j++) {
                    mbar_wait(bar_tail + 8 * j, 0);
                    uint32_t f0[4], f1[4];
                    ldsm_x4_t(f0, wa + j * 8192); ldsm_x4_t(f1, wb + j * 8192);
                    const uint32_t b0 = j & 1 ? e[j >> 1].z : e[j >> 1].x, b1 = j & 1 ? e[j >> 1].w : e[j >> 1].y;
                    mma_bf16(c0, f0, b0, b1); mma_bf16(c1, f1, b0, b1);
                }
            }
            sts32(rdst, t & 2 ? (t & 1 ? c1[2] : c1[0]) : (t & 1 ? c0[2] : c0[0]));
            fin_arrive<3>();
        }
        if (f1) {
            constexpr uint32_t b1 = bar_tail + 8 * NWP;
            uint32_t a1[5][4], a3[5][4];
            uint4 e[NG];
#pragma unroll
            for (int i = 0; i < NG; i++) e[i].x = e[i].y = e[i].z = e[i].w = 0;
            uint32_t got = 0, n = 0;
#pragma unroll
            for (int i = 0; i < NB; i++) a3[i][0] = a3[i][1] = a3[i][2] = a3[i][3] = 0;
            mbar_wait(b1, 0);
#pragma unroll
            for (int i = 0; i < NG; i++) ld4p(hs + xa_h(i), e[i], lane < 20);
            mbar_wait(b1 + 8, 0);
#pragma unroll
            for (int i = 0; i < 5; i++) ldsm_x4_t(a1[i], w1a + i * 4096);
            uint4 hb0, hb1;
            uint2 hb2;
            float sv[4];
#pragma unroll 1
            while (true) {
#define S_(f, c) (((f(e[0].c) + f(e[1].c)) + (f(e[2].c) + f(e[3].c))) + (f(e[4].c) + f(e[5].c)))
                const float sx = S_(__uint_as_float, x), sy = S_(__uint_as_float, y), sz = S_(__uint_as_float, z), sw = S_(__uint_as_float, w), sa = (sx + sy) + (sz + sw);
#undef S_
                const uint32_t h0 = add_bf2(xres.x, pack_bf(sy, sx)), h1 = add_bf2(xres.y, pack_bf(sw, sz));
                sts64(bs, h0, h1);
                __syncwarp();
                hb0 = lds128(hl); hb1 = lds128(hl + 16); hb2 = lds64(hl + 32);
                const float a = bf_lo(h0), b = bf_hi(h0), c = bf_lo(h1), d = bf_hi(h1);
                const float s1 = (a + b) + (c + d), s2 = fmaf(a, a, b * b) + fmaf(c, c, d * d);
                sv[0] = odd ? s2 : s1;
                sv[1] = __shfl_xor_sync(0xffffffffu, odd ? s1 : s2, 1);
                sv[2] = __shfl_xor_sync(0xffffffffu, sv[0], 2);
                sv[3] = __shfl_xor_sync(0xffffffffu, odd ? s1 : s2, 3);
                bool miss = __any_sync(0xffffffffu, sa != sa);
                if (miss) {
                    miss = false;
#pragma unroll
                    for (int i = 0; i < NG; i++) {
                        const bool m = max4(e[i]) == SENT;
                        ld4p(hs + xa_h(i), e[i], m);
                        miss = miss || m;
                    }
                    ldsm_if<4096>(a3[0], a3[1], w1a + (SM_W3 - SM_W1), b1 + 16, got);
                    if (++n > SPIN_LIMIT) __trap();
                    miss = __any_sync(0xffffffffu, miss);
                }
                if (!miss) break;
            }
            float cg[3][4], cu[3][4];
#pragma unroll
            for (int i = 0; i < 3; i++) { zero4(cg[i]); zero4(cu[i]); }
            const uint32_t hb[5][2] = {{hb0.x, hb0.y}, {hb0.z, hb0.w}, {hb1.x, hb1.y}, {hb1.z, hb1.w}, {hb2.x, hb2.y}};
            const float st = (sv[0] + sv[1]) + (sv[2] + sv[3]);
#pragma unroll
            for (int i = 0; i < 4; i++) sv[i] = __shfl_down_sync(0xffffffffu, st, 4 * i + 4);
#pragma unroll
            for (int i = 0; i < 5; i++) mma_bf16(cg[i % 3], a1[i], hb[i][0], hb[i][1]);
            sts32(lnd, ((st + sv[0]) + sv[1]) + (sv[2] + sv[3]));
            sts32(rdst + 32 * 48, odd ? (cg[0][2] + cg[2][2]) + cg[1][2] : (cg[0][0] + cg[2][0]) + cg[1][0]);
            fin_arrive<4>();
            if (__any_sync(0xffffffffu, !got)) {
                mbar_wait(b1 + 16, 0);
#pragma unroll
                for (int i = 0; i < NB; i++) ldsm_x4_t(a3[i], w1a + (SM_W3 - SM_W1) + i * 4096);
            }
            mbar_wait(b1 + 24, 0);
#pragma unroll
            for (int i = NB; i < 5; i++) ldsm_x4_t(a3[i], w1a + (SM_W3 - SM_W1) + i * 4096);
#pragma unroll
            for (int i = 0; i < 5; i++) mma_bf16(cu[i % 3], a3[i], hb[i][0], hb[i][1]);
            sts32(rdst + 64 * 48, odd ? (cu[0][2] + cu[2][2]) + cu[1][2] : (cu[0][0] + cu[2][0]) + cu[1][0]);
            __syncwarp();
            if (first) mbar_arrive(bar_up);
        }
        if (f2) {
            uint32_t a2[NF2][2][4];
#pragma unroll
            for (int i = 0; i < 4; i++) a2[NF2 - 1][0][i] = a2[NF2 - 1][1][i] = 0;
#pragma unroll
            for (int j = 0; j < NF2 - 1; j++) {
                mbar_wait(b2 + 8 * j, 0);
                ldsm_x4_t(a2[j][0], w2a + j * 8192); ldsm_x4_t(a2[j][1], w2a + j * 8192 + 512);
            }
            uint32_t n = 0, got = 0;
            uint4 e[NF2];
#pragma unroll 1
            while (true) {
                const uint4 pa = ld4(as);
                ldsm_if<512>(a2[NF2 - 1][0], a2[NF2 - 1][1], w2a + (NF2 - 1) * 8192, b2 + 8 * (NF2 - 1), got);
                if (++n > SPIN_LIMIT) __trap();
                sts128(at, pa);
                __syncwarp();
#pragma unroll
                for (int j = 0; j < 3; j++) e[j] = lds128v(al + j * 64);
                if (__all_sync(0xffffffffu, ok8(pa))) break;
            }
#pragma unroll
            for (int j = 3; j < NF2; j++) e[j] = lds128v(al + j * 64);
            float c[6][4];
#pragma unroll
            for (int j = 0; j < 6; j++) zero4(c[j]);
#pragma unroll
            for (int j = 0; j < NF2; j++) { mma_bf16(c[(j % 3) * 2], a2[j][0], e[j].x, e[j].y); mma_bf16(c[(j % 3) * 2 + 1], a2[j][1], e[j].z, e[j].w); }
            if (__any_sync(0xffffffffu, !got)) {
                constexpr int j = NF2 - 1;
                mbar_wait(b2 + 8 * j, 0);
                ldsm_x4_t(a2[j][0], w2a + j * 8192); ldsm_x4_t(a2[j][1], w2a + j * 8192 + 512);
                mma_bf16(c[4], a2[j][0], e[j].x, e[j].y); mma_bf16(c[5], a2[j][1], e[j].z, e[j].w);
            }
            sts32(rdst + 96 * 48, odd ? (((c[0][2] + c[1][2]) + (c[2][2] + c[3][2])) + c[4][2]) + c[5][2] : (((c[0][0] + c[1][0]) + (c[2][0] + c[3][0])) + c[4][0]) + c[5][0]);
            fin_arrive<6>();
        }
#undef F_
    }
}

typedef CUresult (*EncodeTiledFn)(CUtensorMap*, CUtensorMapDataType, cuuint32_t, void*, const cuuint64_t*, const cuuint64_t*,
                                  const cuuint32_t*, const cuuint32_t*, CUtensorMapInterleave, CUtensorMapSwizzle,
                                  CUtensorMapL2promotion, CUtensorMapFloatOOBfill);

void make_map(EncodeTiledFn fn, CUtensorMap* tm, const void* w, const int (&d)[5], const int (&st)[4], const int (&bx)[5],
              CUtensorMapSwizzle sw, int promo) {
    cuuint64_t dims[5], strides[4];
    cuuint32_t box[5], estr[5];
    for (int i = 0; i < 5; i++) { dims[i] = (cuuint64_t)d[i]; box[i] = (cuuint32_t)bx[i]; estr[i] = 1; }
    for (int i = 0; i < 4; i++) strides[i] = (cuuint64_t)st[i];
    fn(tm, CU_TENSOR_MAP_DATA_TYPE_BFLOAT16, 5, const_cast<void*>(w), dims, strides, box, estr, CU_TENSOR_MAP_INTERLEAVE_NONE, sw,
       (CUtensorMapL2promotion)promo, CU_TENSOR_MAP_FLOAT_OOB_FILL_NONE);
}

enum { T_PER, T_LEAD, T_STAG, T_TD, T_PERO, T_F1D, T_PERF, T_F2, T_PER2, T_Q, T_PWO, T_PW13, T_PW2, T_TG, T_GA, T_TGA, T_TG0, T_SH, T_INFL, T_DZ, T_Q2, T_ST, T_RD, T_RL, T_PKV, T_N };
int g_tune[T_N] = {478, 1150, 4, -30, 289, 250, 113, 1357, 125, 4800, 2, 2, 2, 1490, 250, 250, 75, 15, 5, 30, 6200, 1800, 3, 1, 2};

}

extern "C" void kernel_launch(void* const* d_in, const int* in_sizes, int n_in, void* d_out, int out_size) {
    (void)in_sizes; (void)n_in; (void)out_size;
    static EncodeTiledFn encode = nullptr;
    static Scratch* scratch = nullptr;
    static unsigned char* xarea = nullptr;
    if (!encode) {
        void* sp = nullptr;
        cudaGetSymbolAddress(&sp, g_scratch);
        scratch = reinterpret_cast<Scratch*>(sp);
        cudaGetSymbolAddress(&sp, g_xarea);
        xarea = reinterpret_cast<unsigned char*>((reinterpret_cast<uintptr_t>(sp) + XA_ALIGN - 1) / XA_ALIGN * XA_ALIGN);
        void* fn = nullptr;
        cudaDriverEntryPointQueryResult st;
        cudaGetDriverEntryPoint("cuTensorMapEncodeTiled", &fn, cudaEnableDefault, &st);
        encode = reinterpret_cast<EncodeTiledFn>(fn);
        cudaFuncSetAttribute(fused_decode_kernel, cudaFuncAttributeMaxDynamicSharedMemorySize, SM_TOTAL);
        int dev = 0, khz = 0, bits = 0;
        cudaGetDevice(&dev);
        if (cudaDeviceGetAttribute(&khz, cudaDevAttrMemoryClockRate, dev) == cudaSuccess &&
            cudaDeviceGetAttribute(&bits, cudaDevAttrGlobalMemoryBusWidth, dev) == cudaSuccess && khz > 0 && bits > 0) {
            const double f = 2619000.0 * 5120.0 / ((double)khz * bits);
            for (int i : {T_PER, T_STAG, T_PERO, T_PERF, T_F2, T_Q, T_Q2}) g_tune[i] = (int)(g_tune[i] * f + 0.5);
        }
        (void)cudaGetLastError();
    }
    const int* T = g_tune;
    KParams p;
    p.x = (const __nv_bfloat16*)d_in[0];
    p.wq = (const __nv_bfloat16*)d_in[3];
    p.out = (__nv_bfloat16*)d_out;
    p.sc = scratch;
    p.xa = xarea;
    p.per = T[T_PER];
    p.stag = T[T_STAG];
    p.t_k0 = (NQT + 1) * T[T_PER] - T[T_LEAD];
    {
        int t = p.t_k0 + 2 * NKT * T[T_PER] + T[T_STAG] * 3 / 2 + T[T_SH] * 31 / 2 + T[T_TD];
        for (int i = 0; i < NWP; i++, t += T[T_PERO]) p.item[i] = t;
        for (int i = 0, t1 = t + T[T_F1D]; i < NP1; i++, t1 += T[T_PERF]) p.item[NWP + i] = t1;
        for (int i = 0, t2 = t + T[T_F2]; i < NF2; i++, t2 += T[T_PER2]) p.item[NWP + NP1 + i] = t2;
        for (int i = NITEM; i < 32; i++) p.item[i] = 0;
    }
    p.target = T[T_TG]; p.t_q = T[T_Q]; p.t_q2 = T[T_Q2]; p.t_stat = T[T_ST]; p.rdelay = T[T_RD]; p.rlast = T[T_RL]; p.gain = T[T_GA] / 100.f; p.tgain = T[T_TGA] / 47800.f; p.tg0 = T[T_TG0] / 10.f; p.dz = T[T_DZ] / 10.f; p.stagh = T[T_SH]; p.infl = T[T_INFL]; p.t_fill = p.t_k0 + 55 * T[T_PER];
    for (int i = 0, nw = 0, n1 = 0, n2 = 0; i < NCTA; i++) {
        const int grp = i >> 2;
        const bool f2 = grp % 3 == 2, both = grp == 8 || grp == 23, wo = !both, f1 = !f2 || both;
        p.role[i] = (wo ? 1 | nw / 20 << 3 | nw % 20 << 6 : 0) | (f1 ? 2 | n1 << 11 : 0) | (f2 ? 4 | n2 << 18 : 0);
        nw += wo; n1 += f1; n2 += f2;
    }
    TMaps tm;
    constexpr int R1 = FF * 2, R2 = D_MODEL * 2;
    for (int i = 0; i < 2; i++)
        make_map(encode, &tm.k + i, d_in[1 + i], {64, 96, 1, 1, NHEAD * SK / 32}, {128, TILE_BYTES, TILE_BYTES, TILE_BYTES}, {64, 96, 1, 1, 1}, CU_TENSOR_MAP_SWIZZLE_128B, T[T_PKV]);
    make_map(encode, &tm.wo, d_in[4], {D_MODEL, 2, 4, 2, NHEAD * DH / 16}, {R2, 4 * R2, 2 * R2, 16 * R2}, {32, 2, 4, 2, 8}, CU_TENSOR_MAP_SWIZZLE_64B, T[T_PWO]);
    make_map(encode, &tm.w1, d_in[6], {FF, 2, 4, 2, D_MODEL / 16}, {R1, 4 * R1, 2 * R1, 16 * R1}, {16, 2, 4, 2, 8}, CU_TENSOR_MAP_SWIZZLE_32B, T[T_PW13]);
    make_map(encode, &tm.w3, d_in[7], {FF, 2, 4, 2, D_MODEL / 16}, {R1, 4 * R1, 2 * R1, 16 * R1}, {16, 2, 4, 2, 8}, CU_TENSOR_MAP_SWIZZLE_32B, T[T_PW13]);
    make_map(encode, &tm.w2, d_in[8], {D_MODEL, 2, 4, 4, FF / 32}, {R2, 8 * R2, 2 * R2, 32 * R2}, {16, 2, 4, 4, 8}, CU_TENSOR_MAP_SWIZZLE_32B, T[T_PW2]);
    fused_decode_kernel<<<NCTA, NTHREADS, SM_TOTAL, cudaStreamPerThread>>>(p, tm);
}
```

```cpp
#include <cuda_runtime.h>
#include <cuda_bf16.h>
#include <cuda.h>
#include <stdint.h>
#include <initializer_list>

namespace {

constexpr int D_MODEL = 640;
constexpr int NHEAD = 32;
constexpr int DH = 192;
constexpr int SK = 32768;
constexpr int WIN = 4096;
constexpr int FF = 1536;

constexpr int NCTA = 128;
constexpr int NTHREADS = 256 + 64 + 192;
constexpr int TILE_BYTES = 32 * DH * 2;
constexpr int NSLOT = 16;
constexpr int NKT = 32;
constexpr int NQT = 5;
constexpr int QSLOT = NSLOT - NQT;
constexpr int NG = 6;
constexpr int NWP = 8, NP1 = 10, NF2 = 6;
constexpr int NITEM = NWP + NP1 + NF2;
constexpr int NF1 = 4, NA = 2, NB = 2;
constexpr int NTAIL = NWP + NF1 + NF2;

constexpr uint32_t sbase = 1024;
constexpr int SM_W1 = NWP * 8192, SM_W3 = SM_W1 + 20480, SM_W2 = SM_W3 + 20480;
constexpr int SM_P = NSLOT * TILE_BYTES;
constexpr int SM_Q = SM_P + 2048;
constexpr int SM_RED = SM_Q + 12288;
constexpr int SM_BC = SM_RED + 128 * 48;
constexpr int SM_ONE = SM_BC + 4096;
constexpr int SM_ST = SM_ONE + 64;
constexpr int SM_WT = SM_ST + 256;
constexpr int SM_RO = SM_WT + 512;
constexpr int SM_LN = SM_RO + 48 * 80;
constexpr int SM_MISC = SM_LN + 64;
constexpr int SM_LATE = SM_MISC + 32;
constexpr int SM_BAR = SM_LATE + 32;
constexpr int SM_TOTAL = SM_BAR + 512;
static_assert(SM_TOTAL <= 232448, "shared memory");

struct __align__(128) Scratch {
    uint2 qbuf[NCTA * 96];
    uint2 qall[NHEAD * 96];
    uint2 mbuf[NCTA * NHEAD];
    uint32_t ready[NCTA];
    uint32_t late[32];
    uint32_t epoch;
};
__device__ Scratch g_scratch;
constexpr int XA_ALIGN = 2 << 20;
constexpr uint32_t SENT = 0xffffffffu;
__device__ unsigned char g_xarea[XA_ALIGN + (9 << 20)];
__device__ __forceinline__ uint32_t xa_o(uint32_t kw, uint32_t j) { return (kw >> 4) * 16384 + (kw & 15) * 256 + j * 32; }
constexpr int NLATE = 4;
__device__ __forceinline__ uint32_t xa_p(uint32_t h, uint32_t q, uint32_t j) {
    const uint32_t k = ((NHEAD - 1 - h) * 4 + q) * 8 + j;
    return (1 << 20) + (2 * k + ((k ^ (k >> 3) ^ (k >> 4) ^ (k >> 6)) & 1)) * 4096;
}
__host__ __device__ constexpr uint32_t xa_h(uint32_t i) { return (1 << 18) + (i >> 2) * (3 << 16) + (i & 3) * (1 << 14); }
constexpr uint32_t XA_A = xa_h(NG);

constexpr uint32_t XA_PROBE = 1 << 13 | 1 << 19;

constexpr uint32_t SPIN_LIMIT = 1u << 22;

__device__ __forceinline__ uint32_t smem_u32(const void* p) { return (uint32_t)__cvta_generic_to_shared(p); }
__device__ __forceinline__ uint32_t now_ns() { uint64_t t; asm volatile("mov.u64 %0, %globaltimer;" : "=l"(t)); return (uint32_t)t; }
__device__ __forceinline__ void mbar_init(uint32_t bar, uint32_t cnt) {
    asm volatile("mbarrier.init.shared::cta.b64 [%0], %1;" ::"r"(bar), "r"(cnt) : "memory");
}
__device__ __forceinline__ void mbar_expect_tx(uint32_t bar, uint32_t bytes) {
    asm volatile("mbarrier.arrive.expect_tx.shared::cta.b64 _, [%0], %1;" ::"r"(bar), "r"(bytes) : "memory");
}
__device__ __forceinline__ void mbar_arrive(uint32_t bar) {
    asm volatile("mbarrier.arrive.shared::cta.b64 _, [%0];" ::"r"(bar) : "memory");
}
__device__ __forceinline__ void mbar_arrive8(uint32_t bar) {
    asm volatile("mbarrier.arrive.shared::cta.b64 _, [%0], 8;" ::"r"(bar) : "memory");
}
__device__ __forceinline__ bool mbar_test(uint32_t bar, uint32_t parity) {
    uint32_t ok;
    asm volatile("{\n.reg .pred p;\nmbarrier.test_wait.parity.shared::cta.b64 p, [%1], %2;\nselp.u32 %0, 1, 0, p;\n}"
                 : "=r"(ok) : "r"(bar), "r"(parity) : "memory");
    return ok;
}
__device__ __forceinline__ void mbar_wait(uint32_t bar, uint32_t parity) {
    asm volatile("{\n.reg .pred p;\nW_%=:\nmbarrier.try_wait.parity.shared::cta.b64 p, [%0], %1;\n@!p bra.uni W_%=;\n}" ::"r"(bar), "r"(parity) : "memory");
}
__device__ __forceinline__ void mbar_wait_after(uint32_t bar, uint32_t dump, float v) {
    uint32_t ok;
    asm volatile("{\n.reg .pred p;\nmbarrier.try_wait.parity.shared::cta.b64 p, [%1], 0;\nselp.u32 %0, 1, 0, p;\n}" : "=r"(ok) : "r"(bar) : "memory");
    asm volatile("st.volatile.shared.f32 [%0], %1;" ::"r"(dump), "f"(v) : "memory");
    if (__builtin_expect(!ok, 0)) mbar_wait(bar, 0);
}
__device__ __forceinline__ void tma_load_at(uint32_t when, uint32_t dst, const CUtensorMap* tm, int c0, int c4, uint32_t bar, uint64_t pol) {
    asm volatile("{\n.reg .pred p, e;\n.reg .b64 t;\n.reg .b32 lo, hi;\nelect.sync _|e, -1;\n"
                 "W_%=:\nmov.u64 t, %globaltimer;\nmov.b64 {lo, hi}, t;\nsub.u32 lo, lo, %7;\nsetp.lt.s32 p, lo, 0;\n@p bra.uni W_%=;\n"
                 "@e cp.async.bulk.tensor.5d.shared::cluster.global.mbarrier::complete_tx::bytes.L2::cache_hint [%0], [%1, {%3, %5, %5, %5, %4}], [%2], %6;\n}"
                 ::"r"(dst), "l"(reinterpret_cast<uint64_t>(tm)), "r"(bar), "r"(c0), "r"(c4), "r"(0), "l"(pol), "r"(when) : "memory");
}
__device__ __forceinline__ void pin(uint32_t& v) { asm volatile("shfl.sync.bfly.b32 %0, %0, 0, 31, -1;" : "+r"(v) :: "memory"); }
__device__ __forceinline__ void pin_u(uint32_t& v) { asm volatile("shfl.sync.idx.b32 %0, %0, 0, 31, -1;" : "+r"(v) :: "memory"); }
template <class T> __device__ __forceinline__ void pin(T*& v) {
    asm volatile("{\n.reg .b32 a, b;\nmov.b64 {a, b}, %0;\nshfl.sync.bfly.b32 a, a, 0, 31, -1;\nshfl.sync.bfly.b32 b, b, 0, 31, -1;\nmov.b64 %0, {a, b};\n}" : "+l"(v) :: "memory");
}
__device__ __forceinline__ void sts16(uint32_t a, uint32_t v) { asm volatile("st.shared.u16 [%0], %1;" ::"r"(a), "h"((unsigned short)v) : "memory"); }
__device__ __forceinline__ void sts32(uint32_t a, float v) { asm volatile("st.shared.f32 [%0], %1;" ::"r"(a), "f"(v) : "memory"); }
__device__ __forceinline__ void sts32(uint32_t a, uint32_t v) { asm volatile("st.shared.u32 [%0], %1;" ::"r"(a), "r"(v) : "memory"); }
__device__ __forceinline__ void sts64(uint32_t a, uint32_t x, uint32_t y) { asm volatile("st.shared.v2.u32 [%0], {%1, %2};" ::"r"(a), "r"(x), "r"(y) : "memory"); }
__device__ __forceinline__ void sts128(uint32_t a, const uint4& v) { asm volatile("st.shared.v4.u32 [%0], {%1, %2, %3, %4};" ::"r"(a), "r"(v.x), "r"(v.y), "r"(v.z), "r"(v.w) : "memory"); }
__device__ __forceinline__ void cons_sync() { asm volatile("bar.sync 1, 256;" ::: "memory"); }
template <int ID> __device__ __forceinline__ void fin_arrive() { asm volatile("bar.arrive %0, 288;" ::"n"(ID) : "memory"); }
template <int ID> __device__ __forceinline__ void fin_sync() { asm volatile("bar.sync %0, 288;" ::"n"(ID) : "memory"); }

__device__ __forceinline__ uint4 lds128(uint32_t a) {
    uint4 v;
    asm volatile("ld.shared.v4.u32 {%0,%1,%2,%3}, [%4];" : "=r"(v.x), "=r"(v.y), "=r"(v.z), "=r"(v.w) : "r"(a) : "memory");
    return v;
}
__device__ __forceinline__ uint4 lds128v(uint32_t a) {
    uint4 v;
    asm volatile("ld.volatile.shared.v4.u32 {%0,%1,%2,%3}, [%4];" : "=r"(v.x), "=r"(v.y), "=r"(v.z), "=r"(v.w) : "r"(a) : "memory");
    return v;
}
__device__ __forceinline__ float4 lds128f(uint32_t a) {
    float4 v;
    asm volatile("ld.shared.v4.f32 {%0,%1,%2,%3}, [%4];" : "=f"(v.x), "=f"(v.y), "=f"(v.z), "=f"(v.w) : "r"(a) : "memory");
    return v;
}
__device__ __forceinline__ uint2 lds64(uint32_t a) {
    uint2 v;
    asm volatile("ld.shared.v2.u32 {%0,%1}, [%2];" : "=r"(v.x), "=r"(v.y) : "r"(a) : "memory");
    return v;
}
__device__ __forceinline__ uint32_t lds32(uint32_t a) {
    uint32_t v;
    asm volatile("ld.shared.u32 %0, [%1];" : "=r"(v) : "r"(a) : "memory");
    return v;
}
__device__ __forceinline__ float sum8(uint32_t a) {
    const float4 x = lds128f(a), y = lds128f(a + 16);
    return ((x.x + x.y) + (x.z + x.w)) + ((y.x + y.y) + (y.z + y.w));
}
__device__ __forceinline__ void ldsm_x4(uint32_t* r, uint32_t a) {
    asm volatile("ldmatrix.sync.aligned.m8n8.x4.shared.b16 {%0,%1,%2,%3}, [%4];"
                 : "=r"(r[0]), "=r"(r[1]), "=r"(r[2]), "=r"(r[3]) : "r"(a) : "memory");
}
__device__ __forceinline__ void ldsm_x4_t(uint32_t* r, uint32_t a) {
    asm volatile("ldmatrix.sync.aligned.m8n8.x4.trans.shared.b16 {%0,%1,%2,%3}, [%4];"
                 : "=r"(r[0]), "=r"(r[1]), "=r"(r[2]), "=r"(r[3]) : "r"(a) : "memory");
}
template <int STRIDE>
__device__ __forceinline__ void ldsm_if(uint32_t* r0, uint32_t* r1, uint32_t a, uint32_t bar, uint32_t& got) {
        asm volatile("{\n.reg .pred p, q;\nsetp.eq.u32 q, %8, 0;\nmbarrier.test_wait.parity.shared::cta.b64 p, [%10], 0;\nand.pred p, p, q;\n"
                     "@p ldmatrix.sync.aligned.m8n8.x4.trans.shared.b16 {%0,%1,%2,%3}, [%9];\n"
                     "@p ldmatrix.sync.aligned.m8n8.x4.trans.shared.b16 {%4,%5,%6,%7}, [%9+%11];\n@p mov.u32 %8, 1;\n}"
                     : "+r"(r0[0]), "+r"(r0[1]), "+r"(r0[2]), "+r"(r0[3]), "+r"(r1[0]), "+r"(r1[1]), "+r"(r1[2]), "+r"(r1[3]), "+r"(got)
                     : "r"(a), "r"(bar), "n"(STRIDE) : "memory");
}
__device__ __forceinline__ void mma_bf16(float* c, uint32_t a0, uint32_t a1, uint32_t a2, uint32_t a3, uint32_t b0, uint32_t b1) {
    asm volatile("mma.sync.aligned.m16n8k16.row.col.f32.bf16.bf16.f32 {%0,%1,%2,%3}, {%4,%5,%6,%7}, {%8,%9}, {%0,%1,%2,%3};"
                 : "+f"(c[0]), "+f"(c[1]), "+f"(c[2]), "+f"(c[3]) : "r"(a0), "r"(a1), "r"(a2), "r"(a3), "r"(b0), "r"(b1));
}
__device__ __forceinline__ void mma_bf16(float* c, const uint32_t* a, uint32_t b0, uint32_t b1) { mma_bf16(c, a[0], a[1], a[2], a[3], b0, b1); }
__device__ __forceinline__ void zero4(float* c) { c[0] = c[1] = c[2] = c[3] = 0.f; }
__device__ __forceinline__ float bf_lo(uint32_t u) { return __uint_as_float(u << 16); }
__device__ __forceinline__ float bf_hi(uint32_t u) { return __uint_as_float(u & 0xffff0000u); }
__device__ __forceinline__ uint32_t pack_bf(float hi, float lo) { uint32_t r; asm("cvt.rn.bf16x2.f32 %0, %1, %2;" : "=r"(r) : "f"(hi), "f"(lo)); return r; }
__device__ __forceinline__ uint32_t add_bf2(uint32_t a, uint32_t b) { uint32_t r; asm("add.rn.bf16x2 %0, %1, %2;" : "=r"(r) : "r"(a), "r"(b)); return r; }
__device__ __forceinline__ float bfr(float x) { return __uint_as_float(pack_bf(x, 0.f)); }

__device__ __forceinline__ uint32_t in_word(float v) { return __float_as_uint(v); }
__device__ __forceinline__ void st1(void* p, uint32_t v) {
    asm volatile("st.relaxed.gpu.global.u32 [%0], %1;" ::"l"(p), "r"(v) : "memory");
}
__device__ __forceinline__ void st16(void* p, uint32_t v) {
    asm volatile("st.relaxed.gpu.global.u16 [%0], %1;" ::"l"(p), "h"((unsigned short)v) : "memory");
}
__device__ __forceinline__ void st2(void* p, uint32_t a, uint32_t b) {
    asm volatile("st.relaxed.gpu.global.v2.u32 [%0], {%1, %2};" ::"l"(p), "r"(a), "r"(b) : "memory");
}
__device__ __forceinline__ void st4(void* p, uint32_t a, uint32_t b, uint32_t c, uint32_t d) {
    asm volatile("st.relaxed.gpu.global.v4.u32 [%0], {%1, %2, %3, %4};" ::"l"(p), "r"(a), "r"(b), "r"(c), "r"(d) : "memory");
}
__device__ __forceinline__ uint32_t ld1(const void* p) {
    uint32_t v;
    asm volatile("ld.relaxed.gpu.global.u32 %0, [%1];" : "=r"(v) : "l"(p) : "memory");
    return v;
}
__device__ __forceinline__ uint2 ld2(const void* p) {
    uint2 v;
    asm volatile("ld.relaxed.gpu.global.v2.u32 {%0, %1}, [%2];" : "=r"(v.x), "=r"(v.y) : "l"(p) : "memory");
    return v;
}
__device__ __forceinline__ uint4 ld4(const void* p) {
    uint4 v;
    asm volatile("ld.relaxed.gpu.global.v4.u32 {%0, %1, %2, %3}, [%4];" : "=r"(v.x), "=r"(v.y), "=r"(v.z), "=r"(v.w) : "l"(p) : "memory");
    return v;
}
__device__ __forceinline__ void ld4p(const void* p, uint4& v, bool on) {
    asm volatile("{\n.reg .pred q;\nsetp.ne.u32 q, %5, 0;\n@q ld.relaxed.gpu.global.v4.u32 {%0, %1, %2, %3}, [%4];\n}"
                 : "+r"(v.x), "+r"(v.y), "+r"(v.z), "+r"(v.w) : "l"(p), "r"((uint32_t)on) : "memory");
}
__device__ __forceinline__ bool ok8(const uint4& v) {
    const uint32_t m = __vimax3_u16x2(__vimax3_u16x2(v.x, v.y, v.z), v.w, v.w);
    return __vimax3_u16x2(m, m << 16, m >> 16) != SENT;
}
__device__ __forceinline__ uint32_t max4(const uint4& v) { return max(max(v.x, v.y), max(v.z, v.w)); }
__device__ __forceinline__ void pkt_ld2(const uint4* p, uint64_t& a, uint64_t& b) {
    asm volatile("ld.relaxed.gpu.global.v2.b64 {%0, %1}, [%2];" : "=l"(a), "=l"(b) : "l"(p) : "memory");
}
__device__ __forceinline__ bool tag_ok(uint64_t v, uint32_t tag) { return (uint32_t)(v >> 32) == tag; }
__device__ __forceinline__ float val_of(uint64_t v) { return __uint_as_float((uint32_t)v); }

__device__ __forceinline__ float warp_sum(float v) {
#pragma unroll
    for (int o = 16; o > 0; o >>= 1) v += __shfl_xor_sync(0xffffffffu, v, o);
    return v;
}
__device__ __forceinline__ float warp_max(float v) {
#pragma unroll
    for (int o = 16; o > 0; o >>= 1) v = fmaxf(v, __shfl_xor_sync(0xffffffffu, v, o));
    return v;
}
__device__ __forceinline__ float sqrt_fast(float x) { float r; asm("sqrt.approx.ftz.f32 %0, %1;" : "=f"(r) : "f"(x)); return r; }
__device__ __forceinline__ float rcp_fast(float x) { float r; asm("rcp.approx.ftz.f32 %0, %1;" : "=f"(r) : "f"(x)); return r; }
__device__ __forceinline__ float ex2(float x) { float r; asm("ex2.approx.ftz.f32 %0, %1;" : "=f"(r) : "f"(x)); return r; }
constexpr float L2E = 1.4426950408889634f;
__device__ __forceinline__ void ln_finish(float s1, float s2, float& mean_b, float& inv_den) {
    const float mean = s1 * (1.0f / D_MODEL);
    const float var = fmaxf(fmaf(-mean, mean, s2 * (1.0f / D_MODEL)), 0.f);
    mean_b = bfr(mean);
    inv_den = rcp_fast(bfr(sqrt_fast(bfr(bfr(var) + 1e-5f))));
}
__device__ __forceinline__ uint32_t ln_apply2(uint32_t u, float mean_b, float inv_den) {
    const uint32_t d = pack_bf(bf_hi(u) - mean_b, bf_lo(u) - mean_b);
    return pack_bf(bf_hi(d) * inv_den, bf_lo(d) * inv_den);
}
__device__ __forceinline__ void ln_acc(uint32_t u, float& s1, float& s2) {
    const float a = bf_lo(u), b = bf_hi(u);
    s1 += a + b;
    s2 = fmaf(a, a, fmaf(b, b, s2));
}
__device__ __forceinline__ float silu_b(float g) { return bfr(__fdividef(g, 1.0f + ex2(-g * L2E))); }

struct KParams {
    const __nv_bfloat16* wq;
    const __nv_bfloat16* x;
    __nv_bfloat16* out;
    Scratch* sc;
    unsigned char* xa;
    int t_k0, per, stag, stagh;
    int target, infl;
    float dz, gain, tg0, tgain;
    int t_q, t_q2, t_stat, t_fill;
    int rdelay, rlast;
    uint32_t item[32];
    uint32_t role[NCTA];
};
struct TMaps { CUtensorMap k, v, wo, w1, w3, w2; };

__global__ void __launch_bounds__(NTHREADS, 1)
fused_decode_kernel(const __grid_constant__ KParams p, const __grid_constant__ TMaps tm) {
    extern __shared__ __align__(1024) unsigned char smem[];
    const int tid = threadIdx.x;
    const int b = blockIdx.x;
    const int head = b >> 2, sp = b & 3;
    {
        const char* a = reinterpret_cast<const char*>(p.wq) + (uint32_t)((sp * 160 + (tid >> 2)) * (NHEAD * DH * 2) + head * (DH * 2) + (tid & 3) * 128);
        if (tid < 320) asm volatile("prefetch.global.L2 [%0];" ::"l"(a) : "memory");
    }
    if (tid < 256) {
        const uint32_t r = tid >> 3, ch = tid & 7;
        const char* src = reinterpret_cast<const char*>(p.wq) + ((sp * 160 + r) * (NHEAD * DH * 2) + head * (DH * 2) + ch * 16);
#pragma unroll
        for (int i = 0; i < NQT; i++) {
#pragma unroll
            for (int j = 0; j < 3; j++)
                asm volatile("cp.async.cg.shared.global [%0], [%1], 16;"
                             ::"r"(sbase + (QSLOT + i) * TILE_BYTES + (3 * r + j) * 128 + ((ch ^ ((3 * r + j) & 7)) << 4)),
                               "l"(src + (size_t)i * 32 * (NHEAD * DH * 2) + j * 128) : "memory");
        }
    }
    const uint32_t t0 = now_ns();
    const int warp = __shfl_sync(0xffffffffu, tid >> 5, 0), lane = tid & 31;
    const uint32_t role = p.role[b];
    const int kg = role >> 3 & 7, ng = role >> 6 & 31;
    const int u1 = role >> 11 & 127, u2 = role >> 18;
    const bool has_wo = role & 1, has_f1 = role & 2, has_f2 = role & 4;
    constexpr uint32_t bar_full = sbase + SM_BAR;
    constexpr uint32_t bar_empty = sbase + SM_BAR + 128;
    constexpr uint32_t bar_tail = sbase + SM_BAR + 256;
    constexpr uint32_t bar_rdy = bar_tail + 8 * NTAIL;
    constexpr uint32_t bar_side = bar_rdy + 8;
    constexpr uint32_t bar_wt = bar_side + 8;
    constexpr uint32_t bar_go = bar_side + 16;
    constexpr uint32_t bar_stat = bar_side + 24;
    constexpr uint32_t bar_up = bar_side + 32;

    if (warp == 8) {
        if (smem_u32(smem) != sbase) __trap();
        uint64_t pol;
        asm volatile("createpolicy.fractional.L2::evict_first.b64 %0, 1.0;" : "=l"(pol));
        sts32(sbase + SM_LATE + (lane & 7) * 4, 0u);
        if (lane == 0) {
#pragma unroll
            for (int i = 0; i < 32 + NTAIL + 6; i++)
                mbar_init(bar_full + 8 * i, (i >= 16 && i < 32) || i > 35 + NTAIL ? 8 : i == 32 + NWP ? NA : i == 33 + NWP ? 5 - NA : i == 34 + NWP ? NB : i == 35 + NWP ? 5 - NB : 1);
#pragma unroll
            for (int i = 0; i < 6; i++) asm volatile("prefetch.tensormap [%0];" ::"l"(reinterpret_cast<uint64_t>(&tm.k + i)) : "memory");
            asm volatile("fence.mbarrier_init.release.cluster;" ::: "memory");
        }
        __syncwarp();
        asm volatile("bar.arrive 2, 512;" ::: "memory");
        const uint32_t tu = __shfl_sync(0xffffffffu, t0, 0);
        if (b == 0 && lane < 8) st1(p.sc->late + lane, lane ? 0 : (tu & 0xffffffu) | 1u << 24);
        const int seg = (lane >= NWP) + (lane >= NWP + NP1), i = lane - (seg == 0 ? 0 : seg == 1 ? NWP : NWP + NP1);
        const bool todo = lane < NITEM && (role >> seg & 1);
        const uint32_t len = seg == 1 ? 4096 : 8192, dst = sbase + (seg == 0 ? 0 : seg == 1 ? SM_W1 : SM_W2) + i * len;
        const int w3 = seg == 1 && i >= 5;
        const uint32_t mi = seg == 2 ? 3 : seg + w3;
        const int c0 = seg == 0 ? ng * 32 : seg == 1 ? u1 * 16 : u2 * 16;
        const int c4 = (seg == 0 ? kg * 64 : w3 * -40) + i * 8;
        const uint32_t bar = bar_tail + 8 * (seg == 0 ? i : seg == 1 ? NWP + (i >= NA) + w3 + (i >= 5 + NB) : NWP + NF1 + i);
        const int tile0 = (SK - WIN) / 32 + b;
        uint32_t tk = tu + p.t_k0 + sp * p.stag + head * p.stagh, tw = tk, acc = 0;
        int slip = 0, base = 0, w = 0, d0 = 0;
        float a2 = 0.f, drift = 0.f;
#pragma unroll 1
        for (int n = 0; n < 2 * NKT; n++) {
            const int slot = n & (NSLOT - 1);
            mbar_wait(bar_empty + 8 * slot, (((n + NQT) >> 4) & 1) ^ 1);
            if (lane == 0) mbar_expect_tx(bar_full + 8 * slot, TILE_BYTES);
            bool more;
            do {
                const uint32_t t = now_ns();
                if (__all_sync(0xffffffffu, mbar_test(bar_full + 8 * (w & (NSLOT - 1)), (w >> 4) & 1))) {
                    acc += t - tw;
                    tw += p.per;
                    w++;
                    if ((w & 7) == 0) {
                        if (lane == 0) asm volatile("red.relaxed.gpu.global.add.u32 [%0], %1;" ::"l"(p.sc->late + (w >> 3)), "r"((1u << 24) + min(max(((int)acc >> 3) + d0, 0), 65535)) : "memory");
                        acc = 0;
                    }
                }
                more = __any_sync(0xffffffffu, (int)(t - tk) < slip - 60) || w <= n - p.infl;
            } while (more);
            tma_load_at(tk + slip, sbase + slot * TILE_BYTES, &tm.k + (n >> 5), 0, tile0 + (n & (NKT - 1)) * (SK / 32), bar_full + 8 * slot, pol);
            tk += p.per;
            if ((n & 7) == 5 && lane < 2)
                asm volatile("cp.async.cg.shared.global [%0], [%1], 16;" ::"r"(sbase + SM_LATE + lane * 16), "l"(p.sc->late + lane * 4) : "memory");
            const uint32_t org = lds32(sbase + SM_LATE);
            if (org) d0 = (int)((tu - org) << 8) >> 8;
            int k = n >> 3;
            uint32_t rep = lds32(sbase + SM_LATE + k * 4);
            const uint32_t rep0 = lds32(sbase + SM_LATE + max(k - 1, 0) * 4);
            if (!(rep >> 30)) { rep = rep0; k--; }
            if (rep >> 30) {
                const float a = (float)(rep & 0xffffffu) * rcp_fast((float)(rep >> 24));
                if (k <= 2) a2 = a; else drift = fminf(fmaxf((a - a2) * rcp_fast((float)(8 * k - 16)), -12.f), 12.f);
                base = max((int)a - p.target - d0, -900);
                slip = base + (int)(fmaxf(drift - p.dz, 0.f) * p.gain * (float)(n + 5 - 8 * k));
            }
        }
        const uint32_t tn = tu + base + p.item[lane] + (int)(drift * fmaf(p.tgain, (float)(int)(p.item[lane] - p.item[0]), p.tg0));
        if (todo) mbar_expect_tx(bar, len);
        const uint32_t c04 = c0 | c4 << 16, db = dst | (bar - bar_tail) << 18 | mi << 28;
#pragma unroll 1
        for (uint32_t left = __ballot_sync(0xffffffffu, todo); left; left &= left - 1) {
            const int k = __ffs(left) - 1;
            const uint32_t kc = __shfl_sync(0xffffffffu, c04, k), kd = __shfl_sync(0xffffffffu, db, k), kt = __shfl_sync(0xffffffffu, tn, k);
            mbar_wait(bar_empty + 8 * (k < NWP ? 5 : 12), k < NWP);
            tma_load_at(kt, kd & 0x3ffff, &tm.wo + (kd >> 28), kc & 0xffff, kc >> 16, bar_tail + (kd >> 18 & 0x3ff), pol);
        }
    } else if (warp >= 10) {
        asm volatile("bar.sync 2, 512;" ::: "memory");
        const uint32_t t4 = (lds32(sbase + SM_MISC) & 7) + 1, id = tid - 320, sg = id / 12;
        while (!mbar_test(bar_wt, 0)) __nanosleep(500);
        const float4 wa = lds128f(sbase + SM_WT + sg * 32), wb = lds128f(sbase + SM_WT + sg * 32 + 16);
        const float wt[8] = {wa.x, wa.y, wa.z, wa.w, wb.x, wb.y, wb.z, wb.w};
        uint32_t sd = sp & 1;
        if (head >= NHEAD - NLATE) {
            while (!mbar_test(bar_side, 0)) __nanosleep(200);
            sd = lds32(sbase + SM_MISC + 4);
        }
        const uint32_t o0 = (xa_p(head, sp, 0) ^ sd << 12) + id * 16;
        const unsigned char* a0 = p.xa + o0;
        const unsigned char* a1 = p.xa + (o0 ^ 4096);
        uint32_t dst = sbase + SM_RO + (id - sg * 12) * 320 + sg * 4;
        pin(a0); pin(a1); pin(dst);
        mbar_wait(bar_go, 0);
        uint4 e[8];
#pragma unroll
        for (int j = 0; j < 8; j++) e[j] = ld4((j & 1 ? a1 : a0) + j * 8192);
        uint32_t k = 0;
        bool miss;
#pragma unroll 1
        do {
            miss = false;
#pragma unroll
            for (int j = 0; j < 8; j++) {
                const bool m = (((e[j].x ^ t4) | (e[j].y ^ t4) | (e[j].z ^ t4) | (e[j].w ^ t4)) & 15) != 0;
                ld4p((j & 1 ? a1 : a0) + j * 8192, e[j], m);
                miss = miss || m;
            }
            if (++k > SPIN_LIMIT) __trap();
        } while (__any_sync(0xffffffffu, miss));
        float o[4] = {0.f, 0.f, 0.f, 0.f};
#pragma unroll
        for (int j = 0; j < 8; j++) {
            o[0] = fmaf(wt[j], __uint_as_float(e[j].x ^ t4), o[0]); o[1] = fmaf(wt[j], __uint_as_float(e[j].y ^ t4), o[1]);
            o[2] = fmaf(wt[j], __uint_as_float(e[j].z ^ t4), o[2]); o[3] = fmaf(wt[j], __uint_as_float(e[j].w ^ t4), o[3]);
        }
#pragma unroll
        for (int i = 0; i < 4; i++) sts32(dst + i * 80, o[i]);
        asm volatile("bar.arrive 5, 224;" ::: "memory");
    } else if (warp == 9) {
        const uint32_t tag = ld1(&p.sc->epoch) + 1;
        const uint32_t aoff = XA_A + (u1 >> 1 & 7) * 384 + (u1 >> 4) * 64 + (u1 & 1) * 32, hoff = xa_h(kg) + (ng & 3) * 1024 + (ng >> 2) * 64;
        sts32(sbase + SM_ONE + (lane & 15) * 4, 0x3f803f80u);
        const uint32_t l24 = min(lane, 23), od = head * 12 + sp * 3 + (l24 >> 3);
        const uint32_t ooff = xa_o((od >> 6) * 8 + (od & 7), od >> 3 & 7);
        unsigned char* slot[3] = {p.xa + (ooff + (l24 & 7) * 4), p.xa + (ooff + (l24 & 7) * 4 + 4096),
                                  p.xa + (lane < 16 ? (has_wo ? hoff + (lane >> 3) * 4096 + (lane >> 2 & 1) * 512 + (lane & 3) * 16 : ooff) : has_f1 ? aoff + (lane >> 1 & 1) * 4096 + (lane & 1) * 16 : ooff)};
#pragma unroll
        for (int i = 0; i < 2; i++) st4(p.sc->qbuf + b * 96 + i * 32 + lane * 2, 0, 0, 0, 0);
        uint2* qdst = p.sc->qall + ((head & 7) * 4 + (head >> 3)) * 96 + sp * 24 + l24;
        st2(qdst, 0, 0);
        sts32(sbase + SM_MISC, tag);
        asm volatile("bar.sync 2, 512;" ::: "memory");
        uint32_t n = 0;
        {
            const uint32_t t4 = (tag & 7) + 1;
            uint2 e[4];
            uint32_t bad;
#pragma unroll 1
            do {
                do __nanosleep(100); while ((int)(now_ns() - (t0 + p.t_q)) < 0);
                bad = 0;
#pragma unroll
                for (int i = 0; i < 4; i++) e[i] = ld2(p.sc->qbuf + (head * 4 + i) * 96 + l24 * 4 + sp);
#pragma unroll
                for (int i = 0; i < 4; i++) { e[i].x ^= t4; e[i].y ^= t4; bad |= e[i].x | e[i].y; }
                if (++n > SPIN_LIMIT) __trap();
            } while (__any_sync(0xffffffffu, bad & 15));
#define S_(c) ((__uint_as_float(e[0].c) + __uint_as_float(e[1].c)) + (__uint_as_float(e[2].c) + __uint_as_float(e[3].c)))
            asm volatile("st.relaxed.gpu.global.b64 [%0], %1;" ::"l"(qdst), "l"((uint64_t)tag << 32 | pack_bf(S_(y), S_(x))) : "memory");
#undef S_
        }
        {
            while (!mbar_test(bar_stat, 0)) __nanosleep(200);
            const uint2 st = lds64(sbase + SM_ST + lane * 8);
            asm volatile("st.relaxed.gpu.global.b64 [%0], %1;" ::"l"(p.sc->mbuf + b * NHEAD + lane), "l"((uint64_t)st.y << 32 | st.x) : "memory");
            const uint32_t t1 = now_ns() + p.t_stat, t16 = (tag & 0x7fff) + 1;
            uint64_t e[4];
            do {
                do __nanosleep(200); while ((int)(now_ns() - t1) < 0);
#pragma unroll
                for (int i = 0; i < 4; i++) asm volatile("ld.relaxed.gpu.global.b64 %0, [%1];" : "=l"(e[i]) : "l"(p.sc->mbuf + (lane + 32 * i) * NHEAD + head) : "memory");
#pragma unroll
                for (int i = 0; i < 4; i++) e[i] ^= t16;
                if (++n > SPIN_LIMIT) __trap();
            } while (__any_sync(0xffffffffu, (e[0] | e[1] | e[2] | e[3]) & 0xffff));
            const float M = warp_max(fmaxf(fmaxf(val_of(e[0]), val_of(e[1])), fmaxf(val_of(e[2]), val_of(e[3]))));
            float x[4], L = 0.f;
#pragma unroll
            for (int i = 0; i < 4; i++) { x[i] = ex2((val_of(e[i]) - M) * L2E); L = fmaf(x[i], val_of(e[i] >> 32), L); }
            L = rcp_fast(warp_sum(L));
#pragma unroll
            for (int i = 0; i < 4; i++) sts32(sbase + SM_WT + (lane & 15) * 32 + (lane >> 4) * 4 + i * 8, x[i] * L);
            __syncwarp();
            if (lane == 0) mbar_arrive(bar_wt);
        }
        unsigned char* pr = p.xa + (xa_h(b & 7) + XA_PROBE + (b >> 3) * 128 + lane * 4);
        st1(pr, SENT); st1(pr + 4096, SENT);
        int vote = 0;
#pragma unroll 1
        for (int r = 0; r < 9 && (!vote || (int)(now_ns() - (t0 + p.t_fill)) < -1000); r++) {
            __nanosleep(100);
            uint32_t d;
            asm volatile("{\n.reg .pred p, q;\n.reg .b32 a, b, c0, c1;\nmov.b32 c0, 0;\nmov.b32 c1, 0;\n"
                         "atom.relaxed.gpu.global.exch.b32 a, [%1], -1;\natom.relaxed.gpu.global.exch.b32 b, [%2], -1;\n"
                         "setp.eq.u32 p, a, -1;\n@p mov.u32 c0, %%clock;\nsetp.eq.u32 q, b, -1;\n@q mov.u32 c1, %%clock;\nsub.u32 %0, c1, c0;\n}"
                         : "=r"(d) : "l"(pr + (r & 1) * 4096), "l"(pr + (~r & 1) * 4096) : "memory");
            vote += (d > 90) == (r & 1) ? 1 : -1;
        }
        const uint32_t side = __shfl_sync(0xffffffffu, vote, 0) > 0;
        if (lane == 0) { sts32(sbase + SM_MISC + 4, side); mbar_arrive(bar_side); }
        while ((int)(now_ns() - (t0 + p.t_fill)) < 0) __nanosleep(200);
        st1(slot[0], SENT); st1(slot[1], SENT); st4(slot[2], SENT, SENT, SENT, SENT);
        uint32_t ack = SENT;
#pragma unroll
        for (int i = 0; i < 3; i++) { uint32_t v; asm volatile("atom.relaxed.gpu.global.exch.b32 %0, [%1], -1;" : "=r"(v) : "l"(slot[i]) : "memory"); ack &= v; }
        if (__any_sync(0xffffffffu, ack != SENT)) __trap();
        if (lane == 0) st1(p.sc->ready + b, tag);
        const uint32_t t2 = now_ns() + 1500;
        while (true) {
            do __nanosleep(200); while ((int)(now_ns() - t2) < 0);
            const uint4 e = ld4(p.sc->ready + lane * 4);
            if (__all_sync(0xffffffffu, e.x == tag && e.y == tag && e.z == tag && e.w == tag)) break;
            if (++n > SPIN_LIMIT) __trap();
        }
        if (lane == 0) {
            mbar_arrive(bar_rdy);
            if (b == 0) p.sc->epoch = tag;
        }
        unsigned char* hdst = p.xa + (hoff + (side ^ 1) * 4096 + (lane >> 4) * 512 + (lane & 15) * 4);
        unsigned char* hdst2 = p.xa + (hoff + side * 4096 + (lane >> 4) * 512 + (lane & 15) * 4);
        unsigned char* adst = p.xa + (aoff + (lane >> 4) * 4096 + (lane & 15) * 2);
        __nv_bfloat16* odst = p.out + u2 * 16 + (lane & 15);
        uint32_t r0 = sbase + SM_RED + lane * 48, r1 = sbase + SM_RED + (lane & 15) * 48;
        uint32_t res;
        asm volatile("ld.global.nc.u16 %0, [%1];" : "=r"(res) : "l"(p.x + u2 * 16 + (lane & 15)));
        pin(hdst); pin(hdst2); pin(adst); pin(odst); pin(r0); pin(r1);
        {
            uint32_t ro = sbase + SM_RO + l24 * 160;
            pin(ro);
            asm volatile("bar.sync 5, 224;" ::: "memory");
            const uint32_t v = pack_bf(sum8(ro + 80) + sum8(ro + 112), sum8(ro) + sum8(ro + 32));
            st1(slot[0], v); st1(slot[1], v);
        }
        if (has_wo) {
            fin_sync<3>();
            const uint32_t v = in_word(sum8(r0));
            st1(hdst, v); st1(hdst2, v);
        }
        if (has_f1) {
            fin_sync<4>();
            float mean_b, inv_den;
            ln_finish(sum8(sbase + SM_LN), sum8(sbase + SM_LN + 32), mean_b, inv_den);
            const float gr = fmaf(-mean_b, sum8(r1 + 48 * 48), sum8(r1 + 32 * 48)) * inv_den;
            mbar_wait_after(bar_up, r0, gr);
            const float gs = bfr(gr);
            const float up = bfr(fmaf(-mean_b, sum8(r1 + 80 * 48), sum8(r1 + 64 * 48)) * inv_den);
            st16(adst, pack_bf(0.f, silu_b(gs) * up));
            if (b == 0 && lane < 8) st1(p.sc->late + lane, 0);
        }
        if (has_f2) {
            mbar_wait(bar_tail + 8 * (NWP + NF1 + 3), 0);
            const unsigned char* hsrc = p.xa + ((lane >> 4) * (1 << 14) + side * 4096 + (u2 & 7) * 512 + (u2 >> 3) * 64 + (lane & 15) * 4);
            uint32_t e[3];
            do {
#pragma unroll
                for (int i = 0; i < 3; i++) e[i] = ld1(hsrc + xa_h(2 * i));
                if (++n > SPIN_LIMIT) __trap();
            } while (__any_sync(0xffffffffu, max(max(e[0], e[1]), e[2]) == SENT));
            float f[3];
#pragma unroll
            for (int i = 0; i < 3; i++) f[i] = __uint_as_float(e[i]) + __uint_as_float(__shfl_xor_sync(0xffffffffu, e[i], 16));
            res = add_bf2(res, pack_bf(0.f, (f[0] + f[1]) + f[2]));
            pin(res);
            fin_sync<6>();
            asm volatile("st.global.u16 [%0], %1;" ::"l"(odst), "h"((unsigned short)add_bf2(res, pack_bf(0.f, sum8(r1 + 96 * 48)))) : "memory");
        }
    } else {
        const int g = lane >> 2, t = lane & 3;
        uint2 xres;
        {
            uint32_t xr;
            uint2 xu[5];
            const char* xb = reinterpret_cast<const char*>(p.x);
            asm volatile("ld.global.nc.u16 %0, [%1];" : "=r"(xr) : "l"(xb + (sp * 160 + min(tid, 159)) * 2));
#pragma unroll
            for (int i = 0; i < 5; i++) asm volatile("ld.global.nc.v2.u32 {%0, %1}, [%2];" : "=r"(xu[i].x), "=r"(xu[i].y) : "l"(xb + i * 256 + lane * 8));
            asm volatile("ld.global.nc.v2.u32 {%0, %1}, [%2];" : "=r"(xres.x), "=r"(xres.y) : "l"(xb + min(g, 4) * 256 + warp * 32 + t * 8));
            if (lane >= 20) xres.x = xres.y = 0;
            float s1 = 0.f, s2 = 0.f, mean_b, inv_den;
#pragma unroll
            for (int i = 0; i < 5; i++) { ln_acc(xu[i].x, s1, s2); ln_acc(xu[i].y, s1, s2); }
            ln_finish(warp_sum(s1), warp_sum(s2), mean_b, inv_den);
            sts16(sbase + SM_P + warp * 64 + ((lane >> 1 & 3) * 8 + (lane >> 3) * 2 + (lane & 1)) * 2, ln_apply2(xr, mean_b, inv_den));
            asm volatile("cp.async.wait_all;" ::: "memory");
            asm volatile("bar.sync 2, 512;" ::: "memory");
        }
        uint32_t va[3];
#pragma unroll
        for (int i = 0; i < 3; i++) {
            const int cc = 3 * warp + i, row = 3 * lane + (cc >> 3);
            va[i] = sbase + row * 128 + (((cc ^ row) & 7) << 4);
        }
        const uint32_t tag = lds32(sbase + SM_MISC);
        const int gi = g >= 3 ? g - 3 : g;
        const uint32_t t4 = (tag & 7) + 1;
        auto pdst = [&](int n) {
            return p.xa + ((xa_p(n, warp >> 1, b >> 4) ^ (n >= NHEAD - NLATE ? g >= 3 : warp >> 1 & 1) << 12) + (b & 15) * 192 + (warp & 1) * 96 + gi * 32 + t * 8);
        };

#pragma unroll 1
        for (int ph = 0; ph < 2; ph++) {
            if (ph == 1) {
                uint32_t ka[3];
#pragma unroll
                for (int j = 0; j < 3; j++) {
                    const int row = 3 * (lane & 15) + j;
                    ka[j] = sbase + row * 128 + ((((lane >> 4) ^ row) & 7) << 4) + warp * TILE_BYTES;
                }
                const uint32_t t16 = (tag & 0x7fff) + 1;
#pragma unroll 1
                for (int it = 0; it < 4; it++) {
                    uint4 qf[6];
#pragma unroll
                    for (int i = 0; i < 6; i++) qf[i] = lds128(sbase + SM_Q + warp * 1536 + it * 384 + t * 96 + i * 16);
                    const int slot = (it & 1) * 8 + warp;
                    const uint32_t so = (it & 1) * 8 * TILE_BYTES;
                    float c[2][2][4];
                    zero4(c[0][0]); zero4(c[0][1]); zero4(c[1][0]); zero4(c[1][1]);
                    mbar_wait(bar_full + 8 * slot, it >> 1);
#pragma unroll
                    for (int ks = 0; ks < 12; ks++) {
                        const uint32_t a = (ka[ks >> 2] + so) ^ ((ks & 3) << 5);
                        uint32_t f0[4], f1[4];
                        ldsm_x4(f0, a); ldsm_x4(f1, a + 16 * DH * 2);
                        const uint32_t b0 = ks & 1 ? qf[ks >> 1].z : qf[ks >> 1].x, b1 = ks & 1 ? qf[ks >> 1].w : qf[ks >> 1].y;
                        mma_bf16(c[0][ks & 1], f0, b0, b1); mma_bf16(c[1][ks & 1], f1, b0, b1);
                    }
                    if (lane == 0) mbar_arrive8(bar_empty + 8 * slot);
                    const float v = t & 2 ? (t & 1 ? c[1][0][2] + c[1][1][2] : c[1][0][0] + c[1][1][0]) : (t & 1 ? c[0][0][2] + c[0][1][2] : c[0][0][0] + c[0][1][0]);
                    const float sc = bfr(bfr(v) * 0.07216878364870322f), m = warp_max(sc), e = ex2((sc - m) * L2E), l = warp_sum(e);
                    sts16(sbase + SM_P + (it * 8 + warp) * 64 + ((g >> 1) * 8 + t * 2 + (g & 1)) * 2, pack_bf(0.f, e));
                    sts64(sbase + SM_ST + (it * 8 + warp) * 8, (__float_as_uint(m) & 0xffff0000u) | t16, __float_as_uint(l));
                }
                if (lane == 0) mbar_arrive(bar_stat);
                cons_sync();
            }
            float acc[3][4];
#pragma unroll
            for (int i = 0; i < 3; i++) zero4(acc[i]);
            const int nt = ph ? NKT : NQT, nr = min(head + (head >= NHEAD - NLATE ? p.rlast : p.rdelay), NKT - 1);
            uint32_t v0, v1;
#pragma unroll 1
            for (int n = 0; n < nt; n++) {
                const int slot = ph ? (n & (NSLOT - 1)) : QSLOT + n;
                const uint4 w = lds128(sbase + SM_P + n * 64 + t * 16);
                unsigned char* dst = pdst(n);
                if (ph) mbar_wait(bar_full + 8 * slot, (n >> 4) & 1);
                uint32_t f[3][4];
#pragma unroll
                for (int i = 0; i < 3; i++) ldsm_x4_t(f[i], va[i] + slot * TILE_BYTES);
#pragma unroll
                for (int i = 0; i < 3; i++) mma_bf16(acc[i], w.x, w.x, w.y, w.y, f[i][0], f[i][1]);
#pragma unroll
                for (int i = 0; i < 3; i++) mma_bf16(acc[i], w.z, w.z, w.w, w.w, f[i][2], f[i][3]);
                if (lane == 0) mbar_arrive(bar_empty + 8 * slot);
                v0 = (__float_as_uint(gi == 0 ? acc[0][0] : gi == 1 ? acc[1][0] : acc[2][0]) & ~15u) | t4;
                v1 = (__float_as_uint(gi == 0 ? acc[0][1] : gi == 1 ? acc[1][1] : acc[2][1]) & ~15u) | t4;
                if (!ph) continue;
                if (g < (n >= NHEAD - NLATE ? 6 : 3)) st2(dst, v0, v1);
#pragma unroll
                for (int i = 0; i < 3; i++) zero4(acc[i]);
                if (n >= 22 && n < 22 + NLATE && g < 6) st2(pdst(n + NHEAD - NLATE - 22), 0, 0);
                if (n == nr && tid == 0) mbar_arrive(bar_go);
            }
            if (ph == 1) break;
            if (g < 3) st2(p.sc->qbuf + b * 96 + warp * 12 + lane, v0, v1);
            {
                uint64_t e[6][2];
                uint32_t n = 0;
                bool ok;
#pragma unroll 1
                do {
                    do __nanosleep(100); while ((int)(now_ns() - (t0 + p.t_q2)) < 0);
                    ok = true;
#pragma unroll
                    for (int i = 0; i < 6; i++) pkt_ld2(reinterpret_cast<const uint4*>(p.sc->qall) + warp * 192 + i * 32 + lane, e[i][0], e[i][1]);
#pragma unroll
                    for (int i = 0; i < 6; i++) ok = ok && tag_ok(e[i][0], tag) && tag_ok(e[i][1], tag);
                    if (++n > SPIN_LIMIT) __trap();
                } while (!__all_sync(0xffffffffu, ok));
#pragma unroll
                for (int i = 0; i < 6; i++) sts64(sbase + SM_Q + warp * 1536 + i * 256 + lane * 8, (uint32_t)e[i][0], (uint32_t)e[i][1]);
            }
            cons_sync();
        }
        mbar_wait(bar_rdy, 0);
        const uint32_t side = lds32(sbase + SM_MISC + 4) * 4096;
        const unsigned char* osrc = p.xa + (xa_o(kg * 8 + warp, 0) + side + lane * 8);
        const int r16 = (lane & 7) + ((lane >> 4) << 3), mi = lane >> 3 & 1;
        const uint32_t f32 = sbase + r16 * 32 + ((mi ^ (lane >> 2 & 1)) << 4);
        uint32_t rdst = sbase + SM_RED + (t * 8 + g) * 48 + warp * 4;
        uint32_t bl = sbase + SM_BC + warp * 512 + t * 80, bs = bl + g * 8;
        uint32_t hl = g < 4 ? bl : sbase + SM_ONE;
        uint32_t w1a = f32 + SM_W1 + warp * 512, w2a = f32 + SM_W2 + warp * 1024;
        uint32_t lnd = lane < 2 ? sbase + SM_LN + lane * 32 + warp * 4 : sbase + SM_BC + warp * 512 + 384 + lane * 4;
        const unsigned char* hs = p.xa + (side + warp * 512 + lane * 16);
        const unsigned char* as = p.xa + (XA_A + side + warp * 384 + min(lane, 23) * 16);
        uint32_t al = sbase + SM_BC + warp * 512 + t * 16, at = sbase + SM_BC + warp * 512 + lane * 16;
        uint32_t fl = role, ln = lane;
        pin_u(fl); pin(ln);
        const bool f1 = fl & 2, f2 = fl & 4, odd = ln & 1, first = ln == 0;
        constexpr uint32_t b2 = bar_tail + 8 * (NWP + NF1);
        pin(rdst); pin(bs); pin(hl); pin(w1a); pin(w2a); pin(lnd); pin(hs); pin(as); pin(al); pin(at);
#define F_(i, c) __uint_as_float(e[i].c)
        if (has_wo) {
            uint4 e[4];
            uint32_t n = 0;
            uint2 o;
            const uint32_t wa = sbase + (warp * 16 + r16) * 64 + ((mi ^ (r16 >> 1 & 3)) << 4), wb = wa ^ 32;
            float c0[4], c1[4];
            zero4(c0); zero4(c1);
            mbar_wait(bar_tail + 8 * 2, 0);
            uint32_t miss = ~0u;
#pragma unroll
            for (int h = 0; h < 2; h++) {
                const uint32_t need = h ? ~0u : (1u << 4 * 6) - 1;
                if (miss & need) {
#pragma unroll 1
                    do {
                        o = ld2(osrc);
                        if (++n > SPIN_LIMIT) __trap();
                        miss = __ballot_sync(0xffffffffu, max(o.x, o.y) == SENT);
                    } while (miss & need);
                    sts64(bs, o.x, o.y);
                    __syncwarp();
#pragma unroll
                    for (int i = h ? 6 / 2 : 0; i < 4; i++) e[i] = lds128(bl + i * 16);
                }
#pragma unroll
                for (int j = h ? 6 : 0; j < (h ? NWP : 6); j++) {
                    mbar_wait(bar_tail + 8 * j, 0);
                    uint32_t f0[4], f1[4];
                    ldsm_x4_t(f0, wa + j * 8192); ldsm_x4_t(f1, wb + j * 8192);
                    const uint32_t b0 = j & 1 ? e[j >> 1].z : e[j >> 1].x, b1 = j & 1 ? e[j >> 1].w : e[j >> 1].y;
                    mma_bf16(c0, f0, b0, b1); mma_bf16(c1, f1, b0, b1);
                }
            }
            sts32(rdst, t & 2 ? (t & 1 ? c1[2] : c1[0]) : (t & 1 ? c0[2] : c0[0]));
            fin_arrive<3>();
        }
        if (f1) {
            constexpr uint32_t b1 = bar_tail + 8 * NWP;
            uint32_t a1[5][4], a3[5][4];
            uint4 e[NG];
#pragma unroll
            for (int i = 0; i < NG; i++) e[i].x = e[i].y = e[i].z = e[i].w = 0;
            uint32_t got = 0, n = 0;
#pragma unroll
            for (int i = 0; i < NB; i++) a3[i][0] = a3[i][1] = a3[i][2] = a3[i][3] = 0;
            mbar_wait(b1, 0);
#pragma unroll
            for (int i = 0; i < NG; i++) ld4p(hs + xa_h(i), e[i], lane < 20);
            mbar_wait(b1 + 8, 0);
#pragma unroll
            for (int i = 0; i < 5; i++) ldsm_x4_t(a1[i], w1a + i * 4096);
            uint4 hb0, hb1;
            uint2 hb2;
            float sv[4];
#pragma unroll 1
            while (true) {
#define S_(f, c) (((f(e[0].c) + f(e[1].c)) + (f(e[2].c) + f(e[3].c))) + (f(e[4].c) + f(e[5].c)))
                const float sx = S_(__uint_as_float, x), sy = S_(__uint_as_float, y), sz = S_(__uint_as_float, z), sw = S_(__uint_as_float, w), sa = (sx + sy) + (sz + sw);
#undef S_
                const uint32_t h0 = add_bf2(xres.x, pack_bf(sy, sx)), h1 = add_bf2(xres.y, pack_bf(sw, sz));
                sts64(bs, h0, h1);
                __syncwarp();
                hb0 = lds128(hl); hb1 = lds128(hl + 16); hb2 = lds64(hl + 32);
                const float a = bf_lo(h0), b = bf_hi(h0), c = bf_lo(h1), d = bf_hi(h1);
                const float s1 = (a + b) + (c + d), s2 = fmaf(a, a, b * b) + fmaf(c, c, d * d);
                sv[0] = odd ? s2 : s1;
                sv[1] = __shfl_xor_sync(0xffffffffu, odd ? s1 : s2, 1);
                sv[2] = __shfl_xor_sync(0xffffffffu, sv[0], 2);
                sv[3] = __shfl_xor_sync(0xffffffffu, odd ? s1 : s2, 3);
                bool miss = __any_sync(0xffffffffu, sa != sa);
                if (miss) {
                    miss = false;
#pragma unroll
                    for (int i = 0; i < NG; i++) {
                        const bool m = max4(e[i]) == SENT;
                        ld4p(hs + xa_h(i), e[i], m);
                        miss = miss || m;
                    }
                    ldsm_if<4096>(a3[0], a3[1], w1a + (SM_W3 - SM_W1), b1 + 16, got);
                    if (++n > SPIN_LIMIT) __trap();
                    miss = __any_sync(0xffffffffu, miss);
                }
                if (!miss) break;
            }
            float cg[3][4], cu[3][4];
#pragma unroll
            for (int i = 0; i < 3; i++) { zero4(cg[i]); zero4(cu[i]); }
            const uint32_t hb[5][2] = {{hb0.x, hb0.y}, {hb0.z, hb0.w}, {hb1.x, hb1.y}, {hb1.z, hb1.w}, {hb2.x, hb2.y}};
            const float st = (sv[0] + sv[1]) + (sv[2] + sv[3]);
#pragma unroll
            for (int i = 0; i < 4; i++) sv[i] = __shfl_down_sync(0xffffffffu, st, 4 * i + 4);
#pragma unroll
            for (int i = 0; i < 5; i++) mma_bf16(cg[i % 3], a1[i], hb[i][0], hb[i][1]);
            sts32(lnd, ((st + sv[0]) + sv[1]) + (sv[2] + sv[3]));
            sts32(rdst + 32 * 48, odd ? (cg[0][2] + cg[2][2]) + cg[1][2] : (cg[0][0] + cg[2][0]) + cg[1][0]);
            fin_arrive<4>();
            if (__any_sync(0xffffffffu, !got)) {
                mbar_wait(b1 + 16, 0);
#pragma unroll
                for (int i = 0; i < NB; i++) ldsm_x4_t(a3[i], w1a + (SM_W3 - SM_W1) + i * 4096);
            }
            mbar_wait(b1 + 24, 0);
#pragma unroll
            for (int i = NB; i < 5; i++) ldsm_x4_t(a3[i], w1a + (SM_W3 - SM_W1) + i * 4096);
#pragma unroll
            for (int i = 0; i < 5; i++) mma_bf16(cu[i % 3], a3[i], hb[i][0], hb[i][1]);
            sts32(rdst + 64 * 48, odd ? (cu[0][2] + cu[2][2]) + cu[1][2] : (cu[0][0] + cu[2][0]) + cu[1][0]);
            __syncwarp();
            if (first) mbar_arrive(bar_up);
        }
        if (f2) {
            uint32_t a2[NF2][2][4];
#pragma unroll
            for (int i = 0; i < 4; i++) a2[NF2 - 1][0][i] = a2[NF2 - 1][1][i] = 0;
#pragma unroll
            for (int j = 0; j < NF2 - 1; j++) {
                mbar_wait(b2 + 8 * j, 0);
                ldsm_x4_t(a2[j][0], w2a + j * 8192); ldsm_x4_t(a2[j][1], w2a + j * 8192 + 512);
            }
            uint32_t n = 0, got = 0;
            uint4 e[NF2];
#pragma unroll 1
            while (true) {
                const uint4 pa = ld4(as);
                ldsm_if<512>(a2[NF2 - 1][0], a2[NF2 - 1][1], w2a + (NF2 - 1) * 8192, b2 + 8 * (NF2 - 1), got);
                if (++n > SPIN_LIMIT) __trap();
                sts128(at, pa);
                __syncwarp();
#pragma unroll
                for (int j = 0; j < 3; j++) e[j] = lds128v(al + j * 64);
                if (__all_sync(0xffffffffu, ok8(pa))) break;
            }
#pragma unroll
            for (int j = 3; j < NF2; j++) e[j] = lds128v(al + j * 64);
            float c[6][4];
#pragma unroll
            for (int j = 0; j < 6; j++) zero4(c[j]);
#pragma unroll
            for (int j = 0; j < NF2; j++) { mma_bf16(c[(j % 3) * 2], a2[j][0], e[j].x, e[j].y); mma_bf16(c[(j % 3) * 2 + 1], a2[j][1], e[j].z, e[j].w); }
            if (__any_sync(0xffffffffu, !got)) {
                constexpr int j = NF2 - 1;
                mbar_wait(b2 + 8 * j, 0);
                ldsm_x4_t(a2[j][0], w2a + j * 8192); ldsm_x4_t(a2[j][1], w2a + j * 8192 + 512);
                mma_bf16(c[4], a2[j][0], e[j].x, e[j].y); mma_bf16(c[5], a2[j][1], e[j].z, e[j].w);
            }
            sts32(rdst + 96 * 48, odd ? (((c[0][2] + c[1][2]) + (c[2][2] + c[3][2])) + c[4][2]) + c[5][2] : (((c[0][0] + c[1][0]) + (c[2][0] + c[3][0])) + c[4][0]) + c[5][0]);
            fin_arrive<6>();
        }
#undef F_
    }
}

typedef CUresult (*EncodeTiledFn)(CUtensorMap*, CUtensorMapDataType, cuuint32_t, void*, const cuuint64_t*, const cuuint64_t*,
                                  const cuuint32_t*, const cuuint32_t*, CUtensorMapInterleave, CUtensorMapSwizzle,
                                  CUtensorMapL2promotion, CUtensorMapFloatOOBfill);

void make_map(EncodeTiledFn fn, CUtensorMap* tm, const void* w, const int (&d)[5], const int (&st)[4], const int (&bx)[5],
              CUtensorMapSwizzle sw, int promo) {
    cuuint64_t dims[5], strides[4];
    cuuint32_t box[5], estr[5];
    for (int i = 0; i < 5; i++) { dims[i] = (cuuint64_t)d[i]; box[i] = (cuuint32_t)bx[i]; estr[i] = 1; }
    for (int i = 0; i < 4; i++) strides[i] = (cuuint64_t)st[i];
    fn(tm, CU_TENSOR_MAP_DATA_TYPE_BFLOAT16, 5, const_cast<void*>(w), dims, strides, box, estr, CU_TENSOR_MAP_INTERLEAVE_NONE, sw,
       (CUtensorMapL2promotion)promo, CU_TENSOR_MAP_FLOAT_OOB_FILL_NONE);
}

enum { T_PER, T_LEAD, T_STAG, T_TD, T_PERO, T_F1D, T_PERF, T_F2, T_PER2, T_Q, T_PWO, T_PW13, T_PW2, T_TG, T_GA, T_TGA, T_TG0, T_SH, T_INFL, T_DZ, T_Q2, T_ST, T_RD, T_RL, T_PKV, T_N };
int g_tune[T_N] = {478, 1150, 4, -30, 289, 250, 113, 1357, 125, 4800, 2, 2, 2, 1490, 250, 250, 75, 15, 5, 30, 6200, 1800, 3, 1, 2};

}

extern "C" void kernel_launch(void* const* d_in, const int* in_sizes, int n_in, void* d_out, int out_size) {
    (void)in_sizes; (void)n_in; (void)out_size;
    static EncodeTiledFn encode = nullptr;
    static Scratch* scratch = nullptr;
    static unsigned char* xarea = nullptr;
    if (!encode) {
        void* sp = nullptr;
        cudaGetSymbolAddress(&sp, g_scratch);
        scratch = reinterpret_cast<Scratch*>(sp);
        cudaGetSymbolAddress(&sp, g_xarea);
        xarea = reinterpret_cast<unsigned char*>((reinterpret_cast<uintptr_t>(sp) + XA_ALIGN - 1) / XA_ALIGN * XA_ALIGN);
        void* fn = nullptr;
        cudaDriverEntryPointQueryResult st;
        cudaGetDriverEntryPoint("cuTensorMapEncodeTiled", &fn, cudaEnableDefault, &st);
        encode = reinterpret_cast<EncodeTiledFn>(fn);
        cudaFuncSetAttribute(fused_decode_kernel, cudaFuncAttributeMaxDynamicSharedMemorySize, SM_TOTAL);
        int dev = 0, khz = 0, bits = 0;
        cudaGetDevice(&dev);
        if (cudaDeviceGetAttribute(&khz, cudaDevAttrMemoryClockRate, dev) == cudaSuccess &&
            cudaDeviceGetAttribute(&bits, cudaDevAttrGlobalMemoryBusWidth, dev) == cudaSuccess && khz > 0 && bits > 0) {
            const double f = 2619000.0 * 5120.0 / ((double)khz * bits);
            for (int i : {T_PER, T_STAG, T_SH, T_PERO, T_PERF, T_F2, T_Q, T_Q2}) g_tune[i] = (int)(g_tune[i] * f + 0.5);
        }
        (void)cudaGetLastError();
    }
    const int* T = g_tune;
    KParams p;
    p.x = (const __nv_bfloat16*)d_in[0];
    p.wq = (const __nv_bfloat16*)d_in[3];
    p.out = (__nv_bfloat16*)d_out;
    p.sc = scratch;
    p.xa = xarea;
    p.per = T[T_PER];
    p.stag = T[T_STAG];
    p.t_k0 = (NQT + 1) * T[T_PER] - T[T_LEAD];
    {
        int t = p.t_k0 + 2 * NKT * T[T_PER] + T[T_STAG] * 3 / 2 + T[T_SH] * 31 / 2 + T[T_TD];
        for (int i = 0; i < NWP; i++, t += T[T_PERO]) p.item[i] = t;
        for (int i = 0, t1 = t + T[T_F1D]; i < NP1; i++, t1 += T[T_PERF]) p.item[NWP + i] = t1;
        for (int i = 0, t2 = t + T[T_F2]; i < NF2; i++, t2 += T[T_PER2]) p.item[NWP + NP1 + i] = t2;
        for (int i = NITEM; i < 32; i++) p.item[i] = 0;
    }
    p.target = T[T_TG]; p.t_q = T[T_Q]; p.t_q2 = T[T_Q2]; p.t_stat = T[T_ST]; p.rdelay = T[T_RD]; p.rlast = T[T_RL]; p.gain = T[T_GA] / 100.f; p.tgain = T[T_TGA] / 47800.f; p.tg0 = T[T_TG0] / 10.f; p.dz = T[T_DZ] / 10.f; p.stagh = T[T_SH]; p.infl = T[T_INFL]; p.t_fill = p.t_k0 + 59 * T[T_PER];
    for (int i = 0, nw = 0, n1 = 0, n2 = 0; i < NCTA; i++) {
        const int grp = i >> 2;
        const bool f2 = grp % 3 == 2, both = grp == 8 || grp == 23, wo = !both, f1 = !f2 || both;
        p.role[i] = (wo ? 1 | nw / 20 << 3 | nw % 20 << 6 : 0) | (f1 ? 2 | n1 << 11 : 0) | (f2 ? 4 | n2 << 18 : 0);
        nw += wo; n1 += f1; n2 += f2;
    }
    TMaps tm;
    constexpr int R1 = FF * 2, R2 = D_MODEL * 2;
    for (int i = 0; i < 2; i++)
        make_map(encode, &tm.k + i, d_in[1 + i], {64, 96, 1, 1, NHEAD * SK / 32}, {128, TILE_BYTES, TILE_BYTES, TILE_BYTES}, {64, 96, 1, 1, 1}, CU_TENSOR_MAP_SWIZZLE_128B, T[T_PKV]);
    make_map(encode, &tm.wo, d_in[4], {D_MODEL, 2, 4, 2, NHEAD * DH / 16}, {R2, 4 * R2, 2 * R2, 16 * R2}, {32, 2, 4, 2, 8}, CU_TENSOR_MAP_SWIZZLE_64B, T[T_PWO]);
    make_map(encode, &tm.w1, d_in[6], {FF, 2, 4, 2, D_MODEL / 16}, {R1, 4 * R1, 2 * R1, 16 * R1}, {16, 2, 4, 2, 8}, CU_TENSOR_MAP_SWIZZLE_32B, T[T_PW13]);
    make_map(encode, &tm.w3, d_in[7], {FF, 2, 4, 2, D_MODEL / 16}, {R1, 4 * R1, 2 * R1, 16 * R1}, {16, 2, 4, 2, 8}, CU_TENSOR_MAP_SWIZZLE_32B, T[T_PW13]);
    make_map(encode, &tm.w2, d_in[8], {D_MODEL, 2, 4, 4, FF / 32}, {R2, 8 * R2, 2 * R2, 32 * R2}, {16, 2, 4, 4, 8}, CU_TENSOR_MAP_SWIZZLE_32B, T[T_PW2]);
    fused_decode_kernel<<<NCTA, NTHREADS, SM_TOTAL, cudaStreamPerThread>>>(p, tm);
}
```

```cpp
#include <cuda_runtime.h>
#include <cuda_bf16.h>
#include <cuda.h>
#include <stdint.h>
#include <initializer_list>

namespace {

constexpr int D_MODEL = 640;
constexpr int NHEAD = 32;
constexpr int DH = 192;
constexpr int SK = 32768;
constexpr int WIN = 4096;
constexpr int FF = 1536;

constexpr int NCTA = 128;
constexpr int NTHREADS = 256 + 64 + 192;
constexpr int TILE_BYTES = 32 * DH * 2;
constexpr int NSLOT = 16;
constexpr int NKT = 32;
constexpr int NQT = 5;
constexpr int QSLOT = NSLOT - NQT;
constexpr int NG = 6;
constexpr int NWP = 8, NP1 = 10, NF2 = 6;
constexpr int NITEM = NWP + NP1 + NF2;
constexpr int NF1 = 4, NA = 2, NB = 2;
constexpr int NTAIL = NWP + NF1 + NF2;

constexpr uint32_t sbase = 1024;
constexpr int SM_W1 = NWP * 8192, SM_W3 = SM_W1 + 20480, SM_W2 = SM_W3 + 20480;
constexpr int SM_P = NSLOT * TILE_BYTES;
constexpr int SM_Q = SM_P + 2048;
constexpr int SM_RED = SM_Q + 12288;
constexpr int SM_BC = SM_RED + 128 * 48;
constexpr int SM_ONE = SM_BC + 4096;
constexpr int SM_ST = SM_ONE + 64;
constexpr int SM_WT = SM_ST + 256;
constexpr int SM_RO = SM_WT + 512;
constexpr int SM_LN = SM_RO + 48 * 80;
constexpr int SM_MISC = SM_LN + 64;
constexpr int SM_LATE = SM_MISC + 32;
constexpr int SM_BAR = SM_LATE + 32;
constexpr int SM_TOTAL = SM_BAR + 512;
static_assert(SM_TOTAL <= 232448, "shared memory");

struct __align__(128) Scratch {
    uint2 qbuf[NCTA * 96];
    uint2 qall[NHEAD * 96];
    uint2 mbuf[NCTA * NHEAD];
    uint32_t ready[NCTA];
    uint32_t late[32];
    uint32_t epoch;
};
__device__ Scratch g_scratch;
constexpr int XA_ALIGN = 2 << 20;
constexpr uint32_t SENT = 0xffffffffu;
__device__ unsigned char g_xarea[XA_ALIGN + (9 << 20)];
__device__ __forceinline__ uint32_t xa_o(uint32_t kw, uint32_t j) { return (kw >> 4) * 16384 + (kw & 15) * 256 + j * 32; }
constexpr int NLATE = 4;
__device__ __forceinline__ uint32_t xa_p(uint32_t h, uint32_t q, uint32_t j) {
    const uint32_t k = ((NHEAD - 1 - h) * 4 + q) * 8 + j;
    return (1 << 20) + (2 * k + ((k ^ (k >> 3) ^ (k >> 4) ^ (k >> 6)) & 1)) * 4096;
}
__host__ __device__ constexpr uint32_t xa_h(uint32_t i) { return (1 << 18) + (i >> 2) * (3 << 16) + (i & 3) * (1 << 14); }
constexpr uint32_t XA_A = xa_h(NG);

constexpr uint32_t XA_PROBE = 1 << 13 | 1 << 19;

constexpr uint32_t SPIN_LIMIT = 1u << 22;

__device__ __forceinline__ uint32_t smem_u32(const void* p) { return (uint32_t)__cvta_generic_to_shared(p); }
__device__ __forceinline__ uint32_t now_ns() { uint64_t t; asm volatile("mov.u64 %0, %globaltimer;" : "=l"(t)); return (uint32_t)t; }
__device__ __forceinline__ void mbar_init(uint32_t bar, uint32_t cnt) {
    asm volatile("mbarrier.init.shared::cta.b64 [%0], %1;" ::"r"(bar), "r"(cnt) : "memory");
}
__device__ __forceinline__ void mbar_expect_tx(uint32_t bar, uint32_t bytes) {
    asm volatile("mbarrier.arrive.expect_tx.shared::cta.b64 _, [%0], %1;" ::"r"(bar), "r"(bytes) : "memory");
}
__device__ __forceinline__ void mbar_arrive(uint32_t bar) {
    asm volatile("mbarrier.arrive.shared::cta.b64 _, [%0];" ::"r"(bar) : "memory");
}
__device__ __forceinline__ void mbar_arrive8(uint32_t bar) {
    asm volatile("mbarrier.arrive.shared::cta.b64 _, [%0], 8;" ::"r"(bar) : "memory");
}
__device__ __forceinline__ bool mbar_test(uint32_t bar, uint32_t parity) {
    uint32_t ok;
    asm volatile("{\n.reg .pred p;\nmbarrier.test_wait.parity.shared::cta.b64 p, [%1], %2;\nselp.u32 %0, 1, 0, p;\n}"
                 : "=r"(ok) : "r"(bar), "r"(parity) : "memory");
    return ok;
}
__device__ __forceinline__ void mbar_wait(uint32_t bar, uint32_t parity) {
    asm volatile("{\n.reg .pred p;\nW_%=:\nmbarrier.try_wait.parity.shared::cta.b64 p, [%0], %1;\n@!p bra.uni W_%=;\n}" ::"r"(bar), "r"(parity) : "memory");
}
__device__ __forceinline__ void mbar_wait_after(uint32_t bar, uint32_t dump, float v) {
    uint32_t ok;
    asm volatile("{\n.reg .pred p;\nmbarrier.try_wait.parity.shared::cta.b64 p, [%1], 0;\nselp.u32 %0, 1, 0, p;\n}" : "=r"(ok) : "r"(bar) : "memory");
    asm volatile("st.volatile.shared.f32 [%0], %1;" ::"r"(dump), "f"(v) : "memory");
    if (__builtin_expect(!ok, 0)) mbar_wait(bar, 0);
}
__device__ __forceinline__ void tma_load_at(uint32_t when, uint32_t dst, const CUtensorMap* tm, int c0, int c4, uint32_t bar, uint64_t pol) {
    asm volatile("{\n.reg .pred p, e;\n.reg .b64 t;\n.reg .b32 lo, hi;\nelect.sync _|e, -1;\n"
                 "W_%=:\nmov.u64 t, %globaltimer;\nmov.b64 {lo, hi}, t;\nsub.u32 lo, lo, %7;\nsetp.lt.s32 p, lo, 0;\n@p bra.uni W_%=;\n"
                 "@e cp.async.bulk.tensor.5d.shared::cluster.global.mbarrier::complete_tx::bytes.L2::cache_hint [%0], [%1, {%3, %5, %5, %5, %4}], [%2], %6;\n}"
                 ::"r"(dst), "l"(reinterpret_cast<uint64_t>(tm)), "r"(bar), "r"(c0), "r"(c4), "r"(0), "l"(pol), "r"(when) : "memory");
}
__device__ __forceinline__ void pin(uint32_t& v) { asm volatile("shfl.sync.bfly.b32 %0, %0, 0, 31, -1;" : "+r"(v) :: "memory"); }
__device__ __forceinline__ void pin_u(uint32_t& v) { asm volatile("shfl.sync.idx.b32 %0, %0, 0, 31, -1;" : "+r"(v) :: "memory"); }
template <class T> __device__ __forceinline__ void pin(T*& v) {
    asm volatile("{\n.reg .b32 a, b;\nmov.b64 {a, b}, %0;\nshfl.sync.bfly.b32 a, a, 0, 31, -1;\nshfl.sync.bfly.b32 b, b, 0, 31, -1;\nmov.b64 %0, {a, b};\n}" : "+l"(v) :: "memory");
}
__device__ __forceinline__ void sts16(uint32_t a, uint32_t v) { asm volatile("st.shared.u16 [%0], %1;" ::"r"(a), "h"((unsigned short)v) : "memory"); }
__device__ __forceinline__ void sts32(uint32_t a, float v) { asm volatile("st.shared.f32 [%0], %1;" ::"r"(a), "f"(v) : "memory"); }
__device__ __forceinline__ void sts32(uint32_t a, uint32_t v) { asm volatile("st.shared.u32 [%0], %1;" ::"r"(a), "r"(v) : "memory"); }
__device__ __forceinline__ void sts64(uint32_t a, uint32_t x, uint32_t y) { asm volatile("st.shared.v2.u32 [%0], {%1, %2};" ::"r"(a), "r"(x), "r"(y) : "memory"); }
__device__ __forceinline__ void sts128(uint32_t a, const uint4& v) { asm volatile("st.shared.v4.u32 [%0], {%1, %2, %3, %4};" ::"r"(a), "r"(v.x), "r"(v.y), "r"(v.z), "r"(v.w) : "memory"); }
__device__ __forceinline__ void cons_sync() { asm volatile("bar.sync 1, 256;" ::: "memory"); }
template <int ID> __device__ __forceinline__ void fin_arrive() { asm volatile("bar.arrive %0, 288;" ::"n"(ID) : "memory"); }
template <int ID> __device__ __forceinline__ void fin_sync() { asm volatile("bar.sync %0, 288;" ::"n"(ID) : "memory"); }

__device__ __forceinline__ uint4 lds128(uint32_t a) {
    uint4 v;
    asm volatile("ld.shared.v4.u32 {%0,%1,%2,%3}, [%4];" : "=r"(v.x), "=r"(v.y), "=r"(v.z), "=r"(v.w) : "r"(a) : "memory");
    return v;
}
__device__ __forceinline__ uint4 lds128v(uint32_t a) {
    uint4 v;
    asm volatile("ld.volatile.shared.v4.u32 {%0,%1,%2,%3}, [%4];" : "=r"(v.x), "=r"(v.y), "=r"(v.z), "=r"(v.w) : "r"(a) : "memory");
    return v;
}
__device__ __forceinline__ float4 lds128f(uint32_t a) {
    float4 v;
    asm volatile("ld.shared.v4.f32 {%0,%1,%2,%3}, [%4];" : "=f"(v.x), "=f"(v.y), "=f"(v.z), "=f"(v.w) : "r"(a) : "memory");
    return v;
}
__device__ __forceinline__ uint2 lds64(uint32_t a) {
    uint2 v;
    asm volatile("ld.shared.v2.u32 {%0,%1}, [%2];" : "=r"(v.x), "=r"(v.y) : "r"(a) : "memory");
    return v;
}
__device__ __forceinline__ uint32_t lds32(uint32_t a) {
    uint32_t v;
    asm volatile("ld.shared.u32 %0, [%1];" : "=r"(v) : "r"(a) : "memory");
    return v;
}
__device__ __forceinline__ float sum8(uint32_t a) {
    const float4 x = lds128f(a), y = lds128f(a + 16);
    return ((x.x + x.y) + (x.z + x.w)) + ((y.x + y.y) + (y.z + y.w));
}
__device__ __forceinline__ void ldsm_x4(uint32_t* r, uint32_t a) {
    asm volatile("ldmatrix.sync.aligned.m8n8.x4.shared.b16 {%0,%1,%2,%3}, [%4];"
                 : "=r"(r[0]), "=r"(r[1]), "=r"(r[2]), "=r"(r[3]) : "r"(a) : "memory");
}
__device__ __forceinline__ void ldsm_x4_t(uint32_t* r, uint32_t a) {
    asm volatile("ldmatrix.sync.aligned.m8n8.x4.trans.shared.b16 {%0,%1,%2,%3}, [%4];"
                 : "=r"(r[0]), "=r"(r[1]), "=r"(r[2]), "=r"(r[3]) : "r"(a) : "memory");
}
template <int STRIDE>
__device__ __forceinline__ void ldsm_if(uint32_t* r0, uint32_t* r1, uint32_t a, uint32_t bar, uint32_t& got) {
        asm volatile("{\n.reg .pred p, q;\nsetp.eq.u32 q, %8, 0;\nmbarrier.test_wait.parity.shared::cta.b64 p, [%10], 0;\nand.pred p, p, q;\n"
                     "@p ldmatrix.sync.aligned.m8n8.x4.trans.shared.b16 {%0,%1,%2,%3}, [%9];\n"
                     "@p ldmatrix.sync.aligned.m8n8.x4.trans.shared.b16 {%4,%5,%6,%7}, [%9+%11];\n@p mov.u32 %8, 1;\n}"
                     : "+r"(r0[0]), "+r"(r0[1]), "+r"(r0[2]), "+r"(r0[3]), "+r"(r1[0]), "+r"(r1[1]), "+r"(r1[2]), "+r"(r1[3]), "+r"(got)
                     : "r"(a), "r"(bar), "n"(STRIDE) : "memory");
}
__device__ __forceinline__ void mma_bf16(float* c, uint32_t a0, uint32_t a1, uint32_t a2, uint32_t a3, uint32_t b0, uint32_t b1) {
    asm volatile("mma.sync.aligned.m16n8k16.row.col.f32.bf16.bf16.f32 {%0,%1,%2,%3}, {%4,%5,%6,%7}, {%8,%9}, {%0,%1,%2,%3};"
                 : "+f"(c[0]), "+f"(c[1]), "+f"(c[2]), "+f"(c[3]) : "r"(a0), "r"(a1), "r"(a2), "r"(a3), "r"(b0), "r"(b1));
}
__device__ __forceinline__ void mma_bf16(float* c, const uint32_t* a, uint32_t b0, uint32_t b1) { mma_bf16(c, a[0], a[1], a[2], a[3], b0, b1); }
__device__ __forceinline__ void zero4(float* c) { c[0] = c[1] = c[2] = c[3] = 0.f; }
__device__ __forceinline__ float bf_lo(uint32_t u) { return __uint_as_float(u << 16); }
__device__ __forceinline__ float bf_hi(uint32_t u) { return __uint_as_float(u & 0xffff0000u); }
__device__ __forceinline__ uint32_t pack_bf(float hi, float lo) { uint32_t r; asm("cvt.rn.bf16x2.f32 %0, %1, %2;" : "=r"(r) : "f"(hi), "f"(lo)); return r; }
__device__ __forceinline__ uint32_t add_bf2(uint32_t a, uint32_t b) { uint32_t r; asm("add.rn.bf16x2 %0, %1, %2;" : "=r"(r) : "r"(a), "r"(b)); return r; }
__device__ __forceinline__ float bfr(float x) { return __uint_as_float(pack_bf(x, 0.f)); }

__device__ __forceinline__ uint32_t in_word(float v) { return __float_as_uint(v); }
__device__ __forceinline__ void st1(void* p, uint32_t v) {
    asm volatile("st.relaxed.gpu.global.u32 [%0], %1;" ::"l"(p), "r"(v) : "memory");
}
__device__ __forceinline__ void st16(void* p, uint32_t v) {
    asm volatile("st.relaxed.gpu.global.u16 [%0], %1;" ::"l"(p), "h"((unsigned short)v) : "memory");
}
__device__ __forceinline__ void st2(void* p, uint32_t a, uint32_t b) {
    asm volatile("st.relaxed.gpu.global.v2.u32 [%0], {%1, %2};" ::"l"(p), "r"(a), "r"(b) : "memory");
}
__device__ __forceinline__ void st4(void* p, uint32_t a, uint32_t b, uint32_t c, uint32_t d) {
    asm volatile("st.relaxed.gpu.global.v4.u32 [%0], {%1, %2, %3, %4};" ::"l"(p), "r"(a), "r"(b), "r"(c), "r"(d) : "memory");
}
__device__ __forceinline__ uint32_t ld1(const void* p) {
    uint32_t v;
    asm volatile("ld.relaxed.gpu.global.u32 %0, [%1];" : "=r"(v) : "l"(p) : "memory");
    return v;
}
__device__ __forceinline__ uint2 ld2(const void* p) {
    uint2 v;
    asm volatile("ld.relaxed.gpu.global.v2.u32 {%0, %1}, [%2];" : "=r"(v.x), "=r"(v.y) : "l"(p) : "memory");
    return v;
}
__device__ __forceinline__ uint4 ld4(const void* p) {
    uint4 v;
    asm volatile("ld.relaxed.gpu.global.v4.u32 {%0, %1, %2, %3}, [%4];" : "=r"(v.x), "=r"(v.y), "=r"(v.z), "=r"(v.w) : "l"(p) : "memory");
    return v;
}
__device__ __forceinline__ void ld4p(const void* p, uint4& v, bool on) {
    asm volatile("{\n.reg .pred q;\nsetp.ne.u32 q, %5, 0;\n@q ld.relaxed.gpu.global.v4.u32 {%0, %1, %2, %3}, [%4];\n}"
                 : "+r"(v.x), "+r"(v.y), "+r"(v.z), "+r"(v.w) : "l"(p), "r"((uint32_t)on) : "memory");
}
__device__ __forceinline__ bool ok8(const uint4& v) {
    const uint32_t m = __vimax3_u16x2(__vimax3_u16x2(v.x, v.y, v.z), v.w, v.w);
    return __vimax3_u16x2(m, m << 16, m >> 16) != SENT;
}
__device__ __forceinline__ uint32_t max4(const uint4& v) { return max(max(v.x, v.y), max(v.z, v.w)); }
__device__ __forceinline__ void pkt_ld2(const uint4* p, uint64_t& a, uint64_t& b) {
    asm volatile("ld.relaxed.gpu.global.v2.b64 {%0, %1}, [%2];" : "=l"(a), "=l"(b) : "l"(p) : "memory");
}
__device__ __forceinline__ bool tag_ok(uint64_t v, uint32_t tag) { return (uint32_t)(v >> 32) == tag; }
__device__ __forceinline__ float val_of(uint64_t v) { return __uint_as_float((uint32_t)v); }

__device__ __forceinline__ float warp_sum(float v) {
#pragma unroll
    for (int o = 16; o > 0; o >>= 1) v += __shfl_xor_sync(0xffffffffu, v, o);
    return v;
}
__device__ __forceinline__ float warp_max(float v) {
#pragma unroll
    for (int o = 16; o > 0; o >>= 1) v = fmaxf(v, __shfl_xor_sync(0xffffffffu, v, o));
    return v;
}
__device__ __forceinline__ float sqrt_fast(float x) { float r; asm("sqrt.approx.ftz.f32 %0, %1;" : "=f"(r) : "f"(x)); return r; }
__device__ __forceinline__ float rcp_fast(float x) { float r; asm("rcp.approx.ftz.f32 %0, %1;" : "=f"(r) : "f"(x)); return r; }
__device__ __forceinline__ float ex2(float x) { float r; asm("ex2.approx.ftz.f32 %0, %1;" : "=f"(r) : "f"(x)); return r; }
constexpr float L2E = 1.4426950408889634f;
__device__ __forceinline__ void ln_finish(float s1, float s2, float& mean_b, float& inv_den) {
    const float mean = s1 * (1.0f / D_MODEL);
    const float var = fmaxf(fmaf(-mean, mean, s2 * (1.0f / D_MODEL)), 0.f);
    mean_b = bfr(mean);
    inv_den = rcp_fast(bfr(sqrt_fast(bfr(bfr(var) + 1e-5f))));
}
__device__ __forceinline__ uint32_t ln_apply2(uint32_t u, float mean_b, float inv_den) {
    const uint32_t d = pack_bf(bf_hi(u) - mean_b, bf_lo(u) - mean_b);
    return pack_bf(bf_hi(d) * inv_den, bf_lo(d) * inv_den);
}
__device__ __forceinline__ void ln_acc(uint32_t u, float& s1, float& s2) {
    const float a = bf_lo(u), b = bf_hi(u);
    s1 += a + b;
    s2 = fmaf(a, a, fmaf(b, b, s2));
}
__device__ __forceinline__ float silu_b(float g) { return bfr(__fdividef(g, 1.0f + ex2(-g * L2E))); }

struct KParams {
    const __nv_bfloat16* wq;
    const __nv_bfloat16* x;
    __nv_bfloat16* out;
    Scratch* sc;
    unsigned char* xa;
    int t_k0, per, stag, stagh;
    int target, infl;
    float dz, gain, tg0, tgain;
    int t_q, t_q2, t_stat, t_fill;
    int rdelay, rlast;
    uint32_t item[32];
    uint32_t role[NCTA];
};
struct TMaps { CUtensorMap k, v, wo, w1, w3, w2; };

__global__ void __launch_bounds__(NTHREADS, 1)
fused_decode_kernel(const __grid_constant__ KParams p, const __grid_constant__ TMaps tm) {
    extern __shared__ __align__(1024) unsigned char smem[];
    const int tid = threadIdx.x;
    const int b = blockIdx.x;
    const int head = b >> 2, sp = b & 3;
    {
        const char* a = reinterpret_cast<const char*>(p.wq) + (uint32_t)((sp * 160 + (tid >> 2)) * (NHEAD * DH * 2) + head * (DH * 2) + (tid & 3) * 128);
        if (tid < 320) asm volatile("prefetch.global.L2 [%0];" ::"l"(a) : "memory");
    }
    if (tid < 256) {
        const uint32_t r = tid >> 3, ch = tid & 7;
        const char* src = reinterpret_cast<const char*>(p.wq) + ((sp * 160 + r) * (NHEAD * DH * 2) + head * (DH * 2) + ch * 16);
#pragma unroll
        for (int i = 0; i < NQT; i++) {
#pragma unroll
            for (int j = 0; j < 3; j++)
                asm volatile("cp.async.cg.shared.global [%0], [%1], 16;"
                             ::"r"(sbase + (QSLOT + i) * TILE_BYTES + (3 * r + j) * 128 + ((ch ^ ((3 * r + j) & 7)) << 4)),
                               "l"(src + (size_t)i * 32 * (NHEAD * DH * 2) + j * 128) : "memory");
        }
    }
    const uint32_t t0 = now_ns();
    const int warp = __shfl_sync(0xffffffffu, tid >> 5, 0), lane = tid & 31;
    const uint32_t role = p.role[b];
    const int kg = role >> 3 & 7, ng = role >> 6 & 31;
    const int u1 = role >> 11 & 127, u2 = role >> 18;
    const bool has_wo = role & 1, has_f1 = role & 2, has_f2 = role & 4;
    constexpr uint32_t bar_full = sbase + SM_BAR;
    constexpr uint32_t bar_empty = sbase + SM_BAR + 128;
    constexpr uint32_t bar_tail = sbase + SM_BAR + 256;
    constexpr uint32_t bar_rdy = bar_tail + 8 * NTAIL;
    constexpr uint32_t bar_side = bar_rdy + 8;
    constexpr uint32_t bar_wt = bar_side + 8;
    constexpr uint32_t bar_go = bar_side + 16;
    constexpr uint32_t bar_stat = bar_side + 24;
    constexpr uint32_t bar_up = bar_side + 32;

    if (warp == 8) {
        if (smem_u32(smem) != sbase) __trap();
        uint64_t pol;
        asm volatile("createpolicy.fractional.L2::evict_first.b64 %0, 1.0;" : "=l"(pol));
        sts32(sbase + SM_LATE + (lane & 7) * 4, 0u);
        if (lane == 0) {
#pragma unroll
            for (int i = 0; i < 32 + NTAIL + 6; i++)
                mbar_init(bar_full + 8 * i, (i >= 16 && i < 32) || i > 35 + NTAIL ? 8 : i == 32 + NWP ? NA : i == 33 + NWP ? 5 - NA : i == 34 + NWP ? NB : i == 35 + NWP ? 5 - NB : 1);
#pragma unroll
            for (int i = 0; i < 6; i++) asm volatile("prefetch.tensormap [%0];" ::"l"(reinterpret_cast<uint64_t>(&tm.k + i)) : "memory");
            asm volatile("fence.mbarrier_init.release.cluster;" ::: "memory");
        }
        __syncwarp();
        asm volatile("bar.arrive 2, 512;" ::: "memory");
        const uint32_t tu = __shfl_sync(0xffffffffu, t0, 0);
        if (b == 0 && lane < 8) st1(p.sc->late + lane, lane ? 0 : (tu & 0xffffffu) | 1u << 24);
        const int seg = (lane >= NWP) + (lane >= NWP + NP1), i = lane - (seg == 0 ? 0 : seg == 1 ? NWP : NWP + NP1);
        const bool todo = lane < NITEM && (role >> seg & 1);
        const uint32_t len = seg == 1 ? 4096 : 8192, dst = sbase + (seg == 0 ? 0 : seg == 1 ? SM_W1 : SM_W2) + i * len;
        const int w3 = seg == 1 && i >= 5;
        const uint32_t mi = seg == 2 ? 3 : seg + w3;
        const int c0 = seg == 0 ? ng * 32 : seg == 1 ? u1 * 16 : u2 * 16;
        const int c4 = (seg == 0 ? kg * 64 : w3 * -40) + i * 8;
        const uint32_t bar = bar_tail + 8 * (seg == 0 ? i : seg == 1 ? NWP + (i >= NA) + w3 + (i >= 5 + NB) : NWP + NF1 + i);
        const int tile0 = (SK - WIN) / 32 + b;
        uint32_t tk = tu + p.t_k0 + sp * p.stag + head * p.stagh, tw = tk, acc = 0;
        int slip = 0, base = 0, w = 0, d0 = 0;
        float a2 = 0.f, drift = 0.f;
#pragma unroll 1
        for (int n = 0; n < 2 * NKT; n++) {
            const int slot = n & (NSLOT - 1);
            mbar_wait(bar_empty + 8 * slot, (((n + NQT) >> 4) & 1) ^ 1);
            if (lane == 0) mbar_expect_tx(bar_full + 8 * slot, TILE_BYTES);
            bool more;
            do {
                const uint32_t t = now_ns();
                if (__all_sync(0xffffffffu, mbar_test(bar_full + 8 * (w & (NSLOT - 1)), (w >> 4) & 1))) {
                    acc += t - tw;
                    tw += p.per;
                    w++;
                    if ((w & 7) == 0) {
                        if (lane == 0) asm volatile("red.relaxed.gpu.global.add.u32 [%0], %1;" ::"l"(p.sc->late + (w >> 3)), "r"((1u << 24) + min(max(((int)acc >> 3) + d0, 0), 65535)) : "memory");
                        acc = 0;
                    }
                }
                more = __any_sync(0xffffffffu, (int)(t - tk) < slip - 60) || w <= n - p.infl;
            } while (more);
            tma_load_at(tk + slip, sbase + slot * TILE_BYTES, &tm.k + (n >> 5), 0, tile0 + (n & (NKT - 1)) * (SK / 32), bar_full + 8 * slot, pol);
            tk += p.per;
            if ((n & 7) == 5 && lane < 2)
                asm volatile("cp.async.cg.shared.global [%0], [%1], 16;" ::"r"(sbase + SM_LATE + lane * 16), "l"(p.sc->late + lane * 4) : "memory");
            const uint32_t org = lds32(sbase + SM_LATE);
            if (org) d0 = (int)((tu - org) << 8) >> 8;
            int k = n >> 3;
            uint32_t rep = lds32(sbase + SM_LATE + k * 4);
            const uint32_t rep0 = lds32(sbase + SM_LATE + max(k - 1, 0) * 4);
            if (!(rep >> 30)) { rep = rep0; k--; }
            if (rep >> 30) {
                const float a = (float)(rep & 0xffffffu) * rcp_fast((float)(rep >> 24));
                if (k <= 2) a2 = a; else drift = fminf(fmaxf((a - a2) * rcp_fast((float)(8 * k - 16)), -4.f), 6.f);
                base = max((int)a - p.target - d0, -900);
                slip = base + (int)(fmaxf(drift - p.dz, 0.f) * p.gain * (float)(n + 5 - 8 * k));
            }
        }
        const uint32_t tn = tu + base + p.item[lane] + (int)(drift * fmaf(p.tgain, (float)(int)(p.item[lane] - p.item[0]), p.tg0));
        if (todo) mbar_expect_tx(bar, len);
        const uint32_t c04 = c0 | c4 << 16, db = dst | (bar - bar_tail) << 18 | mi << 28;
#pragma unroll 1
        for (uint32_t left = __ballot_sync(0xffffffffu, todo); left; left &= left - 1) {
            const int k = __ffs(left) - 1;
            const uint32_t kc = __shfl_sync(0xffffffffu, c04, k), kd = __shfl_sync(0xffffffffu, db, k), kt = __shfl_sync(0xffffffffu, tn, k);
            mbar_wait(bar_empty + 8 * (k < NWP ? 5 : 12), k < NWP);
            tma_load_at(kt, kd & 0x3ffff, &tm.wo + (kd >> 28), kc & 0xffff, kc >> 16, bar_tail + (kd >> 18 & 0x3ff), pol);
        }
    } else if (warp >= 10) {
        asm volatile("bar.sync 2, 512;" ::: "memory");
        const uint32_t t4 = (lds32(sbase + SM_MISC) & 7) + 1, id = tid - 320, sg = id / 12;
        while (!mbar_test(bar_wt, 0)) __nanosleep(500);
        const float4 wa = lds128f(sbase + SM_WT + sg * 32), wb = lds128f(sbase + SM_WT + sg * 32 + 16);
        const float wt[8] = {wa.x, wa.y, wa.z, wa.w, wb.x, wb.y, wb.z, wb.w};
        uint32_t sd = sp & 1;
        if (head >= NHEAD - NLATE) {
            while (!mbar_test(bar_side, 0)) __nanosleep(200);
            sd = lds32(sbase + SM_MISC + 4);
        }
        const uint32_t o0 = (xa_p(head, sp, 0) ^ sd << 12) + id * 16;
        const unsigned char* a0 = p.xa + o0;
        const unsigned char* a1 = p.xa + (o0 ^ 4096);
        uint32_t dst = sbase + SM_RO + (id - sg * 12) * 320 + sg * 4;
        pin(a0); pin(a1); pin(dst);
        mbar_wait(bar_go, 0);
        uint4 e[8];
#pragma unroll
        for (int j = 0; j < 8; j++) e[j] = ld4((j & 1 ? a1 : a0) + j * 8192);
        uint32_t k = 0;
        bool miss;
#pragma unroll 1
        do {
            miss = false;
#pragma unroll
            for (int j = 0; j < 8; j++) {
                const bool m = (((e[j].x ^ t4) | (e[j].y ^ t4) | (e[j].z ^ t4) | (e[j].w ^ t4)) & 15) != 0;
                ld4p((j & 1 ? a1 : a0) + j * 8192, e[j], m);
                miss = miss || m;
            }
            if (++k > SPIN_LIMIT) __trap();
        } while (__any_sync(0xffffffffu, miss));
        float o[4] = {0.f, 0.f, 0.f, 0.f};
#pragma unroll
        for (int j = 0; j < 8; j++) {
            o[0] = fmaf(wt[j], __uint_as_float(e[j].x ^ t4), o[0]); o[1] = fmaf(wt[j], __uint_as_float(e[j].y ^ t4), o[1]);
            o[2] = fmaf(wt[j], __uint_as_float(e[j].z ^ t4), o[2]); o[3] = fmaf(wt[j], __uint_as_float(e[j].w ^ t4), o[3]);
        }
#pragma unroll
        for (int i = 0; i < 4; i++) sts32(dst + i * 80, o[i]);
        asm volatile("bar.arrive 5, 224;" ::: "memory");
    } else if (warp == 9) {
        const uint32_t tag = ld1(&p.sc->epoch) + 1;
        const uint32_t aoff = XA_A + (u1 >> 1 & 7) * 384 + (u1 >> 4) * 64 + (u1 & 1) * 32, hoff = xa_h(kg) + (ng & 3) * 1024 + (ng >> 2) * 64;
        sts32(sbase + SM_ONE + (lane & 15) * 4, 0x3f803f80u);
        const uint32_t l24 = min(lane, 23), od = head * 12 + sp * 3 + (l24 >> 3);
        const uint32_t ooff = xa_o((od >> 6) * 8 + (od & 7), od >> 3 & 7);
        unsigned char* slot[3] = {p.xa + (ooff + (l24 & 7) * 4), p.xa + (ooff + (l24 & 7) * 4 + 4096),
                                  p.xa + (lane < 16 ? (has_wo ? hoff + (lane >> 3) * 4096 + (lane >> 2 & 1) * 512 + (lane & 3) * 16 : ooff) : has_f1 ? aoff + (lane >> 1 & 1) * 4096 + (lane & 1) * 16 : ooff)};
#pragma unroll
        for (int i = 0; i < 2; i++) st4(p.sc->qbuf + b * 96 + i * 32 + lane * 2, 0, 0, 0, 0);
        uint2* qdst = p.sc->qall + ((head & 7) * 4 + (head >> 3)) * 96 + sp * 24 + l24;
        st2(qdst, 0, 0);
        sts32(sbase + SM_MISC, tag);
        asm volatile("bar.sync 2, 512;" ::: "memory");
        uint32_t n = 0;
        {
            const uint32_t t4 = (tag & 7) + 1;
            uint2 e[4];
            uint32_t bad;
#pragma unroll 1
            do {
                do __nanosleep(100); while ((int)(now_ns() - (t0 + p.t_q)) < 0);
                bad = 0;
#pragma unroll
                for (int i = 0; i < 4; i++) e[i] = ld2(p.sc->qbuf + (head * 4 + i) * 96 + l24 * 4 + sp);
#pragma unroll
                for (int i = 0; i < 4; i++) { e[i].x ^= t4; e[i].y ^= t4; bad |= e[i].x | e[i].y; }
                if (++n > SPIN_LIMIT) __trap();
            } while (__any_sync(0xffffffffu, bad & 15));
#define S_(c) ((__uint_as_float(e[0].c) + __uint_as_float(e[1].c)) + (__uint_as_float(e[2].c) + __uint_as_float(e[3].c)))
            asm volatile("st.relaxed.gpu.global.b64 [%0], %1;" ::"l"(qdst), "l"((uint64_t)tag << 32 | pack_bf(S_(y), S_(x))) : "memory");
#undef S_
        }
        {
            while (!mbar_test(bar_stat, 0)) __nanosleep(200);
            const uint2 st = lds64(sbase + SM_ST + lane * 8);
            asm volatile("st.relaxed.gpu.global.b64 [%0], %1;" ::"l"(p.sc->mbuf + b * NHEAD + lane), "l"((uint64_t)st.y << 32 | st.x) : "memory");
            const uint32_t t1 = now_ns() + p.t_stat, t16 = (tag & 0x7fff) + 1;
            uint64_t e[4];
            do {
                do __nanosleep(200); while ((int)(now_ns() - t1) < 0);
#pragma unroll
                for (int i = 0; i < 4; i++) asm volatile("ld.relaxed.gpu.global.b64 %0, [%1];" : "=l"(e[i]) : "l"(p.sc->mbuf + (lane + 32 * i) * NHEAD + head) : "memory");
#pragma unroll
                for (int i = 0; i < 4; i++) e[i] ^= t16;
                if (++n > SPIN_LIMIT) __trap();
            } while (__any_sync(0xffffffffu, (e[0] | e[1] | e[2] | e[3]) & 0xffff));
            const float M = warp_max(fmaxf(fmaxf(val_of(e[0]), val_of(e[1])), fmaxf(val_of(e[2]), val_of(e[3]))));
            float x[4], L = 0.f;
#pragma unroll
            for (int i = 0; i < 4; i++) { x[i] = ex2((val_of(e[i]) - M) * L2E); L = fmaf(x[i], val_of(e[i] >> 32), L); }
            L = rcp_fast(warp_sum(L));
#pragma unroll
            for (int i = 0; i < 4; i++) sts32(sbase + SM_WT + (lane & 15) * 32 + (lane >> 4) * 4 + i * 8, x[i] * L);
            __syncwarp();
            if (lane == 0) mbar_arrive(bar_wt);
        }
        unsigned char* pr = p.xa + (xa_h(b & 7) + XA_PROBE + (b >> 3) * 128 + lane * 4);
        st1(pr, SENT); st1(pr + 4096, SENT);
        int vote = 0;
#pragma unroll 1
        for (int r = 0; r < 9 && (!vote || (int)(now_ns() - (t0 + p.t_fill)) < -1000); r++) {
            __nanosleep(100);
            uint32_t d;
            asm volatile("{\n.reg .pred p, q;\n.reg .b32 a, b, c0, c1;\nmov.b32 c0, 0;\nmov.b32 c1, 0;\n"
                         "atom.relaxed.gpu.global.exch.b32 a, [%1], -1;\natom.relaxed.gpu.global.exch.b32 b, [%2], -1;\n"
                         "setp.eq.u32 p, a, -1;\n@p mov.u32 c0, %%clock;\nsetp.eq.u32 q, b, -1;\n@q mov.u32 c1, %%clock;\nsub.u32 %0, c1, c0;\n}"
                         : "=r"(d) : "l"(pr + (r & 1) * 4096), "l"(pr + (~r & 1) * 4096) : "memory");
            vote += (d > 90) == (r & 1) ? 1 : -1;
        }
        const uint32_t side = __shfl_sync(0xffffffffu, vote, 0) > 0;
        if (lane == 0) { sts32(sbase + SM_MISC + 4, side); mbar_arrive(bar_side); }
        while ((int)(now_ns() - (t0 + p.t_fill)) < 0) __nanosleep(200);
        st1(slot[0], SENT); st1(slot[1], SENT); st4(slot[2], SENT, SENT, SENT, SENT);
        uint32_t ack = SENT;
#pragma unroll
        for (int i = 0; i < 3; i++) { uint32_t v; asm volatile("atom.relaxed.gpu.global.exch.b32 %0, [%1], -1;" : "=r"(v) : "l"(slot[i]) : "memory"); ack &= v; }
        if (__any_sync(0xffffffffu, ack != SENT)) __trap();
        if (lane == 0) st1(p.sc->ready + b, tag);
        const uint32_t t2 = now_ns() + 1500;
        while (true) {
            do __nanosleep(200); while ((int)(now_ns() - t2) < 0);
            const uint4 e = ld4(p.sc->ready + lane * 4);
            if (__all_sync(0xffffffffu, e.x == tag && e.y == tag && e.z == tag && e.w == tag)) break;
            if (++n > SPIN_LIMIT) __trap();
        }
        if (lane == 0) {
            mbar_arrive(bar_rdy);
            if (b == 0) p.sc->epoch = tag;
        }
        unsigned char* hdst = p.xa + (hoff + (side ^ 1) * 4096 + (lane >> 4) * 512 + (lane & 15) * 4);
        unsigned char* hdst2 = p.xa + (hoff + side * 4096 + (lane >> 4) * 512 + (lane & 15) * 4);
        unsigned char* adst = p.xa + (aoff + (lane >> 4) * 4096 + (lane & 15) * 2);
        __nv_bfloat16* odst = p.out + u2 * 16 + (lane & 15);
        uint32_t r0 = sbase + SM_RED + lane * 48, r1 = sbase + SM_RED + (lane & 15) * 48;
        uint32_t res;
        asm volatile("ld.global.nc.u16 %0, [%1];" : "=r"(res) : "l"(p.x + u2 * 16 + (lane & 15)));
        pin(hdst); pin(hdst2); pin(adst); pin(odst); pin(r0); pin(r1);
        {
            uint32_t ro = sbase + SM_RO + l24 * 160;
            pin(ro);
            asm volatile("bar.sync 5, 224;" ::: "memory");
            const uint32_t v = pack_bf(sum8(ro + 80) + sum8(ro + 112), sum8(ro) + sum8(ro + 32));
            st1(slot[0], v); st1(slot[1], v);
        }
        if (has_wo) {
            fin_sync<3>();
            const uint32_t v = in_word(sum8(r0));
            st1(hdst, v); st1(hdst2, v);
        }
        if (has_f1) {
            fin_sync<4>();
            float mean_b, inv_den;
            ln_finish(sum8(sbase + SM_LN), sum8(sbase + SM_LN + 32), mean_b, inv_den);
            const float gr = fmaf(-mean_b, sum8(r1 + 48 * 48), sum8(r1 + 32 * 48)) * inv_den;
            mbar_wait_after(bar_up, r0, gr);
            const float gs = bfr(gr);
            const float up = bfr(fmaf(-mean_b, sum8(r1 + 80 * 48), sum8(r1 + 64 * 48)) * inv_den);
            st16(adst, pack_bf(0.f, silu_b(gs) * up));
            if (b == 0 && lane < 8) st1(p.sc->late + lane, 0);
        }
        if (has_f2) {
            mbar_wait(bar_tail + 8 * (NWP + NF1 + 3), 0);
            const unsigned char* hsrc = p.xa + ((lane >> 4) * (1 << 14) + side * 4096 + (u2 & 7) * 512 + (u2 >> 3) * 64 + (lane & 15) * 4);
            uint32_t e[3];
            do {
#pragma unroll
                for (int i = 0; i < 3; i++) e[i] = ld1(hsrc + xa_h(2 * i));
                if (++n > SPIN_LIMIT) __trap();
            } while (__any_sync(0xffffffffu, max(max(e[0], e[1]), e[2]) == SENT));
            float f[3];
#pragma unroll
            for (int i = 0; i < 3; i++) f[i] = __uint_as_float(e[i]) + __uint_as_float(__shfl_xor_sync(0xffffffffu, e[i], 16));
            res = add_bf2(res, pack_bf(0.f, (f[0] + f[1]) + f[2]));
            pin(res);
            fin_sync<6>();
            asm volatile("st.global.u16 [%0], %1;" ::"l"(odst), "h"((unsigned short)add_bf2(res, pack_bf(0.f, sum8(r1 + 96 * 48)))) : "memory");
        }
    } else {
        const int g = lane >> 2, t = lane & 3;
        uint2 xres;
        {
            uint32_t xr;
            uint2 xu[5];
            const char* xb = reinterpret_cast<const char*>(p.x);
            asm volatile("ld.global.nc.u16 %0, [%1];" : "=r"(xr) : "l"(xb + (sp * 160 + min(tid, 159)) * 2));
#pragma unroll
            for (int i = 0; i < 5; i++) asm volatile("ld.global.nc.v2.u32 {%0, %1}, [%2];" : "=r"(xu[i].x), "=r"(xu[i].y) : "l"(xb + i * 256 + lane * 8));
            asm volatile("ld.global.nc.v2.u32 {%0, %1}, [%2];" : "=r"(xres.x), "=r"(xres.y) : "l"(xb + min(g, 4) * 256 + warp * 32 + t * 8));
            if (lane >= 20) xres.x = xres.y = 0;
            float s1 = 0.f, s2 = 0.f, mean_b, inv_den;
#pragma unroll
            for (int i = 0; i < 5; i++) { ln_acc(xu[i].x, s1, s2); ln_acc(xu[i].y, s1, s2); }
            ln_finish(warp_sum(s1), warp_sum(s2), mean_b, inv_den);
            sts16(sbase + SM_P + warp * 64 + ((lane >> 1 & 3) * 8 + (lane >> 3) * 2 + (lane & 1)) * 2, ln_apply2(xr, mean_b, inv_den));
            asm volatile("cp.async.wait_all;" ::: "memory");
            asm volatile("bar.sync 2, 512;" ::: "memory");
        }
        uint32_t va[3];
#pragma unroll
        for (int i = 0; i < 3; i++) {
            const int cc = 3 * warp + i, row = 3 * lane + (cc >> 3);
            va[i] = sbase + row * 128 + (((cc ^ row) & 7) << 4);
        }
        const uint32_t tag = lds32(sbase + SM_MISC);
        const int gi = g >= 3 ? g - 3 : g;
        const uint32_t t4 = (tag & 7) + 1;
        auto pdst = [&](int n) {
            return p.xa + ((xa_p(n, warp >> 1, b >> 4) ^ (n >= NHEAD - NLATE ? g >= 3 : warp >> 1 & 1) << 12) + (b & 15) * 192 + (warp & 1) * 96 + gi * 32 + t * 8);
        };

#pragma unroll 1
        for (int ph = 0; ph < 2; ph++) {
            if (ph == 1) {
                uint32_t ka[3];
#pragma unroll
                for (int j = 0; j < 3; j++) {
                    const int row = 3 * (lane & 15) + j;
                    ka[j] = sbase + row * 128 + ((((lane >> 4) ^ row) & 7) << 4) + warp * TILE_BYTES;
                }
                const uint32_t t16 = (tag & 0x7fff) + 1;
#pragma unroll 1
                for (int it = 0; it < 4; it++) {
                    uint4 qf[6];
#pragma unroll
                    for (int i = 0; i < 6; i++) qf[i] = lds128(sbase + SM_Q + warp * 1536 + it * 384 + t * 96 + i * 16);
                    const int slot = (it & 1) * 8 + warp;
                    const uint32_t so = (it & 1) * 8 * TILE_BYTES;
                    float c[2][2][4];
                    zero4(c[0][0]); zero4(c[0][1]); zero4(c[1][0]); zero4(c[1][1]);
                    mbar_wait(bar_full + 8 * slot, it >> 1);
#pragma unroll
                    for (int ks = 0; ks < 12; ks++) {
                        const uint32_t a = (ka[ks >> 2] + so) ^ ((ks & 3) << 5);
                        uint32_t f0[4], f1[4];
                        ldsm_x4(f0, a); ldsm_x4(f1, a + 16 * DH * 2);
                        const uint32_t b0 = ks & 1 ? qf[ks >> 1].z : qf[ks >> 1].x, b1 = ks & 1 ? qf[ks >> 1].w : qf[ks >> 1].y;
                        mma_bf16(c[0][ks & 1], f0, b0, b1); mma_bf16(c[1][ks & 1], f1, b0, b1);
                    }
                    if (lane == 0) mbar_arrive8(bar_empty + 8 * slot);
                    const float v = t & 2 ? (t & 1 ? c[1][0][2] + c[1][1][2] : c[1][0][0] + c[1][1][0]) : (t & 1 ? c[0][0][2] + c[0][1][2] : c[0][0][0] + c[0][1][0]);
                    const float sc = bfr(bfr(v) * 0.07216878364870322f), m = warp_max(sc), e = ex2((sc - m) * L2E), l = warp_sum(e);
                    sts16(sbase + SM_P + (it * 8 + warp) * 64 + ((g >> 1) * 8 + t * 2 + (g & 1)) * 2, pack_bf(0.f, e));
                    sts64(sbase + SM_ST + (it * 8 + warp) * 8, (__float_as_uint(m) & 0xffff0000u) | t16, __float_as_uint(l));
                }
                if (lane == 0) mbar_arrive(bar_stat);
                cons_sync();
            }
            float acc[3][4];
#pragma unroll
            for (int i = 0; i < 3; i++) zero4(acc[i]);
            const int nt = ph ? NKT : NQT, nr = min(head + (head >= NHEAD - NLATE ? p.rlast : p.rdelay), NKT - 1);
            uint32_t v0, v1;
#pragma unroll 1
            for (int n = 0; n < nt; n++) {
                const int slot = ph ? (n & (NSLOT - 1)) : QSLOT + n;
                const uint4 w = lds128(sbase + SM_P + n * 64 + t * 16);
                unsigned char* dst = pdst(n);
                if (ph) mbar_wait(bar_full + 8 * slot, (n >> 4) & 1);
                uint32_t f[3][4];
#pragma unroll
                for (int i = 0; i < 3; i++) ldsm_x4_t(f[i], va[i] + slot * TILE_BYTES);
#pragma unroll
                for (int i = 0; i < 3; i++) mma_bf16(acc[i], w.x, w.x, w.y, w.y, f[i][0], f[i][1]);
#pragma unroll
                for (int i = 0; i < 3; i++) mma_bf16(acc[i], w.z, w.z, w.w, w.w, f[i][2], f[i][3]);
                if (lane == 0) mbar_arrive(bar_empty + 8 * slot);
                v0 = (__float_as_uint(gi == 0 ? acc[0][0] : gi == 1 ? acc[1][0] : acc[2][0]) & ~15u) | t4;
                v1 = (__float_as_uint(gi == 0 ? acc[0][1] : gi == 1 ? acc[1][1] : acc[2][1]) & ~15u) | t4;
                if (!ph) continue;
                if (g < (n >= NHEAD - NLATE ? 6 : 3)) st2(dst, v0, v1);
#pragma unroll
                for (int i = 0; i < 3; i++) zero4(acc[i]);
                if (n >= 22 && n < 22 + NLATE && g < 6) st2(pdst(n + NHEAD - NLATE - 22), 0, 0);
                if (n == nr && tid == 0) mbar_arrive(bar_go);
            }
            if (ph == 1) break;
            if (g < 3) st2(p.sc->qbuf + b * 96 + warp * 12 + lane, v0, v1);
            {
                uint64_t e[6][2];
                uint32_t n = 0;
                bool ok;
#pragma unroll 1
                do {
                    do __nanosleep(100); while ((int)(now_ns() - (t0 + p.t_q2)) < 0);
                    ok = true;
#pragma unroll
                    for (int i = 0; i < 6; i++) pkt_ld2(reinterpret_cast<const uint4*>(p.sc->qall) + warp * 192 + i * 32 + lane, e[i][0], e[i][1]);
#pragma unroll
                    for (int i = 0; i < 6; i++) ok = ok && tag_ok(e[i][0], tag) && tag_ok(e[i][1], tag);
                    if (++n > SPIN_LIMIT) __trap();
                } while (!__all_sync(0xffffffffu, ok));
#pragma unroll
                for (int i = 0; i < 6; i++) sts64(sbase + SM_Q + warp * 1536 + i * 256 + lane * 8, (uint32_t)e[i][0], (uint32_t)e[i][1]);
            }
            cons_sync();
        }
        mbar_wait(bar_rdy, 0);
        const uint32_t side = lds32(sbase + SM_MISC + 4) * 4096;
        const unsigned char* osrc = p.xa + (xa_o(kg * 8 + warp, 0) + side + lane * 8);
        const int r16 = (lane & 7) + ((lane >> 4) << 3), mi = lane >> 3 & 1;
        const uint32_t f32 = sbase + r16 * 32 + ((mi ^ (lane >> 2 & 1)) << 4);
        uint32_t rdst = sbase + SM_RED + (t * 8 + g) * 48 + warp * 4;
        uint32_t bl = sbase + SM_BC + warp * 512 + t * 80, bs = bl + g * 8;
        uint32_t hl = g < 4 ? bl : sbase + SM_ONE;
        uint32_t w1a = f32 + SM_W1 + warp * 512, w2a = f32 + SM_W2 + warp * 1024;
        uint32_t lnd = lane < 2 ? sbase + SM_LN + lane * 32 + warp * 4 : sbase + SM_BC + warp * 512 + 384 + lane * 4;
        const unsigned char* hs = p.xa + (side + warp * 512 + lane * 16);
        const unsigned char* as = p.xa + (XA_A + side + warp * 384 + min(lane, 23) * 16);
        uint32_t al = sbase + SM_BC + warp * 512 + t * 16, at = sbase + SM_BC + warp * 512 + lane * 16;
        uint32_t fl = role, ln = lane;
        pin_u(fl); pin(ln);
        const bool f1 = fl & 2, f2 = fl & 4, odd = ln & 1, first = ln == 0;
        constexpr uint32_t b2 = bar_tail + 8 * (NWP + NF1);
        pin(rdst); pin(bs); pin(hl); pin(w1a); pin(w2a); pin(lnd); pin(hs); pin(as); pin(al); pin(at);
#define F_(i, c) __uint_as_float(e[i].c)
        if (has_wo) {
            uint4 e[4];
            uint32_t n = 0;
            uint2 o;
            const uint32_t wa = sbase + (warp * 16 + r16) * 64 + ((mi ^ (r16 >> 1 & 3)) << 4), wb = wa ^ 32;
            float c0[4], c1[4];
            zero4(c0); zero4(c1);
            mbar_wait(bar_tail + 8 * 2, 0);
            uint32_t miss = ~0u;
#pragma unroll
            for (int h = 0; h < 2; h++) {
                const uint32_t need = h ? ~0u : (1u << 4 * 6) - 1;
                if (miss & need) {
#pragma unroll 1
                    do {
                        o = ld2(osrc);
                        if (++n > SPIN_LIMIT) __trap();
                        miss = __ballot_sync(0xffffffffu, max(o.x, o.y) == SENT);
                    } while (miss & need);
                    sts64(bs, o.x, o.y);
                    __syncwarp();
#pragma unroll
                    for (int i = h ? 6 / 2 : 0; i < 4; i++) e[i] = lds128(bl + i * 16);
                }
#pragma unroll
                for (int j = h ? 6 : 0; j < (h ? NWP : 6); j++) {
                    mbar_wait(bar_tail + 8 * j, 0);
                    uint32_t f0[4], f1[4];
                    ldsm_x4_t(f0, wa + j * 8192); ldsm_x4_t(f1, wb + j * 8192);
                    const uint32_t b0 = j & 1 ? e[j >> 1].z : e[j >> 1].x, b1 = j & 1 ? e[j >> 1].w : e[j >> 1].y;
                    mma_bf16(c0, f0, b0, b1); mma_bf16(c1, f1, b0, b1);
                }
            }
            sts32(rdst, t & 2 ? (t & 1 ? c1[2] : c1[0]) : (t & 1 ? c0[2] : c0[0]));
            fin_arrive<3>();
        }
        if (f1) {
            constexpr uint32_t b1 = bar_tail + 8 * NWP;
            uint32_t a1[5][4], a3[5][4];
            uint4 e[NG];
#pragma unroll
            for (int i = 0; i < NG; i++) e[i].x = e[i].y = e[i].z = e[i].w = 0;
            uint32_t got = 0, n = 0;
#pragma unroll
            for (int i = 0; i < NB; i++) a3[i][0] = a3[i][1] = a3[i][2] = a3[i][3] = 0;
            mbar_wait(b1, 0);
#pragma unroll
            for (int i = 0; i < NG; i++) ld4p(hs + xa_h(i), e[i], lane < 20);
            mbar_wait(b1 + 8, 0);
#pragma unroll
            for (int i = 0; i < 5; i++) ldsm_x4_t(a1[i], w1a + i * 4096);
            uint4 hb0, hb1;
            uint2 hb2;
            float sv[4];
#pragma unroll 1
            while (true) {
#define S_(f, c) (((f(e[0].c) + f(e[1].c)) + (f(e[2].c) + f(e[3].c))) + (f(e[4].c) + f(e[5].c)))
                const float sx = S_(__uint_as_float, x), sy = S_(__uint_as_float, y), sz = S_(__uint_as_float, z), sw = S_(__uint_as_float, w), sa = (sx + sy) + (sz + sw);
#undef S_
                const uint32_t h0 = add_bf2(xres.x, pack_bf(sy, sx)), h1 = add_bf2(xres.y, pack_bf(sw, sz));
                sts64(bs, h0, h1);
                __syncwarp();
                hb0 = lds128(hl); hb1 = lds128(hl + 16); hb2 = lds64(hl + 32);
                const float a = bf_lo(h0), b = bf_hi(h0), c = bf_lo(h1), d = bf_hi(h1);
                const float s1 = (a + b) + (c + d), s2 = fmaf(a, a, b * b) + fmaf(c, c, d * d);
                sv[0] = odd ? s2 : s1;
                sv[1] = __shfl_xor_sync(0xffffffffu, odd ? s1 : s2, 1);
                sv[2] = __shfl_xor_sync(0xffffffffu, sv[0], 2);
                sv[3] = __shfl_xor_sync(0xffffffffu, odd ? s1 : s2, 3);
                bool miss = __any_sync(0xffffffffu, sa != sa);
                if (miss) {
                    miss = false;
#pragma unroll
                    for (int i = 0; i < NG; i++) {
                        const bool m = max4(e[i]) == SENT;
                        ld4p(hs + xa_h(i), e[i], m);
                        miss = miss || m;
                    }
                    ldsm_if<4096>(a3[0], a3[1], w1a + (SM_W3 - SM_W1), b1 + 16, got);
                    if (++n > SPIN_LIMIT) __trap();
                    miss = __any_sync(0xffffffffu, miss);
                }
                if (!miss) break;
            }
            float cg[3][4], cu[3][4];
#pragma unroll
            for (int i = 0; i < 3; i++) { zero4(cg[i]); zero4(cu[i]); }
            const uint32_t hb[5][2] = {{hb0.x, hb0.y}, {hb0.z, hb0.w}, {hb1.x, hb1.y}, {hb1.z, hb1.w}, {hb2.x, hb2.y}};
            const float st = (sv[0] + sv[1]) + (sv[2] + sv[3]);
#pragma unroll
            for (int i = 0; i < 4; i++) sv[i] = __shfl_down_sync(0xffffffffu, st, 4 * i + 4);
#pragma unroll
            for (int i = 0; i < 5; i++) mma_bf16(cg[i % 3], a1[i], hb[i][0], hb[i][1]);
            sts32(lnd, ((st + sv[0]) + sv[1]) + (sv[2] + sv[3]));
            sts32(rdst + 32 * 48, odd ? (cg[0][2] + cg[2][2]) + cg[1][2] : (cg[0][0] + cg[2][0]) + cg[1][0]);
            fin_arrive<4>();
            if (__any_sync(0xffffffffu, !got)) {
                mbar_wait(b1 + 16, 0);
#pragma unroll
                for (int i = 0; i < NB; i++) ldsm_x4_t(a3[i], w1a + (SM_W3 - SM_W1) + i * 4096);
            }
            mbar_wait(b1 + 24, 0);
#pragma unroll
            for (int i = NB; i < 5; i++) ldsm_x4_t(a3[i], w1a + (SM_W3 - SM_W1) + i * 4096);
#pragma unroll
            for (int i = 0; i < 5; i++) mma_bf16(cu[i % 3], a3[i], hb[i][0], hb[i][1]);
            sts32(rdst + 64 * 48, odd ? (cu[0][2] + cu[2][2]) + cu[1][2] : (cu[0][0] + cu[2][0]) + cu[1][0]);
            __syncwarp();
            if (first) mbar_arrive(bar_up);
        }
        if (f2) {
            uint32_t a2[NF2][2][4];
#pragma unroll
            for (int i = 0; i < 4; i++) a2[NF2 - 1][0][i] = a2[NF2 - 1][1][i] = 0;
#pragma unroll
            for (int j = 0; j < NF2 - 1; j++) {
                mbar_wait(b2 + 8 * j, 0);
                ldsm_x4_t(a2[j][0], w2a + j * 8192); ldsm_x4_t(a2[j][1], w2a + j * 8192 + 512);
            }
            uint32_t n = 0, got = 0;
            uint4 e[NF2];
#pragma unroll 1
            while (true) {
                const uint4 pa = ld4(as);
                if (++n > SPIN_LIMIT) __trap();
                sts128(at, pa);
                __syncwarp();
#pragma unroll
                for (int j = 0; j < 3; j++) e[j] = lds128v(al + j * 64);
                if (__all_sync(0xffffffffu, ok8(pa))) break;
            }
#pragma unroll
            for (int j = 3; j < NF2; j++) e[j] = lds128v(al + j * 64);
            ldsm_if<512>(a2[NF2 - 1][0], a2[NF2 - 1][1], w2a + (NF2 - 1) * 8192, b2 + 8 * (NF2 - 1), got);
            float c[6][4];
#pragma unroll
            for (int j = 0; j < 6; j++) zero4(c[j]);
#pragma unroll
            for (int j = 0; j < NF2; j++) { mma_bf16(c[(j % 3) * 2], a2[j][0], e[j].x, e[j].y); mma_bf16(c[(j % 3) * 2 + 1], a2[j][1], e[j].z, e[j].w); }
            if (__any_sync(0xffffffffu, !got)) {
                constexpr int j = NF2 - 1;
                mbar_wait(b2 + 8 * j, 0);
                ldsm_x4_t(a2[j][0], w2a + j * 8192); ldsm_x4_t(a2[j][1], w2a + j * 8192 + 512);
                mma_bf16(c[4], a2[j][0], e[j].x, e[j].y); mma_bf16(c[5], a2[j][1], e[j].z, e[j].w);
            }
            sts32(rdst + 96 * 48, odd ? (((c[0][2] + c[1][2]) + (c[2][2] + c[3][2])) + c[4][2]) + c[5][2] : (((c[0][0] + c[1][0]) + (c[2][0] + c[3][0])) + c[4][0]) + c[5][0]);
            fin_arrive<6>();
        }
#undef F_
    }
}

typedef CUresult (*EncodeTiledFn)(CUtensorMap*, CUtensorMapDataType, cuuint32_t, void*, const cuuint64_t*, const cuuint64_t*,
                                  const cuuint32_t*, const cuuint32_t*, CUtensorMapInterleave, CUtensorMapSwizzle,
                                  CUtensorMapL2promotion, CUtensorMapFloatOOBfill);

void make_map(EncodeTiledFn fn, CUtensorMap* tm, const void* w, const int (&d)[5], const int (&st)[4], const int (&bx)[5],
              CUtensorMapSwizzle sw, int promo) {
    cuuint64_t dims[5], strides[4];
    cuuint32_t box[5], estr[5];
    for (int i = 0; i < 5; i++) { dims[i] = (cuuint64_t)d[i]; box[i] = (cuuint32_t)bx[i]; estr[i] = 1; }
    for (int i = 0; i < 4; i++) strides[i] = (cuuint64_t)st[i];
    fn(tm, CU_TENSOR_MAP_DATA_TYPE_BFLOAT16, 5, const_cast<void*>(w), dims, strides, box, estr, CU_TENSOR_MAP_INTERLEAVE_NONE, sw,
       (CUtensorMapL2promotion)promo, CU_TENSOR_MAP_FLOAT_OOB_FILL_NONE);
}

enum { T_PER, T_LEAD, T_STAG, T_TD, T_PERO, T_F1D, T_PERF, T_F2, T_PER2, T_Q, T_PWO, T_PW13, T_PW2, T_TG, T_GA, T_TGA, T_TG0, T_SH, T_INFL, T_DZ, T_Q2, T_ST, T_RD, T_RL, T_PKV, T_N };
int g_tune[T_N] = {478, 1170, 4, 20, 285, 300, 109, 1391, 120, 4800, 2, 2, 2, 1520, 250, 600, 75, 15, 4, 30, 6200, 1800, 3, 1, 2};

}

extern "C" void kernel_launch(void* const* d_in, const int* in_sizes, int n_in, void* d_out, int out_size) {
    (void)in_sizes; (void)n_in; (void)out_size;
    static EncodeTiledFn encode = nullptr;
    static Scratch* scratch = nullptr;
    static unsigned char* xarea = nullptr;
    if (!encode) {
        void* sp = nullptr;
        cudaGetSymbolAddress(&sp, g_scratch);
        scratch = reinterpret_cast<Scratch*>(sp);
        cudaGetSymbolAddress(&sp, g_xarea);
        xarea = reinterpret_cast<unsigned char*>((reinterpret_cast<uintptr_t>(sp) + XA_ALIGN - 1) / XA_ALIGN * XA_ALIGN);
        void* fn = nullptr;
        cudaDriverEntryPointQueryResult st;
        cudaGetDriverEntryPoint("cuTensorMapEncodeTiled", &fn, cudaEnableDefault, &st);
        encode = reinterpret_cast<EncodeTiledFn>(fn);
        cudaFuncSetAttribute(fused_decode_kernel, cudaFuncAttributeMaxDynamicSharedMemorySize, SM_TOTAL);
        int dev = 0, khz = 0, bits = 0;
        cudaGetDevice(&dev);
        if (cudaDeviceGetAttribute(&khz, cudaDevAttrMemoryClockRate, dev) == cudaSuccess &&
            cudaDeviceGetAttribute(&bits, cudaDevAttrGlobalMemoryBusWidth, dev) == cudaSuccess && khz > 0 && bits > 0) {
            const double f = 2619000.0 * 5120.0 / ((double)khz * bits);
            for (int i : {T_PER, T_STAG, T_SH, T_PERO, T_PERF, T_F2, T_Q, T_Q2}) g_tune[i] = (int)(g_tune[i] * f + 0.5);
            if (f < 1.0) g_tune[T_INFL] = (int)(g_tune[T_INFL] / f + 0.5);
        }
        (void)cudaGetLastError();
    }
    const int* T = g_tune;
    KParams p;
    p.x = (const __nv_bfloat16*)d_in[0];
    p.wq = (const __nv_bfloat16*)d_in[3];
    p.out = (__nv_bfloat16*)d_out;
    p.sc = scratch;
    p.xa = xarea;
    p.per = T[T_PER];
    p.stag = T[T_STAG];
    p.t_k0 = (NQT + 1) * T[T_PER] - T[T_LEAD];
    {
        int t = p.t_k0 + 2 * NKT * T[T_PER] + T[T_STAG] * 3 / 2 + T[T_SH] * 31 / 2 + T[T_TD];
        for (int i = 0; i < NWP; i++, t += T[T_PERO]) p.item[i] = t;
        for (int i = 0, t1 = t + T[T_F1D]; i < NP1; i++, t1 += T[T_PERF]) p.item[NWP + i] = t1;
        for (int i = 0, t2 = t + T[T_F2]; i < NF2; i++, t2 += T[T_PER2]) p.item[NWP + NP1 + i] = t2;
        for (int i = NITEM; i < 32; i++) p.item[i] = 0;
    }
    p.target = T[T_TG]; p.t_q = T[T_Q]; p.t_q2 = T[T_Q2]; p.t_stat = T[T_ST];
    p.rdelay = T[T_RD]; p.rlast = T[T_RL];
    p.gain = T[T_GA] / 100.f; p.tgain = T[T_TGA] / 47800.f; p.tg0 = T[T_TG0] / 10.f; p.dz = T[T_DZ] / 10.f;
    p.stagh = T[T_SH]; p.infl = T[T_INFL]; p.t_fill = p.t_k0 + 59 * T[T_PER];
    for (int i = 0, nw = 0, n1 = 0, n2 = 0; i < NCTA; i++) {
        const int grp = i >> 2;
        const bool f2 = grp % 3 == 2, both = grp == 8 || grp == 23, wo = !both, f1 = !f2 || both;
        p.role[i] = (wo ? 1 | nw / 20 << 3 | nw % 20 << 6 : 0) | (f1 ? 2 | n1 << 11 : 0) | (f2 ? 4 | n2 << 18 : 0);
        nw += wo; n1 += f1; n2 += f2;
    }
    TMaps tm;
    constexpr int R1 = FF * 2, R2 = D_MODEL * 2;
    for (int i = 0; i < 2; i++)
        make_map(encode, &tm.k + i, d_in[1 + i], {64, 96, 1, 1, NHEAD * SK / 32}, {128, TILE_BYTES, TILE_BYTES, TILE_BYTES}, {64, 96, 1, 1, 1}, CU_TENSOR_MAP_SWIZZLE_128B, T[T_PKV]);
    make_map(encode, &tm.wo, d_in[4], {D_MODEL, 2, 4, 2, NHEAD * DH / 16}, {R2, 4 * R2, 2 * R2, 16 * R2}, {32, 2, 4, 2, 8}, CU_TENSOR_MAP_SWIZZLE_64B, T[T_PWO]);
    make_map(encode, &tm.w1, d_in[6], {FF, 2, 4, 2, D_MODEL / 16}, {R1, 4 * R1, 2 * R1, 16 * R1}, {16, 2, 4, 2, 8}, CU_TENSOR_MAP_SWIZZLE_32B, T[T_PW13]);
    make_map(encode, &tm.w3, d_in[7], {FF, 2, 4, 2, D_MODEL / 16}, {R1, 4 * R1, 2 * R1, 16 * R1}, {16, 2, 4, 2, 8}, CU_TENSOR_MAP_SWIZZLE_32B, T[T_PW13]);
    make_map(encode, &tm.w2, d_in[8], {D_MODEL, 2, 4, 4, FF / 32}, {R2, 8 * R2, 2 * R2, 32 * R2}, {16, 2, 4, 4, 8}, CU_TENSOR_MAP_SWIZZLE_32B, T[T_PW2]);
    fused_decode_kernel<<<NCTA, NTHREADS, SM_TOTAL, cudaStreamPerThread>>>(p, tm);
}
```

```cpp
#include <cuda_runtime.h>
#include <cuda_bf16.h>
#include <cuda.h>
#include <stdint.h>
#include <initializer_list>

namespace {

constexpr int D_MODEL = 640;
constexpr int NHEAD = 32;
constexpr int DH = 192;
constexpr int SK = 32768;
constexpr int WIN = 4096;
constexpr int FF = 1536;

constexpr int NCTA = 128;
constexpr int NTHREADS = 256 + 64 + 192;
constexpr int TILE_BYTES = 32 * DH * 2;
constexpr int NSLOT = 16;
constexpr int NKT = 32;
constexpr int NQT = 5;
constexpr int QSLOT = NSLOT - NQT;
constexpr int NG = 6;
constexpr int NWP = 8, NP1 = 10, NF2 = 6;
constexpr int NITEM = NWP + NP1 + NF2;
constexpr int NF1 = 4, NA = 3, NB = 2;
constexpr int NTAIL = NWP + NF1 + NF2;

constexpr uint32_t sbase = 1024;
constexpr int SM_W1 = NWP * 8192, SM_W3 = SM_W1 + 20480, SM_W2 = SM_W3 + 20480;
constexpr int SM_P = NSLOT * TILE_BYTES;
constexpr int SM_Q = SM_P + 2048;
constexpr int SM_RED = SM_Q + 12288;
constexpr int SM_BC = SM_RED + 128 * 48;
constexpr int SM_ONE = SM_BC + 4096;
constexpr int SM_ST = SM_ONE + 64;
constexpr int SM_WT = SM_ST + 256;
constexpr int SM_RO = SM_WT + 512;
constexpr int SM_LN = SM_RO + 48 * 80;
constexpr int SM_MISC = SM_LN + 64;
constexpr int SM_LATE = SM_MISC + 32;
constexpr int SM_BAR = SM_LATE + 32;
constexpr int SM_TOTAL = SM_BAR + 512;
static_assert(SM_TOTAL <= 232448, "shared memory");

struct __align__(128) Scratch {
    uint2 qbuf[NCTA * 96];
    uint2 qall[NHEAD * 96];
    uint2 mbuf[NCTA * NHEAD];
    uint32_t ready[NCTA];
    uint32_t late[32];
    uint32_t epoch;
};
__device__ Scratch g_scratch;
constexpr int XA_ALIGN = 2 << 20;
constexpr uint32_t SENT = 0xffffffffu;
__device__ unsigned char g_xarea[XA_ALIGN + (9 << 20)];
__device__ __forceinline__ uint32_t xa_o(uint32_t kw, uint32_t j) { return (kw >> 4) * 16384 + (kw & 15) * 256 + j * 32; }
constexpr int NLATE = 4;
__device__ __forceinline__ uint32_t xa_p(uint32_t h, uint32_t q, uint32_t j) {
    const uint32_t k = ((NHEAD - 1 - h) * 4 + q) * 8 + j;
    return (1 << 20) + (2 * k + ((k ^ (k >> 3) ^ (k >> 4) ^ (k >> 6)) & 1)) * 4096;
}
__host__ __device__ constexpr uint32_t xa_h(uint32_t i) { return (1 << 18) + (i >> 2) * (3 << 16) + (i & 3) * (1 << 14); }
constexpr uint32_t XA_A = xa_h(NG);

constexpr uint32_t XA_PROBE = 1 << 13 | 1 << 19;

constexpr uint32_t SPIN_LIMIT = 1u << 22;

__device__ __forceinline__ uint32_t smem_u32(const void* p) { return (uint32_t)__cvta_generic_to_shared(p); }
__device__ __forceinline__ uint32_t now_ns() { uint64_t t; asm volatile("mov.u64 %0, %globaltimer;" : "=l"(t)); return (uint32_t)t; }
__device__ __forceinline__ void mbar_init(uint32_t bar, uint32_t cnt) {
    asm volatile("mbarrier.init.shared::cta.b64 [%0], %1;" ::"r"(bar), "r"(cnt) : "memory");
}
__device__ __forceinline__ void mbar_expect_tx(uint32_t bar, uint32_t bytes) {
    asm volatile("mbarrier.arrive.expect_tx.shared::cta.b64 _, [%0], %1;" ::"r"(bar), "r"(bytes) : "memory");
}
__device__ __forceinline__ void mbar_arrive(uint32_t bar) {
    asm volatile("mbarrier.arrive.shared::cta.b64 _, [%0];" ::"r"(bar) : "memory");
}
__device__ __forceinline__ void mbar_arrive8(uint32_t bar) {
    asm volatile("mbarrier.arrive.shared::cta.b64 _, [%0], 8;" ::"r"(bar) : "memory");
}
__device__ __forceinline__ bool mbar_test(uint32_t bar, uint32_t parity) {
    uint32_t ok;
    asm volatile("{\n.reg .pred p;\nmbarrier.test_wait.parity.shared::cta.b64 p, [%1], %2;\nselp.u32 %0, 1, 0, p;\n}"
                 : "=r"(ok) : "r"(bar), "r"(parity) : "memory");
    return ok;
}
__device__ __forceinline__ void mbar_wait(uint32_t bar, uint32_t parity) {
    asm volatile("{\n.reg .pred p;\nW_%=:\nmbarrier.try_wait.parity.shared::cta.b64 p, [%0], %1;\n@!p bra.uni W_%=;\n}" ::"r"(bar), "r"(parity) : "memory");
}
__device__ __forceinline__ void mbar_wait_after(uint32_t bar, uint32_t dump, float v) {
    uint32_t ok;
    asm volatile("{\n.reg .pred p;\nmbarrier.try_wait.parity.shared::cta.b64 p, [%1], 0;\nselp.u32 %0, 1, 0, p;\n}" : "=r"(ok) : "r"(bar) : "memory");
    asm volatile("st.volatile.shared.f32 [%0], %1;" ::"r"(dump), "f"(v) : "memory");
    if (__builtin_expect(!ok, 0)) mbar_wait(bar, 0);
}
__device__ __forceinline__ void tma_load_at(uint32_t when, uint32_t dst, const CUtensorMap* tm, int c0, int c4, uint32_t bar, uint64_t pol) {
    asm volatile("{\n.reg .pred p, e;\n.reg .b64 t;\n.reg .b32 lo, hi;\nelect.sync _|e, -1;\n"
                 "W_%=:\nmov.u64 t, %globaltimer;\nmov.b64 {lo, hi}, t;\nsub.u32 lo, lo, %7;\nsetp.lt.s32 p, lo, 0;\n@p bra.uni W_%=;\n"
                 "@e cp.async.bulk.tensor.5d.shared::cluster.global.mbarrier::complete_tx::bytes.L2::cache_hint [%0], [%1, {%3, %5, %5, %5, %4}], [%2], %6;\n}"
                 ::"r"(dst), "l"(reinterpret_cast<uint64_t>(tm)), "r"(bar), "r"(c0), "r"(c4), "r"(0), "l"(pol), "r"(when) : "memory");
}
__device__ __forceinline__ void pin(uint32_t& v) { asm volatile("shfl.sync.bfly.b32 %0, %0, 0, 31, -1;" : "+r"(v) :: "memory"); }
__device__ __forceinline__ void pin_u(uint32_t& v) { asm volatile("shfl.sync.idx.b32 %0, %0, 0, 31, -1;" : "+r"(v) :: "memory"); }
template <class T> __device__ __forceinline__ void pin(T*& v) {
    asm volatile("{\n.reg .b32 a, b;\nmov.b64 {a, b}, %0;\nshfl.sync.bfly.b32 a, a, 0, 31, -1;\nshfl.sync.bfly.b32 b, b, 0, 31, -1;\nmov.b64 %0, {a, b};\n}" : "+l"(v) :: "memory");
}
__device__ __forceinline__ void sts16(uint32_t a, uint32_t v) { asm volatile("st.shared.u16 [%0], %1;" ::"r"(a), "h"((unsigned short)v) : "memory"); }
__device__ __forceinline__ void sts32(uint32_t a, float v) { asm volatile("st.shared.f32 [%0], %1;" ::"r"(a), "f"(v) : "memory"); }
__device__ __forceinline__ void sts32(uint32_t a, uint32_t v) { asm volatile("st.shared.u32 [%0], %1;" ::"r"(a), "r"(v) : "memory"); }
__device__ __forceinline__ void sts64(uint32_t a, uint32_t x, uint32_t y) { asm volatile("st.shared.v2.u32 [%0], {%1, %2};" ::"r"(a), "r"(x), "r"(y) : "memory"); }
__device__ __forceinline__ void sts128(uint32_t a, const uint4& v) { asm volatile("st.shared.v4.u32 [%0], {%1, %2, %3, %4};" ::"r"(a), "r"(v.x), "r"(v.y), "r"(v.z), "r"(v.w) : "memory"); }
__device__ __forceinline__ void cons_sync() { asm volatile("bar.sync 1, 256;" ::: "memory"); }
template <int ID> __device__ __forceinline__ void fin_arrive() { asm volatile("bar.arrive %0, 288;" ::"n"(ID) : "memory"); }
template <int ID> __device__ __forceinline__ void fin_sync() { asm volatile("bar.sync %0, 288;" ::"n"(ID) : "memory"); }

__device__ __forceinline__ uint4 lds128(uint32_t a) {
    uint4 v;
    asm volatile("ld.shared.v4.u32 {%0,%1,%2,%3}, [%4];" : "=r"(v.x), "=r"(v.y), "=r"(v.z), "=r"(v.w) : "r"(a) : "memory");
    return v;
}
__device__ __forceinline__ uint4 lds128v(uint32_t a) {
    uint4 v;
    asm volatile("ld.volatile.shared.v4.u32 {%0,%1,%2,%3}, [%4];" : "=r"(v.x), "=r"(v.y), "=r"(v.z), "=r"(v.w) : "r"(a) : "memory");
    return v;
}
__device__ __forceinline__ float4 lds128f(uint32_t a) {
    float4 v;
    asm volatile("ld.shared.v4.f32 {%0,%1,%2,%3}, [%4];" : "=f"(v.x), "=f"(v.y), "=f"(v.z), "=f"(v.w) : "r"(a) : "memory");
    return v;
}
__device__ __forceinline__ uint2 lds64(uint32_t a) {
    uint2 v;
    asm volatile("ld.shared.v2.u32 {%0,%1}, [%2];" : "=r"(v.x), "=r"(v.y) : "r"(a) : "memory");
    return v;
}
__device__ __forceinline__ uint32_t lds32(uint32_t a) {
    uint32_t v;
    asm volatile("ld.shared.u32 %0, [%1];" : "=r"(v) : "r"(a) : "memory");
    return v;
}
__device__ __forceinline__ float sum8(uint32_t a) {
    const float4 x = lds128f(a), y = lds128f(a + 16);
    return ((x.x + x.y) + (x.z + x.w)) + ((y.x + y.y) + (y.z + y.w));
}
__device__ __forceinline__ void ldsm_x4(uint32_t* r, uint32_t a) {
    asm volatile("ldmatrix.sync.aligned.m8n8.x4.shared.b16 {%0,%1,%2,%3}, [%4];"
                 : "=r"(r[0]), "=r"(r[1]), "=r"(r[2]), "=r"(r[3]) : "r"(a) : "memory");
}
__device__ __forceinline__ void ldsm_x4_t(uint32_t* r, uint32_t a) {
    asm volatile("ldmatrix.sync.aligned.m8n8.x4.trans.shared.b16 {%0,%1,%2,%3}, [%4];"
                 : "=r"(r[0]), "=r"(r[1]), "=r"(r[2]), "=r"(r[3]) : "r"(a) : "memory");
}
template <int STRIDE>
__device__ __forceinline__ void ldsm_if(uint32_t* r0, uint32_t* r1, uint32_t a, uint32_t bar, uint32_t& got) {
        asm volatile("{\n.reg .pred p, q;\nsetp.eq.u32 q, %8, 0;\nmbarrier.test_wait.parity.shared::cta.b64 p, [%10], 0;\nand.pred p, p, q;\n"
                     "@p ldmatrix.sync.aligned.m8n8.x4.trans.shared.b16 {%0,%1,%2,%3}, [%9];\n"
                     "@p ldmatrix.sync.aligned.m8n8.x4.trans.shared.b16 {%4,%5,%6,%7}, [%9+%11];\n@p mov.u32 %8, 1;\n}"
                     : "+r"(r0[0]), "+r"(r0[1]), "+r"(r0[2]), "+r"(r0[3]), "+r"(r1[0]), "+r"(r1[1]), "+r"(r1[2]), "+r"(r1[3]), "+r"(got)
                     : "r"(a), "r"(bar), "n"(STRIDE) : "memory");
}
__device__ __forceinline__ void mma_bf16(float* c, uint32_t a0, uint32_t a1, uint32_t a2, uint32_t a3, uint32_t b0, uint32_t b1) {
    asm volatile("mma.sync.aligned.m16n8k16.row.col.f32.bf16.bf16.f32 {%0,%1,%2,%3}, {%4,%5,%6,%7}, {%8,%9}, {%0,%1,%2,%3};"
                 : "+f"(c[0]), "+f"(c[1]), "+f"(c[2]), "+f"(c[3]) : "r"(a0), "r"(a1), "r"(a2), "r"(a3), "r"(b0), "r"(b1));
}
__device__ __forceinline__ void mma_bf16(float* c, const uint32_t* a, uint32_t b0, uint32_t b1) { mma_bf16(c, a[0], a[1], a[2], a[3], b0, b1); }
__device__ __forceinline__ void zero4(float* c) { c[0] = c[1] = c[2] = c[3] = 0.f; }
__device__ __forceinline__ float bf_lo(uint32_t u) { return __uint_as_float(u << 16); }
__device__ __forceinline__ float bf_hi(uint32_t u) { return __uint_as_float(u & 0xffff0000u); }
__device__ __forceinline__ uint32_t pack_bf(float hi, float lo) { uint32_t r; asm("cvt.rn.bf16x2.f32 %0, %1, %2;" : "=r"(r) : "f"(hi), "f"(lo)); return r; }
__device__ __forceinline__ uint32_t add_bf2(uint32_t a, uint32_t b) { uint32_t r; asm("add.rn.bf16x2 %0, %1, %2;" : "=r"(r) : "r"(a), "r"(b)); return r; }
__device__ __forceinline__ float bfr(float x) { return __uint_as_float(pack_bf(x, 0.f)); }

__device__ __forceinline__ uint32_t in_word(float v) { return __float_as_uint(v); }
__device__ __forceinline__ void st1(void* p, uint32_t v) {
    asm volatile("st.relaxed.gpu.global.u32 [%0], %1;" ::"l"(p), "r"(v) : "memory");
}
__device__ __forceinline__ void st16(void* p, uint32_t v) {
    asm volatile("st.relaxed.gpu.global.u16 [%0], %1;" ::"l"(p), "h"((unsigned short)v) : "memory");
}
__device__ __forceinline__ void st2(void* p, uint32_t a, uint32_t b) {
    asm volatile("st.relaxed.gpu.global.v2.u32 [%0], {%1, %2};" ::"l"(p), "r"(a), "r"(b) : "memory");
}
__device__ __forceinline__ void st4(void* p, uint32_t a, uint32_t b, uint32_t c, uint32_t d) {
    asm volatile("st.relaxed.gpu.global.v4.u32 [%0], {%1, %2, %3, %4};" ::"l"(p), "r"(a), "r"(b), "r"(c), "r"(d) : "memory");
}
__device__ __forceinline__ uint32_t ld1(const void* p) {
    uint32_t v;
    asm volatile("ld.relaxed.gpu.global.u32 %0, [%1];" : "=r"(v) : "l"(p) : "memory");
    return v;
}
__device__ __forceinline__ uint2 ld2(const void* p) {
    uint2 v;
    asm volatile("ld.relaxed.gpu.global.v2.u32 {%0, %1}, [%2];" : "=r"(v.x), "=r"(v.y) : "l"(p) : "memory");
    return v;
}
__device__ __forceinline__ uint4 ld4(const void* p) {
    uint4 v;
    asm volatile("ld.relaxed.gpu.global.v4.u32 {%0, %1, %2, %3}, [%4];" : "=r"(v.x), "=r"(v.y), "=r"(v.z), "=r"(v.w) : "l"(p) : "memory");
    return v;
}
__device__ __forceinline__ void ld4p(const void* p, uint4& v, bool on) {
    asm volatile("{\n.reg .pred q;\nsetp.ne.u32 q, %5, 0;\n@q ld.relaxed.gpu.global.v4.u32 {%0, %1, %2, %3}, [%4];\n}"
                 : "+r"(v.x), "+r"(v.y), "+r"(v.z), "+r"(v.w) : "l"(p), "r"((uint32_t)on) : "memory");
}
__device__ __forceinline__ bool ok8(const uint4& v) {
    const uint32_t m = __vimax3_u16x2(__vimax3_u16x2(v.x, v.y, v.z), v.w, v.w);
    return __vimax3_u16x2(m, m << 16, m >> 16) != SENT;
}
__device__ __forceinline__ uint32_t max4(const uint4& v) { return max(max(v.x, v.y), max(v.z, v.w)); }
__device__ __forceinline__ void pkt_ld2(const uint4* p, uint64_t& a, uint64_t& b) {
    asm volatile("ld.relaxed.gpu.global.v2.b64 {%0, %1}, [%2];" : "=l"(a), "=l"(b) : "l"(p) : "memory");
}
__device__ __forceinline__ bool tag_ok(uint64_t v, uint32_t tag) { return (uint32_t)(v >> 32) == tag; }
__device__ __forceinline__ float val_of(uint64_t v) { return __uint_as_float((uint32_t)v); }

__device__ __forceinline__ float warp_sum(float v) {
#pragma unroll
    for (int o = 16; o > 0; o >>= 1) v += __shfl_xor_sync(0xffffffffu, v, o);
    return v;
}
__device__ __forceinline__ float warp_max(float v) {
#pragma unroll
    for (int o = 16; o > 0; o >>= 1) v = fmaxf(v, __shfl_xor_sync(0xffffffffu, v, o));
    return v;
}
__device__ __forceinline__ float sqrt_fast(float x) { float r; asm("sqrt.approx.ftz.f32 %0, %1;" : "=f"(r) : "f"(x)); return r; }
__device__ __forceinline__ float rcp_fast(float x) { float r; asm("rcp.approx.ftz.f32 %0, %1;" : "=f"(r) : "f"(x)); return r; }
__device__ __forceinline__ float ex2(float x) { float r; asm("ex2.approx.ftz.f32 %0, %1;" : "=f"(r) : "f"(x)); return r; }
constexpr float L2E = 1.4426950408889634f;
__device__ __forceinline__ void ln_finish(float s1, float s2, float& mean_b, float& inv_den) {
    const float mean = s1 * (1.0f / D_MODEL);
    const float var = fmaxf(fmaf(-mean, mean, s2 * (1.0f / D_MODEL)), 0.f);
    mean_b = bfr(mean);
    inv_den = rcp_fast(bfr(sqrt_fast(bfr(bfr(var) + 1e-5f))));
}
__device__ __forceinline__ uint32_t ln_apply2(uint32_t u, float mean_b, float inv_den) {
    const uint32_t d = pack_bf(bf_hi(u) - mean_b, bf_lo(u) - mean_b);
    return pack_bf(bf_hi(d) * inv_den, bf_lo(d) * inv_den);
}
__device__ __forceinline__ void ln_acc(uint32_t u, float& s1, float& s2) {
    const float a = bf_lo(u), b = bf_hi(u);
    s1 += a + b;
    s2 = fmaf(a, a, fmaf(b, b, s2));
}
__device__ __forceinline__ float silu_b(float g) { return bfr(__fdividef(g, 1.0f + ex2(-g * L2E))); }

struct KParams {
    const __nv_bfloat16* wq;
    const __nv_bfloat16* x;
    __nv_bfloat16* out;
    Scratch* sc;
    unsigned char* xa;
    int t_k0, per, stag, stagh;
    int target, infl;
    float dz, gain, tg0, tgain;
    int t_q, t_q2, t_stat, t_fill;
    int rdelay, rlast;
    uint32_t item[32];
    uint32_t role[NCTA];
};
struct TMaps { CUtensorMap k, v, wo, w1, w3, w2; };

__global__ void __launch_bounds__(NTHREADS, 1)
fused_decode_kernel(const __grid_constant__ KParams p, const __grid_constant__ TMaps tm) {
    extern __shared__ __align__(1024) unsigned char smem[];
    const int tid = threadIdx.x;
    const int b = blockIdx.x;
    const int head = b >> 2, sp = b & 3;
    {
        const char* a = reinterpret_cast<const char*>(p.wq) + (uint32_t)((sp * 32 + (tid >> 2) + (tid >> 7) * 96) * (NHEAD * DH * 2) + head * (DH * 2) + (tid & 3) * 128);
        if (tid < 320) asm volatile("prefetch.global.L2 [%0];" ::"l"(a) : "memory");
    }
    if (tid < 256) {
        const uint32_t r = tid >> 3, ch = tid & 7;
        const char* src = reinterpret_cast<const char*>(p.wq) + ((sp * 32 + r) * (NHEAD * DH * 2) + head * (DH * 2) + ch * 16);
#pragma unroll
        for (int i = 0; i < NQT; i++) {
#pragma unroll
            for (int j = 0; j < 3; j++)
                asm volatile("cp.async.cg.shared.global [%0], [%1], 16;"
                             ::"r"(sbase + (QSLOT + i) * TILE_BYTES + (3 * r + j) * 128 + ((ch ^ ((3 * r + j) & 7)) << 4)),
                               "l"(src + (size_t)i * 128 * (NHEAD * DH * 2) + j * 128) : "memory");
        }
    }
    const uint32_t t0 = now_ns();
    const int warp = __shfl_sync(0xffffffffu, tid >> 5, 0), lane = tid & 31;
    const uint32_t role = p.role[b];
    const int kg = role >> 3 & 7, ng = role >> 6 & 31;
    const int u1 = role >> 11 & 127, u2 = role >> 18;
    const bool has_wo = role & 1, has_f1 = role & 2, has_f2 = role & 4;
    constexpr uint32_t bar_full = sbase + SM_BAR;
    constexpr uint32_t bar_empty = sbase + SM_BAR + 128;
    constexpr uint32_t bar_tail = sbase + SM_BAR + 256;
    constexpr uint32_t bar_rdy = bar_tail + 8 * NTAIL;
    constexpr uint32_t bar_side = bar_rdy + 8;
    constexpr uint32_t bar_wt = bar_side + 8;
    constexpr uint32_t bar_go = bar_side + 16;
    constexpr uint32_t bar_stat = bar_side + 24;
    constexpr uint32_t bar_up = bar_side + 32;

    if (warp == 8) {
        if (smem_u32(smem) != sbase) __trap();
        uint64_t pol;
        asm volatile("createpolicy.fractional.L2::evict_first.b64 %0, 1.0;" : "=l"(pol));
        sts32(sbase + SM_LATE + (lane & 7) * 4, 0u);
        if (lane == 0) {
#pragma unroll
            for (int i = 0; i < 32 + NTAIL + 6; i++)
                mbar_init(bar_full + 8 * i, (i >= 16 && i < 32) || i > 35 + NTAIL ? 8 : i == 32 + NWP ? NA : i == 33 + NWP ? 5 - NA : i == 34 + NWP ? NB : i == 35 + NWP ? 5 - NB : 1);
#pragma unroll
            for (int i = 0; i < 6; i++) asm volatile("prefetch.tensormap [%0];" ::"l"(reinterpret_cast<uint64_t>(&tm.k + i)) : "memory");
            asm volatile("fence.mbarrier_init.release.cluster;" ::: "memory");
        }
        __syncwarp();
        asm volatile("bar.arrive 2, 512;" ::: "memory");
        const uint32_t tu = __shfl_sync(0xffffffffu, t0, 0);
        if (b == 0 && lane < 8) st1(p.sc->late + lane, lane ? 0 : (tu & 0xffffffu) | 1u << 24);
        const int seg = (lane >= NWP) + (lane >= NWP + NP1), i = lane - (seg == 0 ? 0 : seg == 1 ? NWP : NWP + NP1);
        const bool todo = lane < NITEM && (role >> seg & 1);
        const uint32_t len = seg == 1 ? 4096 : 8192, dst = sbase + (seg == 0 ? 0 : seg == 1 ? SM_W1 : SM_W2) + i * len;
        const int w3 = seg == 1 && i >= 5;
        const uint32_t mi = seg == 2 ? 3 : seg + w3;
        const int c0 = seg == 0 ? ng * 32 : seg == 1 ? u1 * 16 : u2 * 16;
        const int c4 = (seg == 0 ? kg * 64 : w3 * -40) + i * 8;
        const uint32_t bar = bar_tail + 8 * (seg == 0 ? i : seg == 1 ? NWP + (i >= NA) + w3 + (i >= 5 + NB) : NWP + NF1 + i);
        const int tile0 = (SK - WIN) / 32 + b;
        uint32_t tk = tu + p.t_k0 + sp * p.stag + head * p.stagh, tw = tk, acc = 0;
        int slip = 0, base = 0, w = 0, d0 = 0;
        float a2 = 0.f, drift = 0.f;
#pragma unroll 1
        for (int n = 0; n < 2 * NKT; n++) {
            const int slot = n & (NSLOT - 1);
            mbar_wait(bar_empty + 8 * slot, (((n + NQT) >> 4) & 1) ^ 1);
            if (lane == 0) mbar_expect_tx(bar_full + 8 * slot, TILE_BYTES);
            bool more;
            do {
                const uint32_t t = now_ns();
                if (__all_sync(0xffffffffu, mbar_test(bar_full + 8 * (w & (NSLOT - 1)), (w >> 4) & 1))) {
                    acc += t - tw;
                    tw += p.per;
                    w++;
                    if ((w & 7) == 0) {
                        if (lane == 0) asm volatile("red.relaxed.gpu.global.add.u32 [%0], %1;" ::"l"(p.sc->late + (w >> 3)), "r"((1u << 24) + min(max(((int)acc >> 3) + d0, 0), 65535)) : "memory");
                        acc = 0;
                    }
                }
                more = __any_sync(0xffffffffu, (int)(t - tk) < slip - 60) || w <= n - p.infl;
            } while (more);
            tma_load_at(tk + slip, sbase + slot * TILE_BYTES, &tm.k + (n >> 5), 0, tile0 + (n & (NKT - 1)) * (SK / 32), bar_full + 8 * slot, pol);
            tk += p.per;
            if ((n & 7) == 5 && lane < 2)
                asm volatile("cp.async.cg.shared.global [%0], [%1], 16;" ::"r"(sbase + SM_LATE + lane * 16), "l"(p.sc->late + lane * 4) : "memory");
            const uint32_t org = lds32(sbase + SM_LATE);
            if (org) d0 = (int)((tu - org) << 8) >> 8;
            int k = n >> 3;
            uint32_t rep = lds32(sbase + SM_LATE + k * 4);
            const uint32_t rep0 = lds32(sbase + SM_LATE + max(k - 1, 0) * 4);
            if (!(rep >> 30)) { rep = rep0; k--; }
            if (rep >> 30) {
                const float a = (float)(rep & 0xffffffu) * rcp_fast((float)(rep >> 24));
                if (k <= 2) a2 = a; else drift = fminf(fmaxf((a - a2) * rcp_fast((float)(8 * k - 16)), -4.f), 6.f);
                base = max((int)a - p.target - d0, -900);
                slip = base + (int)(fmaxf(drift - p.dz, 0.f) * p.gain * (float)(n + 5 - 8 * k));
            }
        }
        const uint32_t tn = tu + base + p.item[lane] + (int)(drift * fmaf(p.tgain, (float)(int)(p.item[lane] - p.item[0]), p.tg0));
        if (todo) mbar_expect_tx(bar, len);
        const uint32_t c04 = c0 | c4 << 16, db = dst | (bar - bar_tail) << 18 | mi << 28;
#pragma unroll 1
        for (uint32_t left = __ballot_sync(0xffffffffu, todo); left; left &= left - 1) {
            const int k = __ffs(left) - 1;
            const uint32_t kc = __shfl_sync(0xffffffffu, c04, k), kd = __shfl_sync(0xffffffffu, db, k), kt = __shfl_sync(0xffffffffu, tn, k);
            mbar_wait(bar_empty + 8 * (k < NWP ? 5 : 12), k < NWP);
            tma_load_at(kt, kd & 0x3ffff, &tm.wo + (kd >> 28), kc & 0xffff, kc >> 16, bar_tail + (kd >> 18 & 0x3ff), pol);
        }
    } else if (warp >= 10) {
        asm volatile("bar.sync 2, 512;" ::: "memory");
        const uint32_t t4 = (lds32(sbase + SM_MISC) & 7) + 1, id = tid - 320, sg = id / 12;
        while (!mbar_test(bar_wt, 0)) __nanosleep(500);
        const float4 wa = lds128f(sbase + SM_WT + sg * 32), wb = lds128f(sbase + SM_WT + sg * 32 + 16);
        const float wt[8] = {wa.x, wa.y, wa.z, wa.w, wb.x, wb.y, wb.z, wb.w};
        uint32_t sd = sp & 1;
        if (head >= NHEAD - NLATE) {
            while (!mbar_test(bar_side, 0)) __nanosleep(200);
            sd = lds32(sbase + SM_MISC + 4);
        }
        const uint32_t o0 = (xa_p(head, sp, 0) ^ sd << 12) + id * 16;
        const unsigned char* a0 = p.xa + o0;
        const unsigned char* a1 = p.xa + (o0 ^ 4096);
        uint32_t dst = sbase + SM_RO + (id - sg * 12) * 320 + sg * 4;
        pin(a0); pin(a1); pin(dst);
        mbar_wait(bar_go, 0);
        uint4 e[8];
#pragma unroll
        for (int j = 0; j < 8; j++) e[j] = ld4((j & 1 ? a1 : a0) + j * 8192);
        uint32_t k = 0;
        bool miss;
#pragma unroll 1
        do {
            miss = false;
#pragma unroll
            for (int j = 0; j < 8; j++) {
                const bool m = (((e[j].x ^ t4) | (e[j].y ^ t4) | (e[j].z ^ t4) | (e[j].w ^ t4)) & 15) != 0;
                ld4p((j & 1 ? a1 : a0) + j * 8192, e[j], m);
                miss = miss || m;
            }
            if (++k > SPIN_LIMIT) __trap();
        } while (__any_sync(0xffffffffu, miss));
        float o[4] = {0.f, 0.f, 0.f, 0.f};
#pragma unroll
        for (int j = 0; j < 8; j++) {
            o[0] = fmaf(wt[j], __uint_as_float(e[j].x ^ t4), o[0]); o[1] = fmaf(wt[j], __uint_as_float(e[j].y ^ t4), o[1]);
            o[2] = fmaf(wt[j], __uint_as_float(e[j].z ^ t4), o[2]); o[3] = fmaf(wt[j], __uint_as_float(e[j].w ^ t4), o[3]);
        }
#pragma unroll
        for (int i = 0; i < 4; i++) sts32(dst + i * 80, o[i]);
        asm volatile("bar.arrive 5, 224;" ::: "memory");
    } else if (warp == 9) {
        const uint32_t tag = ld1(&p.sc->epoch) + 1;
        const uint32_t aoff = XA_A + (u1 >> 1 & 7) * 384 + (u1 >> 4) * 64 + (u1 & 1) * 32, hoff = xa_h(kg) + (ng & 3) * 1024 + (ng >> 2) * 64;
        sts32(sbase + SM_ONE + (lane & 15) * 4, 0x3f803f80u);
        const uint32_t l24 = min(lane, 23), od = head * 12 + sp * 3 + (l24 >> 3);
        const uint32_t ooff = xa_o((od >> 6) * 8 + (od & 7), od >> 3 & 7);
        unsigned char* slot[3] = {p.xa + (ooff + (l24 & 7) * 4), p.xa + (ooff + (l24 & 7) * 4 + 4096),
                                  p.xa + (lane < 16 ? (has_wo ? hoff + (lane >> 3) * 4096 + (lane >> 2 & 1) * 512 + (lane & 3) * 16 : ooff) : has_f1 ? aoff + (lane >> 1 & 1) * 4096 + (lane & 1) * 16 : ooff)};
#pragma unroll
        for (int i = 0; i < 2; i++) st4(p.sc->qbuf + b * 96 + i * 32 + lane * 2, 0, 0, 0, 0);
        uint2* qdst = p.sc->qall + ((head & 7) * 4 + (head >> 3)) * 96 + sp * 24 + l24;
        st2(qdst, 0, 0);
        sts32(sbase + SM_MISC, tag);
        asm volatile("bar.sync 2, 512;" ::: "memory");
        uint32_t n = 0;
        {
            const uint32_t t4 = (tag & 7) + 1;
            uint2 e[4];
            uint32_t bad;
#pragma unroll 1
            do {
                do __nanosleep(100); while ((int)(now_ns() - (t0 + p.t_q)) < 0);
                bad = 0;
#pragma unroll
                for (int i = 0; i < 4; i++) e[i] = ld2(p.sc->qbuf + (head * 4 + i) * 96 + l24 * 4 + sp);
#pragma unroll
                for (int i = 0; i < 4; i++) { e[i].x ^= t4; e[i].y ^= t4; bad |= e[i].x | e[i].y; }
                if (++n > SPIN_LIMIT) __trap();
            } while (__any_sync(0xffffffffu, bad & 15));
#define S_(c) ((__uint_as_float(e[0].c) + __uint_as_float(e[1].c)) + (__uint_as_float(e[2].c) + __uint_as_float(e[3].c)))
            asm volatile("st.relaxed.gpu.global.b64 [%0], %1;" ::"l"(qdst), "l"((uint64_t)tag << 32 | pack_bf(S_(y), S_(x))) : "memory");
#undef S_
        }
        {
            while (!mbar_test(bar_stat, 0)) __nanosleep(200);
            const uint2 st = lds64(sbase + SM_ST + lane * 8);
            asm volatile("st.relaxed.gpu.global.b64 [%0], %1;" ::"l"(p.sc->mbuf + b * NHEAD + lane), "l"((uint64_t)st.y << 32 | st.x) : "memory");
            const uint32_t t1 = now_ns() + p.t_stat, t16 = (tag & 0x7fff) + 1;
            uint64_t e[4];
            do {
                do __nanosleep(200); while ((int)(now_ns() - t1) < 0);
#pragma unroll
                for (int i = 0; i < 4; i++) asm volatile("ld.relaxed.gpu.global.b64 %0, [%1];" : "=l"(e[i]) : "l"(p.sc->mbuf + (lane + 32 * i) * NHEAD + head) : "memory");
#pragma unroll
                for (int i = 0; i < 4; i++) e[i] ^= t16;
                if (++n > SPIN_LIMIT) __trap();
            } while (__any_sync(0xffffffffu, (e[0] | e[1] | e[2] | e[3]) & 0xffff));
            const float M = warp_max(fmaxf(fmaxf(val_of(e[0]), val_of(e[1])), fmaxf(val_of(e[2]), val_of(e[3]))));
            float x[4], L = 0.f;
#pragma unroll
            for (int i = 0; i < 4; i++) { x[i] = ex2((val_of(e[i]) - M) * L2E); L = fmaf(x[i], val_of(e[i] >> 32), L); }
            L = rcp_fast(warp_sum(L));
#pragma unroll
            for (int i = 0; i < 4; i++) sts32(sbase + SM_WT + (lane & 15) * 32 + (lane >> 4) * 4 + i * 8, x[i] * L);
            __syncwarp();
            if (lane == 0) mbar_arrive(bar_wt);
        }
        unsigned char* pr = p.xa + (xa_h(b & 7) + XA_PROBE + (b >> 3) * 128 + lane * 4);
        st1(pr, SENT); st1(pr + 4096, SENT);
        int vote = 0;
#pragma unroll 1
        for (int r = 0; r < 9 && (!vote || (int)(now_ns() - (t0 + p.t_fill)) < -1000); r++) {
            __nanosleep(100);
            uint32_t d;
            asm volatile("{\n.reg .pred p, q;\n.reg .b32 a, b, c0, c1;\nmov.b32 c0, 0;\nmov.b32 c1, 0;\n"
                         "atom.relaxed.gpu.global.exch.b32 a, [%1], -1;\natom.relaxed.gpu.global.exch.b32 b, [%2], -1;\n"
                         "setp.eq.u32 p, a, -1;\n@p mov.u32 c0, %%clock;\nsetp.eq.u32 q, b, -1;\n@q mov.u32 c1, %%clock;\nsub.u32 %0, c1, c0;\n}"
                         : "=r"(d) : "l"(pr + (r & 1) * 4096), "l"(pr + (~r & 1) * 4096) : "memory");
            vote += (d > 90) == (r & 1) ? 1 : -1;
        }
        const uint32_t side = __shfl_sync(0xffffffffu, vote, 0) > 0;
        if (lane == 0) { sts32(sbase + SM_MISC + 4, side); mbar_arrive(bar_side); }
        while ((int)(now_ns() - (t0 + p.t_fill)) < 0) __nanosleep(200);
        st1(slot[0], SENT); st1(slot[1], SENT); st4(slot[2], SENT, SENT, SENT, SENT);
        uint32_t ack = SENT;
#pragma unroll
        for (int i = 0; i < 3; i++) { uint32_t v; asm volatile("atom.relaxed.gpu.global.exch.b32 %0, [%1], -1;" : "=r"(v) : "l"(slot[i]) : "memory"); ack &= v; }
        if (__any_sync(0xffffffffu, ack != SENT)) __trap();
        if (lane == 0) st1(p.sc->ready + b, tag);
        const uint32_t t2 = now_ns() + 1500;
        while (true) {
            do __nanosleep(200); while ((int)(now_ns() - t2) < 0);
            const uint4 e = ld4(p.sc->ready + lane * 4);
            if (__all_sync(0xffffffffu, e.x == tag && e.y == tag && e.z == tag && e.w == tag)) break;
            if (++n > SPIN_LIMIT) __trap();
        }
        if (lane == 0) {
            mbar_arrive(bar_rdy);
            if (b == 0) p.sc->epoch = tag;
        }
        unsigned char* hdst = p.xa + (hoff + (side ^ 1) * 4096 + (lane >> 4) * 512 + (lane & 15) * 4);
        unsigned char* hdst2 = p.xa + (hoff + side * 4096 + (lane >> 4) * 512 + (lane & 15) * 4);
        unsigned char* adst = p.xa + (aoff + (lane >> 4) * 4096 + (lane & 15) * 2);
        __nv_bfloat16* odst = p.out + u2 * 16 + (lane & 15);
        uint32_t r0 = sbase + SM_RED + lane * 48, r1 = sbase + SM_RED + (lane & 15) * 48;
        uint32_t res;
        asm volatile("ld.global.nc.u16 %0, [%1];" : "=r"(res) : "l"(p.x + u2 * 16 + (lane & 15)));
        pin(hdst); pin(hdst2); pin(adst); pin(odst); pin(r0); pin(r1);
        {
            uint32_t ro = sbase + SM_RO + l24 * 160;
            pin(ro);
            asm volatile("bar.sync 5, 224;" ::: "memory");
            const uint32_t v = pack_bf(sum8(ro + 80) + sum8(ro + 112), sum8(ro) + sum8(ro + 32));
            st1(slot[0], v); st1(slot[1], v);
        }
        if (has_wo) {
            fin_sync<3>();
            const uint32_t v = in_word(sum8(r0));
            st1(hdst, v); st1(hdst2, v);
        }
        if (has_f1) {
            fin_sync<4>();
            float mean_b, inv_den;
            ln_finish(sum8(sbase + SM_LN), sum8(sbase + SM_LN + 32), mean_b, inv_den);
            const float gr = fmaf(-mean_b, sum8(r1 + 48 * 48), sum8(r1 + 32 * 48)) * inv_den;
            mbar_wait_after(bar_up, r0, gr);
            const float gs = bfr(gr);
            const float up = bfr(fmaf(-mean_b, sum8(r1 + 80 * 48), sum8(r1 + 64 * 48)) * inv_den);
            st16(adst, pack_bf(0.f, silu_b(gs) * up));
            if (b == 0 && lane < 8) st1(p.sc->late + lane, 0);
        }
        if (has_f2) {
            mbar_wait(bar_tail + 8 * (NWP + NF1 + 3), 0);
            const unsigned char* hsrc = p.xa + ((lane >> 4) * (1 << 14) + side * 4096 + (u2 & 7) * 512 + (u2 >> 3) * 64 + (lane & 15) * 4);
            uint32_t e[3];
            do {
#pragma unroll
                for (int i = 0; i < 3; i++) e[i] = ld1(hsrc + xa_h(2 * i));
                if (++n > SPIN_LIMIT) __trap();
            } while (__any_sync(0xffffffffu, max(max(e[0], e[1]), e[2]) == SENT));
            float f[3];
#pragma unroll
            for (int i = 0; i < 3; i++) f[i] = __uint_as_float(e[i]) + __uint_as_float(__shfl_xor_sync(0xffffffffu, e[i], 16));
            res = add_bf2(res, pack_bf(0.f, (f[0] + f[1]) + f[2]));
            pin(res);
            fin_sync<6>();
            asm volatile("st.global.u16 [%0], %1;" ::"l"(odst), "h"((unsigned short)add_bf2(res, pack_bf(0.f, sum8(r1 + 96 * 48)))) : "memory");
        }
    } else {
        const int g = lane >> 2, t = lane & 3;
        uint2 xres;
        {
            uint32_t xr;
            uint2 xu[5];
            const char* xb = reinterpret_cast<const char*>(p.x);
            asm volatile("ld.global.nc.u16 %0, [%1];" : "=r"(xr) : "l"(xb + (min(warp, NQT - 1) * 128 + sp * 32 + lane) * 2));
#pragma unroll
            for (int i = 0; i < 5; i++) asm volatile("ld.global.nc.v2.u32 {%0, %1}, [%2];" : "=r"(xu[i].x), "=r"(xu[i].y) : "l"(xb + i * 256 + lane * 8));
            asm volatile("ld.global.nc.v2.u32 {%0, %1}, [%2];" : "=r"(xres.x), "=r"(xres.y) : "l"(xb + min(g, 4) * 256 + warp * 32 + t * 8));
            if (lane >= 20) xres.x = xres.y = 0;
            float s1 = 0.f, s2 = 0.f, mean_b, inv_den;
#pragma unroll
            for (int i = 0; i < 5; i++) { ln_acc(xu[i].x, s1, s2); ln_acc(xu[i].y, s1, s2); }
            ln_finish(warp_sum(s1), warp_sum(s2), mean_b, inv_den);
            sts16(sbase + SM_P + warp * 64 + ((lane >> 1 & 3) * 8 + (lane >> 3) * 2 + (lane & 1)) * 2, ln_apply2(xr, mean_b, inv_den));
            asm volatile("cp.async.wait_all;" ::: "memory");
            asm volatile("bar.sync 2, 512;" ::: "memory");
        }
        uint32_t va[3];
#pragma unroll
        for (int i = 0; i < 3; i++) {
            const int cc = 3 * warp + i, row = 3 * lane + (cc >> 3);
            va[i] = sbase + row * 128 + (((cc ^ row) & 7) << 4);
        }
        const uint32_t tag = lds32(sbase + SM_MISC);
        const int gi = g >= 3 ? g - 3 : g;
        const uint32_t t4 = (tag & 7) + 1;
        auto pdst = [&](int n) {
            return p.xa + ((xa_p(n, warp >> 1, b >> 4) ^ (n >= NHEAD - NLATE ? g >= 3 : warp >> 1 & 1) << 12) + (b & 15) * 192 + (warp & 1) * 96 + gi * 32 + t * 8);
        };

#pragma unroll 1
        for (int ph = 0; ph < 2; ph++) {
            if (ph == 1) {
                uint32_t ka[3];
#pragma unroll
                for (int j = 0; j < 3; j++) {
                    const int row = 3 * (lane & 15) + j;
                    ka[j] = sbase + row * 128 + ((((lane >> 4) ^ row) & 7) << 4) + warp * TILE_BYTES;
                }
                const uint32_t t16 = (tag & 0x7fff) + 1;
#pragma unroll 1
                for (int it = 0; it < 4; it++) {
                    uint4 qf[6];
#pragma unroll
                    for (int i = 0; i < 6; i++) qf[i] = lds128(sbase + SM_Q + warp * 1536 + it * 384 + t * 96 + i * 16);
                    const int slot = (it & 1) * 8 + warp;
                    const uint32_t so = (it & 1) * 8 * TILE_BYTES;
                    float c[2][2][4];
                    zero4(c[0][0]); zero4(c[0][1]); zero4(c[1][0]); zero4(c[1][1]);
                    mbar_wait(bar_full + 8 * slot, it >> 1);
#pragma unroll
                    for (int ks = 0; ks < 12; ks++) {
                        const uint32_t a = (ka[ks >> 2] + so) ^ ((ks & 3) << 5);
                        uint32_t f0[4], f1[4];
                        ldsm_x4(f0, a); ldsm_x4(f1, a + 16 * DH * 2);
                        const uint32_t b0 = ks & 1 ? qf[ks >> 1].z : qf[ks >> 1].x, b1 = ks & 1 ? qf[ks >> 1].w : qf[ks >> 1].y;
                        mma_bf16(c[0][ks & 1], f0, b0, b1); mma_bf16(c[1][ks & 1], f1, b0, b1);
                    }
                    if (lane == 0) mbar_arrive8(bar_empty + 8 * slot);
                    const float v = t & 2 ? (t & 1 ? c[1][0][2] + c[1][1][2] : c[1][0][0] + c[1][1][0]) : (t & 1 ? c[0][0][2] + c[0][1][2] : c[0][0][0] + c[0][1][0]);
                    const float sc = bfr(bfr(v) * 0.07216878364870322f), m = warp_max(sc), e = ex2((sc - m) * L2E), l = warp_sum(e);
                    sts16(sbase + SM_P + (it * 8 + warp) * 64 + ((g >> 1) * 8 + t * 2 + (g & 1)) * 2, pack_bf(0.f, e));
                    sts64(sbase + SM_ST + (it * 8 + warp) * 8, (__float_as_uint(m) & 0xffff0000u) | t16, __float_as_uint(l));
                }
                if (lane == 0) mbar_arrive(bar_stat);
                cons_sync();
            }
            float acc[3][4];
#pragma unroll
            for (int i = 0; i < 3; i++) zero4(acc[i]);
            const int nt = ph ? NKT : NQT, nr = min(head + (head >= NHEAD - NLATE ? p.rlast : p.rdelay), NKT - 1);
            uint32_t v0, v1;
#pragma unroll 1
            for (int n = 0; n < nt; n++) {
                const int slot = ph ? (n & (NSLOT - 1)) : QSLOT + n;
                const uint4 w = lds128(sbase + SM_P + n * 64 + t * 16);
                unsigned char* dst = pdst(n);
                if (ph) mbar_wait(bar_full + 8 * slot, (n >> 4) & 1);
                uint32_t f[3][4];
#pragma unroll
                for (int i = 0; i < 3; i++) ldsm_x4_t(f[i], va[i] + slot * TILE_BYTES);
#pragma unroll
                for (int i = 0; i < 3; i++) mma_bf16(acc[i], w.x, w.x, w.y, w.y, f[i][0], f[i][1]);
#pragma unroll
                for (int i = 0; i < 3; i++) mma_bf16(acc[i], w.z, w.z, w.w, w.w, f[i][2], f[i][3]);
                if (lane == 0) mbar_arrive(bar_empty + 8 * slot);
                v0 = (__float_as_uint(gi == 0 ? acc[0][0] : gi == 1 ? acc[1][0] : acc[2][0]) & ~15u) | t4;
                v1 = (__float_as_uint(gi == 0 ? acc[0][1] : gi == 1 ? acc[1][1] : acc[2][1]) & ~15u) | t4;
                if (!ph) continue;
                if (g < (n >= NHEAD - NLATE ? 6 : 3)) st2(dst, v0, v1);
#pragma unroll
                for (int i = 0; i < 3; i++) zero4(acc[i]);
                if (n >= 22 && n < 22 + NLATE && g < 6) st2(pdst(n + NHEAD - NLATE - 22), 0, 0);
                if (n == nr && tid == 0) mbar_arrive(bar_go);
            }
            if (ph == 1) break;
            if (g < 3) st2(p.sc->qbuf + b * 96 + warp * 12 + lane, v0, v1);
            {
                uint64_t e[6][2];
                uint32_t n = 0;
                bool ok;
#pragma unroll 1
                do {
                    do __nanosleep(100); while ((int)(now_ns() - (t0 + p.t_q2)) < 0);
                    ok = true;
#pragma unroll
                    for (int i = 0; i < 6; i++) pkt_ld2(reinterpret_cast<const uint4*>(p.sc->qall) + warp * 192 + i * 32 + lane, e[i][0], e[i][1]);
#pragma unroll
                    for (int i = 0; i < 6; i++) ok = ok && tag_ok(e[i][0], tag) && tag_ok(e[i][1], tag);
                    if (++n > SPIN_LIMIT) __trap();
                } while (!__all_sync(0xffffffffu, ok));
#pragma unroll
                for (int i = 0; i < 6; i++) sts64(sbase + SM_Q + warp * 1536 + i * 256 + lane * 8, (uint32_t)e[i][0], (uint32_t)e[i][1]);
            }
            cons_sync();
        }
        mbar_wait(bar_rdy, 0);
        const uint32_t side = lds32(sbase + SM_MISC + 4) * 4096;
        const unsigned char* osrc = p.xa + (xa_o(kg * 8 + warp, 0) + side + lane * 8);
        const int r16 = (lane & 7) + ((lane >> 4) << 3), mi = lane >> 3 & 1;
        const uint32_t f32 = sbase + r16 * 32 + ((mi ^ (lane >> 2 & 1)) << 4);
        uint32_t rdst = sbase + SM_RED + (t * 8 + g) * 48 + warp * 4;
        uint32_t bl = sbase + SM_BC + warp * 512 + t * 80, bs = bl + g * 8;
        uint32_t hl = g < 4 ? bl : sbase + SM_ONE;
        uint32_t w1a = f32 + SM_W1 + warp * 512, w2a = f32 + SM_W2 + warp * 1024;
        uint32_t lnd = lane < 2 ? sbase + SM_LN + lane * 32 + warp * 4 : sbase + SM_BC + warp * 512 + 384 + lane * 4;
        const unsigned char* hs = p.xa + (side + warp * 512 + lane * 16);
        const unsigned char* as = p.xa + (XA_A + side + warp * 384 + min(lane, 23) * 16);
        uint32_t al = sbase + SM_BC + warp * 512 + t * 16, at = sbase + SM_BC + warp * 512 + lane * 16;
        uint32_t fl = role, ln = lane;
        pin_u(fl); pin(ln);
        const bool f1 = fl & 2, f2 = fl & 4, odd = ln & 1, first = ln == 0;
        constexpr uint32_t b2 = bar_tail + 8 * (NWP + NF1);
        pin(rdst); pin(bs); pin(hl); pin(w1a); pin(w2a); pin(lnd); pin(hs); pin(as); pin(al); pin(at);
#define F_(i, c) __uint_as_float(e[i].c)
        if (has_wo) {
            uint4 e[4];
            uint32_t n = 0;
            uint2 o;
            const uint32_t wa = sbase + (warp * 16 + r16) * 64 + ((mi ^ (r16 >> 1 & 3)) << 4), wb = wa ^ 32;
            float c0[4], c1[4];
            zero4(c0); zero4(c1);
            mbar_wait(bar_tail + 8 * 2, 0);
            uint32_t miss = ~0u;
#pragma unroll
            for (int h = 0; h < 2; h++) {
                const uint32_t need = h ? ~0u : (1u << 4 * 6) - 1;
                if (miss & need) {
#pragma unroll 1
                    do {
                        o = ld2(osrc);
                        if (++n > SPIN_LIMIT) __trap();
                        miss = __ballot_sync(0xffffffffu, max(o.x, o.y) == SENT);
                    } while (miss & need);
                    sts64(bs, o.x, o.y);
                    __syncwarp();
#pragma unroll
                    for (int i = h ? 6 / 2 : 0; i < 4; i++) e[i] = lds128(bl + i * 16);
                }
#pragma unroll
                for (int j = h ? 6 : 0; j < (h ? NWP : 6); j++) {
                    mbar_wait(bar_tail + 8 * j, 0);
                    uint32_t f0[4], f1[4];
                    ldsm_x4_t(f0, wa + j * 8192); ldsm_x4_t(f1, wb + j * 8192);
                    const uint32_t b0 = j & 1 ? e[j >> 1].z : e[j >> 1].x, b1 = j & 1 ? e[j >> 1].w : e[j >> 1].y;
                    mma_bf16(c0, f0, b0, b1); mma_bf16(c1, f1, b0, b1);
                }
            }
            sts32(rdst, t & 2 ? (t & 1 ? c1[2] : c1[0]) : (t & 1 ? c0[2] : c0[0]));
            fin_arrive<3>();
        }
        if (f1) {
            constexpr uint32_t b1 = bar_tail + 8 * NWP;
            uint32_t a1[5][4], a3[5][4];
            uint4 e[NG];
#pragma unroll
            for (int i = 0; i < NG; i++) e[i].x = e[i].y = e[i].z = e[i].w = 0;
            uint32_t got = 0, n = 0;
#pragma unroll
            for (int i = 0; i < NB; i++) a3[i][0] = a3[i][1] = a3[i][2] = a3[i][3] = 0;
            mbar_wait(b1, 0);
#pragma unroll
            for (int i = 0; i < NG; i++) ld4p(hs + xa_h(i), e[i], lane < 20);
            mbar_wait(b1 + 8, 0);
#pragma unroll
            for (int i = 0; i < 5; i++) ldsm_x4_t(a1[i], w1a + i * 4096);
            uint4 hb0, hb1;
            uint2 hb2;
            float sv[4];
#pragma unroll 1
            while (true) {
#define S_(f, c) (((f(e[0].c) + f(e[1].c)) + (f(e[2].c) + f(e[3].c))) + (f(e[4].c) + f(e[5].c)))
                const float sx = S_(__uint_as_float, x), sy = S_(__uint_as_float, y), sz = S_(__uint_as_float, z), sw = S_(__uint_as_float, w), sa = (sx + sy) + (sz + sw);
#undef S_
                const uint32_t h0 = add_bf2(xres.x, pack_bf(sy, sx)), h1 = add_bf2(xres.y, pack_bf(sw, sz));
                sts64(bs, h0, h1);
                __syncwarp();
                hb0 = lds128(hl); hb1 = lds128(hl + 16); hb2 = lds64(hl + 32);
                const float a = bf_lo(h0), b = bf_hi(h0), c = bf_lo(h1), d = bf_hi(h1);
                const float s1 = (a + b) + (c + d), s2 = fmaf(a, a, b * b) + fmaf(c, c, d * d);
                sv[0] = odd ? s2 : s1;
                sv[1] = __shfl_xor_sync(0xffffffffu, odd ? s1 : s2, 1);
                sv[2] = __shfl_xor_sync(0xffffffffu, sv[0], 2);
                sv[3] = __shfl_xor_sync(0xffffffffu, odd ? s1 : s2, 3);
                bool miss = __any_sync(0xffffffffu, sa != sa);
                if (miss) {
                    miss = false;
#pragma unroll
                    for (int i = 0; i < NG; i++) {
                        const bool m = max4(e[i]) == SENT;
                        ld4p(hs + xa_h(i), e[i], m);
                        miss = miss || m;
                    }
                    ldsm_if<4096>(a3[0], a3[1], w1a + (SM_W3 - SM_W1), b1 + 16, got);
                    if (++n > SPIN_LIMIT) __trap();
                    miss = __any_sync(0xffffffffu, miss);
                }
                if (!miss) break;
            }
            float cg[3][4], cu[3][4];
#pragma unroll
            for (int i = 0; i < 3; i++) { zero4(cg[i]); zero4(cu[i]); }
            const uint32_t hb[5][2] = {{hb0.x, hb0.y}, {hb0.z, hb0.w}, {hb1.x, hb1.y}, {hb1.z, hb1.w}, {hb2.x, hb2.y}};
            const float st = (sv[0] + sv[1]) + (sv[2] + sv[3]);
#pragma unroll
            for (int i = 0; i < 4; i++) sv[i] = __shfl_down_sync(0xffffffffu, st, 4 * i + 4);
#pragma unroll
            for (int i = 0; i < 5; i++) mma_bf16(cg[i % 3], a1[i], hb[i][0], hb[i][1]);
            sts32(lnd, ((st + sv[0]) + sv[1]) + (sv[2] + sv[3]));
            sts32(rdst + 32 * 48, odd ? (cg[0][2] + cg[2][2]) + cg[1][2] : (cg[0][0] + cg[2][0]) + cg[1][0]);
            fin_arrive<4>();
            if (__any_sync(0xffffffffu, !got)) {
                mbar_wait(b1 + 16, 0);
#pragma unroll
                for (int i = 0; i < NB; i++) ldsm_x4_t(a3[i], w1a + (SM_W3 - SM_W1) + i * 4096);
            }
            mbar_wait(b1 + 24, 0);
#pragma unroll
            for (int i = NB; i < 5; i++) ldsm_x4_t(a3[i], w1a + (SM_W3 - SM_W1) + i * 4096);
#pragma unroll
            for (int i = 0; i < 5; i++) mma_bf16(cu[i % 3], a3[i], hb[i][0], hb[i][1]);
            sts32(rdst + 64 * 48, odd ? (cu[0][2] + cu[2][2]) + cu[1][2] : (cu[0][0] + cu[2][0]) + cu[1][0]);
            __syncwarp();
            if (first) mbar_arrive(bar_up);
        }
        if (f2) {
            uint32_t a2[NF2][2][4];
#pragma unroll
            for (int i = 0; i < 4; i++) a2[NF2 - 1][0][i] = a2[NF2 - 1][1][i] = 0;
#pragma unroll
            for (int j = 0; j < NF2 - 1; j++) {
                mbar_wait(b2 + 8 * j, 0);
                ldsm_x4_t(a2[j][0], w2a + j * 8192); ldsm_x4_t(a2[j][1], w2a + j * 8192 + 512);
            }
            uint32_t n = 0, got = 0;
            uint4 e[NF2];
#pragma unroll 1
            while (true) {
                const uint4 pa = ld4(as);
                if (++n > SPIN_LIMIT) __trap();
                sts128(at, pa);
                __syncwarp();
#pragma unroll
                for (int j = 0; j < 3; j++) e[j] = lds128v(al + j * 64);
                if (__all_sync(0xffffffffu, ok8(pa))) break;
            }
#pragma unroll
            for (int j = 3; j < NF2; j++) e[j] = lds128v(al + j * 64);
            ldsm_if<512>(a2[NF2 - 1][0], a2[NF2 - 1][1], w2a + (NF2 - 1) * 8192, b2 + 8 * (NF2 - 1), got);
            float c[6][4];
#pragma unroll
            for (int j = 0; j < 6; j++) zero4(c[j]);
#pragma unroll
            for (int j = 0; j < NF2; j++) { mma_bf16(c[(j % 3) * 2], a2[j][0], e[j].x, e[j].y); mma_bf16(c[(j % 3) * 2 + 1], a2[j][1], e[j].z, e[j].w); }
            if (__any_sync(0xffffffffu, !got)) {
                constexpr int j = NF2 - 1;
                mbar_wait(b2 + 8 * j, 0);
                ldsm_x4_t(a2[j][0], w2a + j * 8192); ldsm_x4_t(a2[j][1], w2a + j * 8192 + 512);
                mma_bf16(c[4], a2[j][0], e[j].x, e[j].y); mma_bf16(c[5], a2[j][1], e[j].z, e[j].w);
            }
            sts32(rdst + 96 * 48, odd ? (((c[0][2] + c[1][2]) + (c[2][2] + c[3][2])) + c[4][2]) + c[5][2] : (((c[0][0] + c[1][0]) + (c[2][0] + c[3][0])) + c[4][0]) + c[5][0]);
            fin_arrive<6>();
        }
#undef F_
    }
}

typedef CUresult (*EncodeTiledFn)(CUtensorMap*, CUtensorMapDataType, cuuint32_t, void*, const cuuint64_t*, const cuuint64_t*,
                                  const cuuint32_t*, const cuuint32_t*, CUtensorMapInterleave, CUtensorMapSwizzle,
                                  CUtensorMapL2promotion, CUtensorMapFloatOOBfill);

void make_map(EncodeTiledFn fn, CUtensorMap* tm, const void* w, const int (&d)[5], const int (&st)[4], const int (&bx)[5],
              CUtensorMapSwizzle sw, int promo) {
    cuuint64_t dims[5], strides[4];
    cuuint32_t box[5], estr[5];
    for (int i = 0; i < 5; i++) { dims[i] = (cuuint64_t)d[i]; box[i] = (cuuint32_t)bx[i]; estr[i] = 1; }
    for (int i = 0; i < 4; i++) strides[i] = (cuuint64_t)st[i];
    fn(tm, CU_TENSOR_MAP_DATA_TYPE_BFLOAT16, 5, const_cast<void*>(w), dims, strides, box, estr, CU_TENSOR_MAP_INTERLEAVE_NONE, sw,
       (CUtensorMapL2promotion)promo, CU_TENSOR_MAP_FLOAT_OOB_FILL_NONE);
}

enum { T_PER, T_LEAD, T_STAG, T_TD, T_PERO, T_F1D, T_PERF, T_F2, T_PER2, T_Q, T_PWO, T_PW13, T_PW2, T_TG, T_GA, T_TGA, T_TG0, T_SH, T_INFL, T_DZ, T_Q2, T_ST, T_RD, T_RL, T_PKV, T_N };
int g_tune[T_N] = {478, 1170, 4, 20, 285, 300, 109, 1391, 120, 4800, 2, 2, 2, 1520, 250, 600, 75, 15, 4, 30, 6200, 1800, 3, 1, 2};

}

extern "C" void kernel_launch(void* const* d_in, const int* in_sizes, int n_in, void* d_out, int out_size) {
    (void)in_sizes; (void)n_in; (void)out_size;
    static EncodeTiledFn encode = nullptr;
    static Scratch* scratch = nullptr;
    static unsigned char* xarea = nullptr;
    if (!encode) {
        void* sp = nullptr;
        cudaGetSymbolAddress(&sp, g_scratch);
        scratch = reinterpret_cast<Scratch*>(sp);
        cudaGetSymbolAddress(&sp, g_xarea);
        xarea = reinterpret_cast<unsigned char*>((reinterpret_cast<uintptr_t>(sp) + XA_ALIGN - 1) / XA_ALIGN * XA_ALIGN);
        void* fn = nullptr;
        cudaDriverEntryPointQueryResult st;
        cudaGetDriverEntryPoint("cuTensorMapEncodeTiled", &fn, cudaEnableDefault, &st);
        encode = reinterpret_cast<EncodeTiledFn>(fn);
        cudaFuncSetAttribute(fused_decode_kernel, cudaFuncAttributeMaxDynamicSharedMemorySize, SM_TOTAL);
        int dev = 0, khz = 0, bits = 0;
        cudaGetDevice(&dev);
        if (cudaDeviceGetAttribute(&khz, cudaDevAttrMemoryClockRate, dev) == cudaSuccess &&
            cudaDeviceGetAttribute(&bits, cudaDevAttrGlobalMemoryBusWidth, dev) == cudaSuccess && khz > 0 && bits > 0) {
            const double f = 2619000.0 * 5120.0 / ((double)khz * bits);
            for (int i : {T_PER, T_STAG, T_SH, T_PERO, T_PERF, T_F2, T_Q, T_Q2}) g_tune[i] = (int)(g_tune[i] * f + 0.5);
            if (f < 1.0) g_tune[T_INFL] = (int)(g_tune[T_INFL] / f + 0.5);
        }
        (void)cudaGetLastError();
    }
    const int* T = g_tune;
    KParams p;
    p.x = (const __nv_bfloat16*)d_in[0];
    p.wq = (const __nv_bfloat16*)d_in[3];
    p.out = (__nv_bfloat16*)d_out;
    p.sc = scratch;
    p.xa = xarea;
    p.per = T[T_PER];
    p.stag = T[T_STAG];
    p.t_k0 = (NQT + 1) * T[T_PER] - T[T_LEAD];
    {
        int t = p.t_k0 + 2 * NKT * T[T_PER] + T[T_STAG] * 3 / 2 + T[T_SH] * 31 / 2 + T[T_TD];
        for (int i = 0; i < NWP; i++, t += T[T_PERO]) p.item[i] = t;
        for (int i = 0, t1 = t + T[T_F1D]; i < NP1; i++, t1 += T[T_PERF]) p.item[NWP + i] = t1;
        for (int i = 0, t2 = t + T[T_F2]; i < NF2; i++, t2 += T[T_PER2]) p.item[NWP + NP1 + i] = t2;
        for (int i = NITEM; i < 32; i++) p.item[i] = 0;
    }
    p.target = T[T_TG]; p.t_q = T[T_Q]; p.t_q2 = T[T_Q2]; p.t_stat = T[T_ST];
    p.rdelay = T[T_RD]; p.rlast = T[T_RL];
    p.gain = T[T_GA] / 100.f; p.tgain = T[T_TGA] / 47800.f; p.tg0 = T[T_TG0] / 10.f; p.dz = T[T_DZ] / 10.f;
    p.stagh = T[T_SH]; p.infl = T[T_INFL]; p.t_fill = p.t_k0 + 59 * T[T_PER];
    for (int i = 0, nw = 0, n1 = 0, n2 = 0; i < NCTA; i++) {
        const int grp = i >> 2;
        const bool f2 = grp % 3 == 2, both = grp == 8 || grp == 23, wo = !both, f1 = !f2 || both;
        p.role[i] = (wo ? 1 | nw / 20 << 3 | nw % 20 << 6 : 0) | (f1 ? 2 | n1 << 11 : 0) | (f2 ? 4 | n2 << 18 : 0);
        nw += wo; n1 += f1; n2 += f2;
    }
    TMaps tm;
    constexpr int R1 = FF * 2, R2 = D_MODEL * 2;
    for (int i = 0; i < 2; i++)
        make_map(encode, &tm.k + i, d_in[1 + i], {64, 96, 1, 1, NHEAD * SK / 32}, {128, TILE_BYTES, TILE_BYTES, TILE_BYTES}, {64, 96, 1, 1, 1}, CU_TENSOR_MAP_SWIZZLE_128B, T[T_PKV]);
    make_map(encode, &tm.wo, d_in[4], {D_MODEL, 2, 4, 2, NHEAD * DH / 16}, {R2, 4 * R2, 2 * R2, 16 * R2}, {32, 2, 4, 2, 8}, CU_TENSOR_MAP_SWIZZLE_64B, T[T_PWO]);
    make_map(encode, &tm.w1, d_in[6], {FF, 2, 4, 2, D_MODEL / 16}, {R1, 4 * R1, 2 * R1, 16 * R1}, {16, 2, 4, 2, 8}, CU_TENSOR_MAP_SWIZZLE_32B, T[T_PW13]);
    make_map(encode, &tm.w3, d_in[7], {FF, 2, 4, 2, D_MODEL / 16}, {R1, 4 * R1, 2 * R1, 16 * R1}, {16, 2, 4, 2, 8}, CU_TENSOR_MAP_SWIZZLE_32B, T[T_PW13]);
    make_map(encode, &tm.w2, d_in[8], {D_MODEL, 2, 4, 4, FF / 32}, {R2, 8 * R2, 2 * R2, 32 * R2}, {16, 2, 4, 4, 8}, CU_TENSOR_MAP_SWIZZLE_32B, T[T_PW2]);
    fused_decode_kernel<<<NCTA, NTHREADS, SM_TOTAL, cudaStreamPerThread>>>(p, tm);
}
```

```cpp
#include <cuda_runtime.h>
#include <cuda_bf16.h>
#include <cuda.h>
#include <stdint.h>
#include <initializer_list>

namespace {

constexpr int D_MODEL = 640;
constexpr int NHEAD = 32;
constexpr int DH = 192;
constexpr int SK = 32768;
constexpr int WIN = 4096;
constexpr int FF = 1536;

constexpr int NCTA = 128;
constexpr int NTHREADS = 256 + 64 + 192;
constexpr int TILE_BYTES = 32 * DH * 2;
constexpr int NSLOT = 16;
constexpr int NKT = 32;
constexpr int NQT = 5;
constexpr int QSLOT = NSLOT - NQT;
constexpr int NG = 6;
constexpr int NWP = 8, NP1 = 10, NF2 = 6;
constexpr int NITEM = NWP + NP1 + NF2;
constexpr int NF1 = 4, NA = 3, NB = 2;
constexpr int NTAIL = NWP + NF1 + NF2;

constexpr uint32_t sbase = 1024;
constexpr int SM_W1 = NWP * 8192, SM_W3 = SM_W1 + 20480, SM_W2 = SM_W3 + 20480;
constexpr int SM_P = NSLOT * TILE_BYTES;
constexpr int SM_Q = SM_P + 2048;
constexpr int SM_RED = SM_Q + 3072;
constexpr int SM_BC = SM_RED + 128 * 48;
constexpr int SM_ONE = SM_BC + 4096;
constexpr int SM_ST = SM_ONE + 64;
constexpr int SM_WT = SM_ST + 256;
constexpr int SM_RO = SM_WT + 512;
constexpr int SM_LN = SM_RO + 48 * 80;
constexpr int SM_MISC = SM_LN + 64;
constexpr int SM_LATE = SM_MISC + 32;
constexpr int SM_BAR = SM_LATE + 32;
constexpr int SM_TOTAL = SM_BAR + 512;
static_assert(SM_TOTAL <= 232448, "shared memory");

struct __align__(128) Scratch {
    uint2 qbuf[NCTA * 96];
    uint2 mbuf[NCTA * NHEAD];
    uint32_t ready[NCTA];
    uint32_t late[32];
    uint32_t epoch;
};
__device__ Scratch g_scratch;
constexpr int XA_ALIGN = 2 << 20;
constexpr uint32_t SENT = 0xffffffffu;
__device__ unsigned char g_xarea[XA_ALIGN + (9 << 20)];
__device__ __forceinline__ uint32_t xa_o(uint32_t kw, uint32_t j) { return (kw >> 4) * 16384 + (kw & 15) * 256 + j * 32; }
constexpr int NLATE = 4, NPW = 6;
__device__ __forceinline__ uint32_t xa_p(uint32_t h, uint32_t q, uint32_t j) {
    const uint32_t k = ((NHEAD - 1 - h) * 4 + q) * 8 + j;
    return (1 << 20) + (2 * k + ((k ^ (k >> 3) ^ (k >> 4) ^ (k >> 6)) & 1)) * 4096;
}
__host__ __device__ constexpr uint32_t xa_h(uint32_t i) { return (1 << 18) + (i >> 2) * (3 << 16) + (i & 3) * (1 << 14); }
constexpr uint32_t XA_A = xa_h(NG);

constexpr uint32_t XA_PROBE = 1 << 13 | 1 << 19;

constexpr uint32_t SPIN_LIMIT = 1u << 22;

__device__ __forceinline__ uint32_t smem_u32(const void* p) { return (uint32_t)__cvta_generic_to_shared(p); }
__device__ __forceinline__ uint32_t now_ns() { uint64_t t; asm volatile("mov.u64 %0, %globaltimer;" : "=l"(t)); return (uint32_t)t; }
__device__ __forceinline__ void mbar_init(uint32_t bar, uint32_t cnt) {
    asm volatile("mbarrier.init.shared::cta.b64 [%0], %1;" ::"r"(bar), "r"(cnt) : "memory");
}
__device__ __forceinline__ void mbar_expect_tx(uint32_t bar, uint32_t bytes) {
    asm volatile("mbarrier.arrive.expect_tx.shared::cta.b64 _, [%0], %1;" ::"r"(bar), "r"(bytes) : "memory");
}
__device__ __forceinline__ void mbar_arrive(uint32_t bar) {
    asm volatile("mbarrier.arrive.shared::cta.b64 _, [%0];" ::"r"(bar) : "memory");
}
__device__ __forceinline__ void mbar_arrive8(uint32_t bar) {
    asm volatile("mbarrier.arrive.shared::cta.b64 _, [%0], 8;" ::"r"(bar) : "memory");
}
__device__ __forceinline__ bool mbar_test(uint32_t bar, uint32_t parity) {
    uint32_t ok;
    asm volatile("{\n.reg .pred p;\nmbarrier.test_wait.parity.shared::cta.b64 p, [%1], %2;\nselp.u32 %0, 1, 0, p;\n}"
                 : "=r"(ok) : "r"(bar), "r"(parity) : "memory");
    return ok;
}
__device__ __forceinline__ void mbar_wait(uint32_t bar, uint32_t parity) {
    asm volatile("{\n.reg .pred p;\nW_%=:\nmbarrier.try_wait.parity.shared::cta.b64 p, [%0], %1;\n@!p bra.uni W_%=;\n}" ::"r"(bar), "r"(parity) : "memory");
}
__device__ __forceinline__ void mbar_wait_after(uint32_t bar, uint32_t dump, float v) {
    uint32_t ok;
    asm volatile("{\n.reg .pred p;\nmbarrier.try_wait.parity.shared::cta.b64 p, [%1], 0;\nselp.u32 %0, 1, 0, p;\n}" : "=r"(ok) : "r"(bar) : "memory");
    asm volatile("st.volatile.shared.f32 [%0], %1;" ::"r"(dump), "f"(v) : "memory");
    if (__builtin_expect(!ok, 0)) mbar_wait(bar, 0);
}
__device__ __forceinline__ void tma_load_at(uint32_t when, uint32_t dst, const CUtensorMap* tm, int c0, int c4, uint32_t bar, uint64_t pol) {
    asm volatile("{\n.reg .pred p, e;\n.reg .b64 t;\n.reg .b32 lo, hi;\nelect.sync _|e, -1;\n"
                 "W_%=:\nmov.u64 t, %globaltimer;\nmov.b64 {lo, hi}, t;\nsub.u32 lo, lo, %7;\nsetp.lt.s32 p, lo, 0;\n@p bra.uni W_%=;\n"
                 "@e cp.async.bulk.tensor.5d.shared::cluster.global.mbarrier::complete_tx::bytes.L2::cache_hint [%0], [%1, {%3, %5, %5, %5, %4}], [%2], %6;\n}"
                 ::"r"(dst), "l"(reinterpret_cast<uint64_t>(tm)), "r"(bar), "r"(c0), "r"(c4), "r"(0), "l"(pol), "r"(when) : "memory");
}
__device__ __forceinline__ void pin(uint32_t& v) { asm volatile("shfl.sync.bfly.b32 %0, %0, 0, 31, -1;" : "+r"(v) :: "memory"); }
__device__ __forceinline__ void pin_u(uint32_t& v) { asm volatile("shfl.sync.idx.b32 %0, %0, 0, 31, -1;" : "+r"(v) :: "memory"); }
template <class T> __device__ __forceinline__ void pin(T*& v) {
    asm volatile("{\n.reg .b32 a, b;\nmov.b64 {a, b}, %0;\nshfl.sync.bfly.b32 a, a, 0, 31, -1;\nshfl.sync.bfly.b32 b, b, 0, 31, -1;\nmov.b64 %0, {a, b};\n}" : "+l"(v) :: "memory");
}
__device__ __forceinline__ void sts16(uint32_t a, uint32_t v) { asm volatile("st.shared.u16 [%0], %1;" ::"r"(a), "h"((unsigned short)v) : "memory"); }
__device__ __forceinline__ void sts32(uint32_t a, float v) { asm volatile("st.shared.f32 [%0], %1;" ::"r"(a), "f"(v) : "memory"); }
__device__ __forceinline__ void sts32(uint32_t a, uint32_t v) { asm volatile("st.shared.u32 [%0], %1;" ::"r"(a), "r"(v) : "memory"); }
__device__ __forceinline__ void sts64(uint32_t a, uint32_t x, uint32_t y) { asm volatile("st.shared.v2.u32 [%0], {%1, %2};" ::"r"(a), "r"(x), "r"(y) : "memory"); }
__device__ __forceinline__ void sts128(uint32_t a, const uint4& v) { asm volatile("st.shared.v4.u32 [%0], {%1, %2, %3, %4};" ::"r"(a), "r"(v.x), "r"(v.y), "r"(v.z), "r"(v.w) : "memory"); }
__device__ __forceinline__ void cons_sync() { asm volatile("bar.sync 1, 256;" ::: "memory"); }
template <int ID> __device__ __forceinline__ void fin_arrive() { asm volatile("bar.arrive %0, 288;" ::"n"(ID) : "memory"); }
template <int ID> __device__ __forceinline__ void fin_sync() { asm volatile("bar.sync %0, 288;" ::"n"(ID) : "memory"); }

__device__ __forceinline__ uint4 lds128(uint32_t a) {
    uint4 v;
    asm volatile("ld.shared.v4.u32 {%0,%1,%2,%3}, [%4];" : "=r"(v.x), "=r"(v.y), "=r"(v.z), "=r"(v.w) : "r"(a) : "memory");
    return v;
}
__device__ __forceinline__ uint4 lds128v(uint32_t a) {
    uint4 v;
    asm volatile("ld.volatile.shared.v4.u32 {%0,%1,%2,%3}, [%4];" : "=r"(v.x), "=r"(v.y), "=r"(v.z), "=r"(v.w) : "r"(a) : "memory");
    return v;
}
__device__ __forceinline__ float4 lds128f(uint32_t a) {
    float4 v;
    asm volatile("ld.shared.v4.f32 {%0,%1,%2,%3}, [%4];" : "=f"(v.x), "=f"(v.y), "=f"(v.z), "=f"(v.w) : "r"(a) : "memory");
    return v;
}
__device__ __forceinline__ uint2 lds64(uint32_t a) {
    uint2 v;
    asm volatile("ld.shared.v2.u32 {%0,%1}, [%2];" : "=r"(v.x), "=r"(v.y) : "r"(a) : "memory");
    return v;
}
__device__ __forceinline__ uint32_t lds32(uint32_t a) {
    uint32_t v;
    asm volatile("ld.shared.u32 %0, [%1];" : "=r"(v) : "r"(a) : "memory");
    return v;
}
__device__ __forceinline__ float sum8(uint32_t a) {
    const float4 x = lds128f(a), y = lds128f(a + 16);
    return ((x.x + x.y) + (x.z + x.w)) + ((y.x + y.y) + (y.z + y.w));
}
__device__ __forceinline__ void ldsm_x4(uint32_t* r, uint32_t a) {
    asm volatile("ldmatrix.sync.aligned.m8n8.x4.shared.b16 {%0,%1,%2,%3}, [%4];"
                 : "=r"(r[0]), "=r"(r[1]), "=r"(r[2]), "=r"(r[3]) : "r"(a) : "memory");
}
__device__ __forceinline__ void ldsm_x4_t(uint32_t* r, uint32_t a) {
    asm volatile("ldmatrix.sync.aligned.m8n8.x4.trans.shared.b16 {%0,%1,%2,%3}, [%4];"
                 : "=r"(r[0]), "=r"(r[1]), "=r"(r[2]), "=r"(r[3]) : "r"(a) : "memory");
}
template <int STRIDE>
__device__ __forceinline__ void ldsm_if(uint32_t* r0, uint32_t* r1, uint32_t a, uint32_t bar, uint32_t& got) {
        asm volatile("{\n.reg .pred p, q;\nsetp.eq.u32 q, %8, 0;\nmbarrier.test_wait.parity.shared::cta.b64 p, [%10], 0;\nand.pred p, p, q;\n"
                     "@p ldmatrix.sync.aligned.m8n8.x4.trans.shared.b16 {%0,%1,%2,%3}, [%9];\n"
                     "@p ldmatrix.sync.aligned.m8n8.x4.trans.shared.b16 {%4,%5,%6,%7}, [%9+%11];\n@p mov.u32 %8, 1;\n}"
                     : "+r"(r0[0]), "+r"(r0[1]), "+r"(r0[2]), "+r"(r0[3]), "+r"(r1[0]), "+r"(r1[1]), "+r"(r1[2]), "+r"(r1[3]), "+r"(got)
                     : "r"(a), "r"(bar), "n"(STRIDE) : "memory");
}
__device__ __forceinline__ void mma_bf16(float* c, uint32_t a0, uint32_t a1, uint32_t a2, uint32_t a3, uint32_t b0, uint32_t b1) {
    asm volatile("mma.sync.aligned.m16n8k16.row.col.f32.bf16.bf16.f32 {%0,%1,%2,%3}, {%4,%5,%6,%7}, {%8,%9}, {%0,%1,%2,%3};"
                 : "+f"(c[0]), "+f"(c[1]), "+f"(c[2]), "+f"(c[3]) : "r"(a0), "r"(a1), "r"(a2), "r"(a3), "r"(b0), "r"(b1));
}
__device__ __forceinline__ void mma_bf16(float* c, const uint32_t* a, uint32_t b0, uint32_t b1) { mma_bf16(c, a[0], a[1], a[2], a[3], b0, b1); }
__device__ __forceinline__ void zero4(float* c) { c[0] = c[1] = c[2] = c[3] = 0.f; }
__device__ __forceinline__ float bf_lo(uint32_t u) { return __uint_as_float(u << 16); }
__device__ __forceinline__ float bf_hi(uint32_t u) { return __uint_as_float(u & 0xffff0000u); }
__device__ __forceinline__ uint32_t pack_bf(float hi, float lo) { uint32_t r; asm("cvt.rn.bf16x2.f32 %0, %1, %2;" : "=r"(r) : "f"(hi), "f"(lo)); return r; }
__device__ __forceinline__ uint32_t add_bf2(uint32_t a, uint32_t b) { uint32_t r; asm("add.rn.bf16x2 %0, %1, %2;" : "=r"(r) : "r"(a), "r"(b)); return r; }
__device__ __forceinline__ float bfr(float x) { return __uint_as_float(pack_bf(x, 0.f)); }

__device__ __forceinline__ uint32_t in_word(float v) { return __float_as_uint(v); }
__device__ __forceinline__ void st1(void* p, uint32_t v) {
    asm volatile("st.relaxed.gpu.global.u32 [%0], %1;" ::"l"(p), "r"(v) : "memory");
}
__device__ __forceinline__ void st16(void* p, uint32_t v) {
    asm volatile("st.relaxed.gpu.global.u16 [%0], %1;" ::"l"(p), "h"((unsigned short)v) : "memory");
}
__device__ __forceinline__ void st2(void* p, uint32_t a, uint32_t b) {
    asm volatile("st.relaxed.gpu.global.v2.u32 [%0], {%1, %2};" ::"l"(p), "r"(a), "r"(b) : "memory");
}
__device__ __forceinline__ void st4(void* p, uint32_t a, uint32_t b, uint32_t c, uint32_t d) {
    asm volatile("st.relaxed.gpu.global.v4.u32 [%0], {%1, %2, %3, %4};" ::"l"(p), "r"(a), "r"(b), "r"(c), "r"(d) : "memory");
}
__device__ __forceinline__ uint32_t ld1(const void* p) {
    uint32_t v;
    asm volatile("ld.relaxed.gpu.global.u32 %0, [%1];" : "=r"(v) : "l"(p) : "memory");
    return v;
}
__device__ __forceinline__ uint2 ld2(const void* p) {
    uint2 v;
    asm volatile("ld.relaxed.gpu.global.v2.u32 {%0, %1}, [%2];" : "=r"(v.x), "=r"(v.y) : "l"(p) : "memory");
    return v;
}
__device__ __forceinline__ uint4 ld4(const void* p) {
    uint4 v;
    asm volatile("ld.relaxed.gpu.global.v4.u32 {%0, %1, %2, %3}, [%4];" : "=r"(v.x), "=r"(v.y), "=r"(v.z), "=r"(v.w) : "l"(p) : "memory");
    return v;
}
__device__ __forceinline__ void ld4p(const void* p, uint4& v, bool on) {
    asm volatile("{\n.reg .pred q;\nsetp.ne.u32 q, %5, 0;\n@q ld.relaxed.gpu.global.v4.u32 {%0, %1, %2, %3}, [%4];\n}"
                 : "+r"(v.x), "+r"(v.y), "+r"(v.z), "+r"(v.w) : "l"(p), "r"((uint32_t)on) : "memory");
}
__device__ __forceinline__ bool ok8(const uint4& v) {
    const uint32_t m = __vimax3_u16x2(__vimax3_u16x2(v.x, v.y, v.z), v.w, v.w);
    return __vimax3_u16x2(m, m << 16, m >> 16) != SENT;
}
__device__ __forceinline__ uint32_t max4(const uint4& v) { return max(max(v.x, v.y), max(v.z, v.w)); }
__device__ __forceinline__ float val_of(uint64_t v) { return __uint_as_float((uint32_t)v); }

__device__ __forceinline__ float warp_sum(float v) {
#pragma unroll
    for (int o = 16; o > 0; o >>= 1) v += __shfl_xor_sync(0xffffffffu, v, o);
    return v;
}
__device__ __forceinline__ float warp_max(float v) {
#pragma unroll
    for (int o = 16; o > 0; o >>= 1) v = fmaxf(v, __shfl_xor_sync(0xffffffffu, v, o));
    return v;
}
__device__ __forceinline__ float sqrt_fast(float x) { float r; asm("sqrt.approx.ftz.f32 %0, %1;" : "=f"(r) : "f"(x)); return r; }
__device__ __forceinline__ float rcp_fast(float x) { float r; asm("rcp.approx.ftz.f32 %0, %1;" : "=f"(r) : "f"(x)); return r; }
__device__ __forceinline__ float ex2(float x) { float r; asm("ex2.approx.ftz.f32 %0, %1;" : "=f"(r) : "f"(x)); return r; }
constexpr float L2E = 1.4426950408889634f;
__device__ __forceinline__ void ln_finish(float s1, float s2, float& mean_b, float& inv_den) {
    const float mean = s1 * (1.0f / D_MODEL);
    const float var = fmaxf(fmaf(-mean, mean, s2 * (1.0f / D_MODEL)), 0.f);
    mean_b = bfr(mean);
    inv_den = rcp_fast(bfr(sqrt_fast(bfr(bfr(var) + 1e-5f))));
}
__device__ __forceinline__ uint32_t ln_apply2(uint32_t u, float mean_b, float inv_den) {
    const uint32_t d = pack_bf(bf_hi(u) - mean_b, bf_lo(u) - mean_b);
    return pack_bf(bf_hi(d) * inv_den, bf_lo(d) * inv_den);
}
__device__ __forceinline__ void ln_acc(uint32_t u, float& s1, float& s2) {
    const float a = bf_lo(u), b = bf_hi(u);
    s1 += a + b;
    s2 = fmaf(a, a, fmaf(b, b, s2));
}
__device__ __forceinline__ float silu_b(float g) { return bfr(__fdividef(g, 1.0f + ex2(-g * L2E))); }

struct KParams {
    const __nv_bfloat16* wq;
    const __nv_bfloat16* x;
    __nv_bfloat16* out;
    Scratch* sc;
    unsigned char* xa;
    int t_k0, per, stag, stagh;
    int target, infl;
    float dz, gain, tg0, tgain;
    int t_q, t_stat, t_fill;
    int rdelay, rlast;
    uint32_t item[32];
    uint32_t role[NCTA];
};
struct TMaps { CUtensorMap k, v, wo, w1, w3, w2; };

__global__ void __launch_bounds__(NTHREADS, 1)
fused_decode_kernel(const __grid_constant__ KParams p, const __grid_constant__ TMaps tm) {
    extern __shared__ __align__(1024) unsigned char smem[];
    const int tid = threadIdx.x;
    const int b = blockIdx.x;
    const int head = b >> 2, sp = b & 3;
    {
        const char* a = reinterpret_cast<const char*>(p.wq) + (uint32_t)((sp * 32 + (tid >> 2) + (tid >> 7) * 96) * (NHEAD * DH * 2) + head * (DH * 2) + (tid & 3) * 128);
        if (tid < 320) asm volatile("prefetch.global.L2 [%0];" ::"l"(a) : "memory");
    }
    if (tid < 256) {
        const uint32_t r = tid >> 3, ch = tid & 7;
        const char* src = reinterpret_cast<const char*>(p.wq) + ((sp * 32 + r) * (NHEAD * DH * 2) + head * (DH * 2) + ch * 16);
#pragma unroll
        for (int i = 0; i < NQT; i++) {
#pragma unroll
            for (int j = 0; j < 3; j++)
                asm volatile("cp.async.cg.shared.global [%0], [%1], 16;"
                             ::"r"(sbase + (QSLOT + i) * TILE_BYTES + (3 * r + j) * 128 + ((ch ^ ((3 * r + j) & 7)) << 4)),
                               "l"(src + (size_t)i * 128 * (NHEAD * DH * 2) + j * 128) : "memory");
        }
    }
    const uint32_t t0 = now_ns();
    const int warp = __shfl_sync(0xffffffffu, tid >> 5, 0), lane = tid & 31;
    const uint32_t role = p.role[b];
    const int kg = role >> 3 & 7, ng = role >> 6 & 31;
    const int u1 = role >> 11 & 127, u2 = role >> 18;
    const bool has_wo = role & 1, has_f1 = role & 2, has_f2 = role & 4;
    constexpr uint32_t bar_full = sbase + SM_BAR;
    constexpr uint32_t bar_empty = sbase + SM_BAR + 128;
    constexpr uint32_t bar_tail = sbase + SM_BAR + 256;
    constexpr uint32_t bar_rdy = bar_tail + 8 * NTAIL;
    constexpr uint32_t bar_side = bar_rdy + 8;
    constexpr uint32_t bar_wt = bar_side + 8;
    constexpr uint32_t bar_go = bar_side + 16;
    constexpr uint32_t bar_stat = bar_side + 24;
    constexpr uint32_t bar_up = bar_side + 32;

    if (warp == 8) {
        if (smem_u32(smem) != sbase) __trap();
        uint64_t pol;
        asm volatile("createpolicy.fractional.L2::evict_first.b64 %0, 1.0;" : "=l"(pol));
        sts32(sbase + SM_LATE + (lane & 7) * 4, 0u);
        if (lane == 0) {
#pragma unroll
            for (int i = 0; i < 32 + NTAIL + 6; i++)
                mbar_init(bar_full + 8 * i, (i >= 16 && i < 32) || i > 35 + NTAIL ? 8 : i == 32 + NWP ? NA : i == 33 + NWP ? 5 - NA : i == 34 + NWP ? NB : i == 35 + NWP ? 5 - NB : 1);
#pragma unroll
            for (int i = 0; i < 6; i++) asm volatile("prefetch.tensormap [%0];" ::"l"(reinterpret_cast<uint64_t>(&tm.k + i)) : "memory");
            asm volatile("fence.mbarrier_init.release.cluster;" ::: "memory");
        }
        __syncwarp();
        asm volatile("bar.arrive 2, 512;" ::: "memory");
        const uint32_t tu = __shfl_sync(0xffffffffu, t0, 0);
        if (b == 0 && lane < 8) st1(p.sc->late + lane, lane ? 0 : (tu & 0xffffffu) | 1u << 24);
        const int seg = (lane >= NWP) + (lane >= NWP + NP1), i = lane - (seg == 0 ? 0 : seg == 1 ? NWP : NWP + NP1);
        const bool todo = lane < NITEM && (role >> seg & 1);
        const uint32_t len = seg == 1 ? 4096 : 8192, dst = sbase + (seg == 0 ? 0 : seg == 1 ? SM_W1 : SM_W2) + i * len;
        const int w3 = seg == 1 && i >= 5;
        const uint32_t mi = seg == 2 ? 3 : seg + w3;
        const int c0 = seg == 0 ? ng * 32 : seg == 1 ? u1 * 16 : u2 * 16;
        const int c4 = (seg == 0 ? kg * 64 : w3 * -40) + i * 8;
        const uint32_t bar = bar_tail + 8 * (seg == 0 ? i : seg == 1 ? NWP + (i >= NA) + w3 + (i >= 5 + NB) : NWP + NF1 + i);
        const int tile0 = (SK - WIN) / 32 + b;
        uint32_t tk = tu + p.t_k0 + sp * p.stag + head * p.stagh, tw = tk, acc = 0;
        int slip = 0, base = 0, w = 0, d0 = 0;
        float a2 = 0.f, drift = 0.f;
#pragma unroll 1
        for (int n = 0; n < 2 * NKT; n++) {
            const int slot = n & (NSLOT - 1);
            mbar_wait(bar_empty + 8 * slot, (((n + NQT) >> 4) & 1) ^ 1);
            if (lane == 0) mbar_expect_tx(bar_full + 8 * slot, TILE_BYTES);
            bool more;
            do {
                const uint32_t t = now_ns();
                if (__all_sync(0xffffffffu, mbar_test(bar_full + 8 * (w & (NSLOT - 1)), (w >> 4) & 1))) {
                    acc += t - tw;
                    tw += p.per;
                    w++;
                    if ((w & 7) == 0) {
                        if (lane == 0) asm volatile("red.relaxed.gpu.global.add.u32 [%0], %1;" ::"l"(p.sc->late + (w >> 3)), "r"((1u << 24) + min(max(((int)acc >> 3) + d0, 0), 65535)) : "memory");
                        acc = 0;
                    }
                }
                more = __any_sync(0xffffffffu, (int)(t - tk) < slip - 60) || w <= n - p.infl;
            } while (more);
            tma_load_at(tk + slip, sbase + slot * TILE_BYTES, &tm.k + (n >> 5), 0, tile0 + (n & (NKT - 1)) * (SK / 32), bar_full + 8 * slot, pol);
            tk += p.per;
            if ((n & 7) == 5 && lane < 2)
                asm volatile("cp.async.cg.shared.global [%0], [%1], 16;" ::"r"(sbase + SM_LATE + lane * 16), "l"(p.sc->late + lane * 4) : "memory");
            const uint32_t org = lds32(sbase + SM_LATE);
            if (org) d0 = (int)((tu - org) << 8) >> 8;
            int k = n >> 3;
            uint32_t rep = lds32(sbase + SM_LATE + k * 4);
            const uint32_t rep0 = lds32(sbase + SM_LATE + max(k - 1, 0) * 4);
            if (!(rep >> 30)) { rep = rep0; k--; }
            if (rep >> 30) {
                const float a = (float)(rep & 0xffffffu) * rcp_fast((float)(rep >> 24));
                if (k <= 2) a2 = a; else drift = (a - a2) * rcp_fast((float)(8 * k - 16));
                if (fabsf(drift - 1.f) > 6.f) drift = 0.f;
                base = max((int)a - p.target - d0, -900);
                slip = base + (int)(fmaxf(drift - p.dz, 0.f) * p.gain * (float)(n + 5 - 8 * k));
            }
        }
        const uint32_t tn = tu + base + p.item[lane] + (int)(drift * fmaf(p.tgain, (float)(int)(p.item[lane] - p.item[0]), p.tg0));
        if (todo) mbar_expect_tx(bar, len);
        const uint32_t c04 = c0 | c4 << 16, db = dst | (bar - bar_tail) << 18 | mi << 28;
#pragma unroll 1
        for (uint32_t left = __ballot_sync(0xffffffffu, todo); left; left &= left - 1) {
            const int k = __ffs(left) - 1;
            const uint32_t kc = __shfl_sync(0xffffffffu, c04, k), kd = __shfl_sync(0xffffffffu, db, k), kt = __shfl_sync(0xffffffffu, tn, k);
            mbar_wait(bar_empty + 8 * (k < NWP ? 5 : 12), k < NWP);
            tma_load_at(kt, kd & 0x3ffff, &tm.wo + (kd >> 28), kc & 0xffff, kc >> 16, bar_tail + (kd >> 18 & 0x3ff), pol);
        }
    } else if (warp >= 10) {
        asm volatile("bar.sync 2, 512;" ::: "memory");
        const uint32_t t4 = (lds32(sbase + SM_MISC) & 7) + 1, id = tid - 320, sg = id / 12;
        while (!mbar_test(bar_wt, 0)) __nanosleep(500);
        const float4 wa = lds128f(sbase + SM_WT + sg * 32), wb = lds128f(sbase + SM_WT + sg * 32 + 16);
        const float wt[8] = {wa.x, wa.y, wa.z, wa.w, wb.x, wb.y, wb.z, wb.w};
        uint32_t sd = sp & 1;
        if (head >= NHEAD - NLATE) {
            while (!mbar_test(bar_side, 0)) __nanosleep(200);
            sd = lds32(sbase + SM_MISC + 4);
        }
        const uint32_t o0 = (xa_p(head, sp, 0) ^ sd << 12) + id * 16;
        const unsigned char* a0 = p.xa + o0;
        const unsigned char* a1 = p.xa + (o0 ^ 4096);
        uint32_t dst = sbase + SM_RO + (id - sg * 12) * 320 + sg * 4;
        pin(a0); pin(a1); pin(dst);
        mbar_wait(bar_go, 0);
        uint4 e[8];
#pragma unroll
        for (int j = 0; j < 8; j++) e[j] = ld4((j & 1 ? a1 : a0) + j * 8192);
        uint32_t k = 0;
        bool miss;
#pragma unroll 1
        do {
            miss = false;
#pragma unroll
            for (int j = 0; j < 8; j++) {
                const bool m = (((e[j].x ^ t4) | (e[j].y ^ t4) | (e[j].z ^ t4) | (e[j].w ^ t4)) & 15) != 0;
                ld4p((j & 1 ? a1 : a0) + j * 8192, e[j], m);
                miss = miss || m;
            }
            if (++k > SPIN_LIMIT) __trap();
        } while (__any_sync(0xffffffffu, miss));
        float o[4] = {0.f, 0.f, 0.f, 0.f};
#pragma unroll
        for (int j = 0; j < 8; j++) {
            o[0] = fmaf(wt[j], __uint_as_float(e[j].x ^ t4), o[0]); o[1] = fmaf(wt[j], __uint_as_float(e[j].y ^ t4), o[1]);
            o[2] = fmaf(wt[j], __uint_as_float(e[j].z ^ t4), o[2]); o[3] = fmaf(wt[j], __uint_as_float(e[j].w ^ t4), o[3]);
        }
#pragma unroll
        for (int i = 0; i < 4; i++) sts32(dst + i * 80, o[i]);
        asm volatile("bar.arrive 5, 224;" ::: "memory");
    } else if (warp == 9) {
        const uint32_t tag = ld1(&p.sc->epoch) + 1;
        const uint32_t aoff = XA_A + (u1 >> 1 & 7) * 384 + (u1 >> 4) * 64 + (u1 & 1) * 32, hoff = xa_h(kg) + (ng & 3) * 1024 + (ng >> 2) * 64;
        sts32(sbase + SM_ONE + (lane & 15) * 4, 0x3f803f80u);
        const uint32_t l24 = min(lane, 23), od = head * 12 + sp * 3 + (l24 >> 3);
        const uint32_t ooff = xa_o((od >> 6) * 8 + (od & 7), od >> 3 & 7);
        unsigned char* slot[3] = {p.xa + (ooff + (l24 & 7) * 4), p.xa + (ooff + (l24 & 7) * 4 + 4096),
                                  p.xa + (lane < 16 ? (has_wo ? hoff + (lane >> 3) * 4096 + (lane >> 2 & 1) * 512 + (lane & 3) * 16 : ooff) : has_f1 ? aoff + (lane >> 1 & 1) * 4096 + (lane & 1) * 16 : ooff)};
#pragma unroll
        for (int i = 0; i < 2; i++) st4(p.sc->qbuf + b * 96 + i * 32 + lane * 2, 0, 0, 0, 0);
        sts32(sbase + SM_MISC, tag);
        asm volatile("bar.sync 2, 512;" ::: "memory");
        uint32_t n = 0;
        {
            while (!mbar_test(bar_stat, 0)) __nanosleep(200);
            const uint2 st = lds64(sbase + SM_ST + lane * 8);
            asm volatile("st.relaxed.gpu.global.b64 [%0], %1;" ::"l"(p.sc->mbuf + b * NHEAD + lane), "l"((uint64_t)st.y << 32 | st.x) : "memory");
            const uint32_t t1 = now_ns() + p.t_stat, t16 = (tag & 0x7fff) + 1;
            uint64_t e[4];
            do {
                do __nanosleep(200); while ((int)(now_ns() - t1) < 0);
#pragma unroll
                for (int i = 0; i < 4; i++) asm volatile("ld.relaxed.gpu.global.b64 %0, [%1];" : "=l"(e[i]) : "l"(p.sc->mbuf + (lane + 32 * i) * NHEAD + head) : "memory");
#pragma unroll
                for (int i = 0; i < 4; i++) e[i] ^= t16;
                if (++n > SPIN_LIMIT) __trap();
            } while (__any_sync(0xffffffffu, (e[0] | e[1] | e[2] | e[3]) & 0xffff));
            const float M = warp_max(fmaxf(fmaxf(val_of(e[0]), val_of(e[1])), fmaxf(val_of(e[2]), val_of(e[3]))));
            float x[4], L = 0.f;
#pragma unroll
            for (int i = 0; i < 4; i++) { x[i] = ex2((val_of(e[i]) - M) * L2E); L = fmaf(x[i], val_of(e[i] >> 32), L); }
            L = rcp_fast(warp_sum(L));
#pragma unroll
            for (int i = 0; i < 4; i++) sts32(sbase + SM_WT + (lane & 15) * 32 + (lane >> 4) * 4 + i * 8, x[i] * L);
            __syncwarp();
            if (lane == 0) mbar_arrive(bar_wt);
        }
        unsigned char* pr = p.xa + (xa_h(b & 7) + XA_PROBE + (b >> 3) * 128 + lane * 4);
        st1(pr, SENT); st1(pr + 4096, SENT);
        int vote = 0;
#pragma unroll 1
        for (int r = 0; r < 9 && (!vote || (int)(now_ns() - (t0 + p.t_fill)) < -1000); r++) {
            __nanosleep(100);
            uint32_t d;
            asm volatile("{\n.reg .pred p, q;\n.reg .b32 a, b, c0, c1;\nmov.b32 c0, 0;\nmov.b32 c1, 0;\n"
                         "atom.relaxed.gpu.global.exch.b32 a, [%1], -1;\natom.relaxed.gpu.global.exch.b32 b, [%2], -1;\n"
                         "setp.eq.u32 p, a, -1;\n@p mov.u32 c0, %%clock;\nsetp.eq.u32 q, b, -1;\n@q mov.u32 c1, %%clock;\nsub.u32 %0, c1, c0;\n}"
                         : "=r"(d) : "l"(pr + (r & 1) * 4096), "l"(pr + (~r & 1) * 4096) : "memory");
            vote += (d > 90) == (r & 1) ? 1 : -1;
        }
        const uint32_t side = __shfl_sync(0xffffffffu, vote, 0) > 0;
        if (lane == 0) { sts32(sbase + SM_MISC + 4, side); mbar_arrive(bar_side); }
        while ((int)(now_ns() - (t0 + p.t_fill)) < 0) __nanosleep(200);
        st1(slot[0], SENT); st1(slot[1], SENT); st4(slot[2], SENT, SENT, SENT, SENT);
        uint32_t ack = SENT;
#pragma unroll
        for (int i = 0; i < 3; i++) { uint32_t v; asm volatile("atom.relaxed.gpu.global.exch.b32 %0, [%1], -1;" : "=r"(v) : "l"(slot[i]) : "memory"); ack &= v; }
        if (__any_sync(0xffffffffu, ack != SENT)) __trap();
        if (lane == 0) st1(p.sc->ready + b, tag);
        const uint32_t t2 = now_ns() + 1500;
        while (true) {
            do __nanosleep(200); while ((int)(now_ns() - t2) < 0);
            const uint4 e = ld4(p.sc->ready + lane * 4);
            if (__all_sync(0xffffffffu, e.x == tag && e.y == tag && e.z == tag && e.w == tag)) break;
            if (++n > SPIN_LIMIT) __trap();
        }
        if (lane == 0) {
            mbar_arrive(bar_rdy);
            if (b == 0) p.sc->epoch = tag;
        }
        unsigned char* hdst = p.xa + (hoff + (side ^ 1) * 4096 + (lane >> 4) * 512 + (lane & 15) * 4);
        unsigned char* hdst2 = p.xa + (hoff + side * 4096 + (lane >> 4) * 512 + (lane & 15) * 4);
        unsigned char* adst = p.xa + (aoff + (lane >> 4) * 4096 + (lane & 15) * 2);
        __nv_bfloat16* odst = p.out + u2 * 16 + (lane & 15);
        uint32_t r0 = sbase + SM_RED + lane * 48, r1 = sbase + SM_RED + (lane & 15) * 48;
        uint32_t res;
        asm volatile("ld.global.nc.u16 %0, [%1];" : "=r"(res) : "l"(p.x + u2 * 16 + (lane & 15)));
        pin(hdst); pin(hdst2); pin(adst); pin(odst); pin(r0); pin(r1);
        {
            uint32_t ro = sbase + SM_RO + l24 * 160;
            pin(ro);
            asm volatile("bar.sync 5, 224;" ::: "memory");
            const uint32_t v = pack_bf(sum8(ro + 80) + sum8(ro + 112), sum8(ro) + sum8(ro + 32));
            st1(slot[0], v); st1(slot[1], v);
        }
        if (has_wo) {
            fin_sync<3>();
            const uint32_t v = in_word(sum8(r0));
            st1(hdst, v); st1(hdst2, v);
        }
        if (has_f1) {
            fin_sync<4>();
            float mean_b, inv_den;
            ln_finish(sum8(sbase + SM_LN), sum8(sbase + SM_LN + 32), mean_b, inv_den);
            const float gr = fmaf(-mean_b, sum8(r1 + 48 * 48), sum8(r1 + 32 * 48)) * inv_den;
            mbar_wait_after(bar_up, r0, gr);
            const float gs = bfr(gr);
            const float up = bfr(fmaf(-mean_b, sum8(r1 + 80 * 48), sum8(r1 + 64 * 48)) * inv_den);
            st16(adst, pack_bf(0.f, silu_b(gs) * up));
            if (b == 0 && lane < 8) st1(p.sc->late + lane, 0);
        }
        if (has_f2) {
            mbar_wait(bar_tail + 8 * (NWP + NF1 + 3), 0);
            const unsigned char* hsrc = p.xa + ((lane >> 4) * (1 << 14) + side * 4096 + (u2 & 7) * 512 + (u2 >> 3) * 64 + (lane & 15) * 4);
            uint32_t e[3];
            do {
#pragma unroll
                for (int i = 0; i < 3; i++) e[i] = ld1(hsrc + xa_h(2 * i));
                if (++n > SPIN_LIMIT) __trap();
            } while (__any_sync(0xffffffffu, max(max(e[0], e[1]), e[2]) == SENT));
            float f[3];
#pragma unroll
            for (int i = 0; i < 3; i++) f[i] = __uint_as_float(e[i]) + __uint_as_float(__shfl_xor_sync(0xffffffffu, e[i], 16));
            res = add_bf2(res, pack_bf(0.f, (f[0] + f[1]) + f[2]));
            pin(res);
            fin_sync<6>();
            asm volatile("st.global.u16 [%0], %1;" ::"l"(odst), "h"((unsigned short)add_bf2(res, pack_bf(0.f, sum8(r1 + 96 * 48)))) : "memory");
        }
    } else {
        const int g = lane >> 2, t = lane & 3;
        uint2 xres;
        {
            uint32_t xr;
            uint2 xu[5];
            const char* xb = reinterpret_cast<const char*>(p.x);
            asm volatile("ld.global.nc.u16 %0, [%1];" : "=r"(xr) : "l"(xb + (min(warp, NQT - 1) * 128 + sp * 32 + lane) * 2));
#pragma unroll
            for (int i = 0; i < 5; i++) asm volatile("ld.global.nc.v2.u32 {%0, %1}, [%2];" : "=r"(xu[i].x), "=r"(xu[i].y) : "l"(xb + i * 256 + lane * 8));
            asm volatile("ld.global.nc.v2.u32 {%0, %1}, [%2];" : "=r"(xres.x), "=r"(xres.y) : "l"(xb + min(g, 4) * 256 + warp * 32 + t * 8));
            if (lane >= 20) xres.x = xres.y = 0;
            float s1 = 0.f, s2 = 0.f, mean_b, inv_den;
#pragma unroll
            for (int i = 0; i < 5; i++) { ln_acc(xu[i].x, s1, s2); ln_acc(xu[i].y, s1, s2); }
            ln_finish(warp_sum(s1), warp_sum(s2), mean_b, inv_den);
            sts16(sbase + SM_P + warp * 64 + ((lane >> 1 & 3) * 8 + (lane >> 3) * 2 + (lane & 1)) * 2, ln_apply2(xr, mean_b, inv_den));
            asm volatile("cp.async.wait_all;" ::: "memory");
            asm volatile("bar.sync 2, 512;" ::: "memory");
        }
        uint32_t va[3];
#pragma unroll
        for (int i = 0; i < 3; i++) {
            const int cc = 3 * warp + i, row = 3 * lane + (cc >> 3);
            va[i] = sbase + row * 128 + (((cc ^ row) & 7) << 4);
        }
        const uint32_t tag = lds32(sbase + SM_MISC);
        const int gi = g >= 3 ? g - 3 : g;
        const uint32_t t4 = (tag & 7) + 1;
        auto pdst = [&](int n) {
            return p.xa + ((xa_p(n, warp >> 1, b >> 4) ^ (n >= NHEAD - NLATE ? g >= 3 : warp >> 1 & 1) << 12) + (b & 15) * 192 + (warp & 1) * 96 + gi * 32 + t * 8);
        };

#pragma unroll 1
        for (int ph = 0; ph < 2; ph++) {
            if (ph == 1) {
                uint32_t ka[3];
#pragma unroll
                for (int j = 0; j < 3; j++) {
                    const int row = 3 * (lane & 15) + j;
                    ka[j] = sbase + row * 128 + ((((lane >> 4) ^ row) & 7) << 4) + warp * TILE_BYTES;
                }
                const uint32_t t16 = (tag & 0x7fff) + 1;
#pragma unroll 1
                for (int it = 0; it < 4; it++) {
                    {
                        const uint4* src = reinterpret_cast<const uint4*>(p.sc->qbuf) + (it * 8 + warp) * 192 + min(lane, 23);
                        uint4 e[8];
                        uint32_t n = 0, bad;
#pragma unroll 1
                        do {
                            while ((int)(now_ns() - (t0 + p.t_q)) < 0 || (n & 1)) { __nanosleep(100); n &= ~1u; }
                            bad = 0;
#pragma unroll
                            for (int i = 0; i < 8; i++) e[i] = ld4(src + i * 24);
#pragma unroll
                            for (int i = 0; i < 8; i++) { e[i].x ^= t4; e[i].y ^= t4; e[i].z ^= t4; e[i].w ^= t4; bad |= (e[i].x | e[i].y) | (e[i].z | e[i].w); }
                            n += 3;
                            if (n > SPIN_LIMIT) __trap();
                        } while (__any_sync(0xffffffffu, bad & 15));
#define S_(h, c) ((__uint_as_float(e[h].c) + __uint_as_float(e[h + 2].c)) + (__uint_as_float(e[h + 4].c) + __uint_as_float(e[h + 6].c)))
                        const uint32_t qa = sbase + SM_Q + warp * 384 + (min(lane, 23) & 1) * 192 + (min(lane, 23) >> 1) * 4;
#pragma unroll
                        for (int h = 0; h < 2; h++) { sts32(qa + h * 48, pack_bf(S_(h, y), S_(h, x))); sts32(qa + h * 48 + 96, pack_bf(S_(h, w), S_(h, z))); }
#undef S_
                        __syncwarp();
                    }
                    uint4 qf[6];
#pragma unroll
                    for (int i = 0; i < 6; i++) qf[i] = lds128(sbase + SM_Q + warp * 384 + t * 96 + i * 16);
                    const int slot = (it & 1) * 8 + warp;
                    const uint32_t so = (it & 1) * 8 * TILE_BYTES;
                    float c[2][2][4];
                    zero4(c[0][0]); zero4(c[0][1]); zero4(c[1][0]); zero4(c[1][1]);
                    mbar_wait(bar_full + 8 * slot, it >> 1);
#pragma unroll
                    for (int ks = 0; ks < 12; ks++) {
                        const uint32_t a = (ka[ks >> 2] + so) ^ ((ks & 3) << 5);
                        uint32_t f0[4], f1[4];
                        ldsm_x4(f0, a); ldsm_x4(f1, a + 16 * DH * 2);
                        const uint32_t b0 = ks & 1 ? qf[ks >> 1].z : qf[ks >> 1].x, b1 = ks & 1 ? qf[ks >> 1].w : qf[ks >> 1].y;
                        mma_bf16(c[0][ks & 1], f0, b0, b1); mma_bf16(c[1][ks & 1], f1, b0, b1);
                    }
                    if (lane == 0) mbar_arrive8(bar_empty + 8 * slot);
                    const float v = t & 2 ? (t & 1 ? c[1][0][2] + c[1][1][2] : c[1][0][0] + c[1][1][0]) : (t & 1 ? c[0][0][2] + c[0][1][2] : c[0][0][0] + c[0][1][0]);
                    const float sc = bfr(bfr(v) * 0.07216878364870322f), m = warp_max(sc), e = ex2((sc - m) * L2E), l = warp_sum(e);
                    sts16(sbase + SM_P + (it * 8 + warp) * 64 + ((g >> 1) * 8 + t * 2 + (g & 1)) * 2, pack_bf(0.f, e));
                    sts64(sbase + SM_ST + (it * 8 + warp) * 8, (__float_as_uint(m) & 0xffff0000u) | t16, __float_as_uint(l));
                }
                if (lane == 0) mbar_arrive(bar_stat);
#pragma unroll 1
                for (int n = 0; n < NPW; n++) if (g < 3) st2(pdst(n), 0, 0);
                cons_sync();
            }
            float acc[3][4];
#pragma unroll
            for (int i = 0; i < 3; i++) zero4(acc[i]);
            const int nt = ph ? NKT : NQT, nr = min(head + (head >= NHEAD - NLATE ? p.rlast : p.rdelay), NKT - 1);
            uint32_t v0, v1;
#pragma unroll 1
            for (int n = 0; n < nt; n++) {
                const int slot = ph ? (n & (NSLOT - 1)) : QSLOT + n;
                const uint4 w = lds128(sbase + SM_P + n * 64 + t * 16);
                unsigned char* dst = pdst(n);
                if (ph) mbar_wait(bar_full + 8 * slot, (n >> 4) & 1);
                uint32_t f[3][4];
#pragma unroll
                for (int i = 0; i < 3; i++) ldsm_x4_t(f[i], va[i] + slot * TILE_BYTES);
#pragma unroll
                for (int i = 0; i < 3; i++) mma_bf16(acc[i], w.x, w.x, w.y, w.y, f[i][0], f[i][1]);
#pragma unroll
                for (int i = 0; i < 3; i++) mma_bf16(acc[i], w.z, w.z, w.w, w.w, f[i][2], f[i][3]);
                if (lane == 0) mbar_arrive(bar_empty + 8 * slot);
                v0 = (__float_as_uint(gi == 0 ? acc[0][0] : gi == 1 ? acc[1][0] : acc[2][0]) & ~15u) | t4;
                v1 = (__float_as_uint(gi == 0 ? acc[0][1] : gi == 1 ? acc[1][1] : acc[2][1]) & ~15u) | t4;
                if (!ph) continue;
                if (g < (n >= NHEAD - NLATE ? 6 : 3)) st2(dst, v0, v1);
#pragma unroll
                for (int i = 0; i < 3; i++) zero4(acc[i]);
                if (n + NPW < NHEAD && g < (n + NPW >= NHEAD - NLATE ? 6 : 3)) st2(pdst(n + NPW), 0, 0);
                if (n == nr && tid == 0) mbar_arrive(bar_go);
            }
            if (ph == 1) break;
            if (g < 3) st2(p.sc->qbuf + b * 96 + warp * 12 + lane, v0, v1);
            cons_sync();
        }
        mbar_wait(bar_rdy, 0);
        const uint32_t side = lds32(sbase + SM_MISC + 4) * 4096;
        const unsigned char* osrc = p.xa + (xa_o(kg * 8 + warp, 0) + side + lane * 8);
        const int r16 = (lane & 7) + ((lane >> 4) << 3), mi = lane >> 3 & 1;
        const uint32_t f32 = sbase + r16 * 32 + ((mi ^ (lane >> 2 & 1)) << 4);
        uint32_t rdst = sbase + SM_RED + (t * 8 + g) * 48 + warp * 4;
        uint32_t bl = sbase + SM_BC + warp * 512 + t * 80, bs = bl + g * 8;
        uint32_t hl = g < 4 ? bl : sbase + SM_ONE;
        uint32_t w1a = f32 + SM_W1 + warp * 512, w2a = f32 + SM_W2 + warp * 1024;
        uint32_t lnd = lane < 2 ? sbase + SM_LN + lane * 32 + warp * 4 : sbase + SM_BC + warp * 512 + 384 + lane * 4;
        const unsigned char* hs = p.xa + (side + warp * 512 + lane * 16);
        const unsigned char* as = p.xa + (XA_A + side + warp * 384 + min(lane, 23) * 16);
        uint32_t al = sbase + SM_BC + warp * 512 + t * 16, at = sbase + SM_BC + warp * 512 + lane * 16;
        uint32_t fl = role, ln = lane;
        pin_u(fl); pin(ln);
        const bool f1 = fl & 2, f2 = fl & 4, odd = ln & 1, first = ln == 0;
        constexpr uint32_t b2 = bar_tail + 8 * (NWP + NF1);
        pin(rdst); pin(bs); pin(hl); pin(w1a); pin(w2a); pin(lnd); pin(hs); pin(as); pin(al); pin(at);
#define F_(i, c) __uint_as_float(e[i].c)
        if (has_wo) {
            uint4 e[4];
            uint32_t n = 0;
            uint2 o;
            const uint32_t wa = sbase + (warp * 16 + r16) * 64 + ((mi ^ (r16 >> 1 & 3)) << 4), wb = wa ^ 32;
            float c0[4], c1[4];
            zero4(c0); zero4(c1);
            mbar_wait(bar_tail + 8 * 2, 0);
            uint32_t miss = ~0u;
#pragma unroll
            for (int h = 0; h < 2; h++) {
                const uint32_t need = h ? ~0u : (1u << 4 * 6) - 1;
                if (miss & need) {
#pragma unroll 1
                    do {
                        o = ld2(osrc);
                        if (++n > SPIN_LIMIT) __trap();
                        miss = __ballot_sync(0xffffffffu, max(o.x, o.y) == SENT);
                    } while (miss & need);
                    sts64(bs, o.x, o.y);
                    __syncwarp();
#pragma unroll
                    for (int i = h ? 6 / 2 : 0; i < 4; i++) e[i] = lds128(bl + i * 16);
                }
#pragma unroll
                for (int j = h ? 6 : 0; j < (h ? NWP : 6); j++) {
                    mbar_wait(bar_tail + 8 * j, 0);
                    uint32_t f0[4], f1[4];
                    ldsm_x4_t(f0, wa + j * 8192); ldsm_x4_t(f1, wb + j * 8192);
                    const uint32_t b0 = j & 1 ? e[j >> 1].z : e[j >> 1].x, b1 = j & 1 ? e[j >> 1].w : e[j >> 1].y;
                    mma_bf16(c0, f0, b0, b1); mma_bf16(c1, f1, b0, b1);
                }
            }
            sts32(rdst, t & 2 ? (t & 1 ? c1[2] : c1[0]) : (t & 1 ? c0[2] : c0[0]));
            fin_arrive<3>();
        }
        if (f1) {
            constexpr uint32_t b1 = bar_tail + 8 * NWP;
            uint32_t a1[5][4], a3[5][4];
            uint4 e[NG];
#pragma unroll
            for (int i = 0; i < NG; i++) e[i].x = e[i].y = e[i].z = e[i].w = 0;
            uint32_t got = 0, n = 0;
#pragma unroll
            for (int i = 0; i < NB; i++) a3[i][0] = a3[i][1] = a3[i][2] = a3[i][3] = 0;
            mbar_wait(b1, 0);
#pragma unroll
            for (int i = 0; i < NG; i++) ld4p(hs + xa_h(i), e[i], lane < 20);
            mbar_wait(b1 + 8, 0);
#pragma unroll
            for (int i = 0; i < 5; i++) ldsm_x4_t(a1[i], w1a + i * 4096);
            uint4 hb0, hb1;
            uint2 hb2;
            float sv[4];
#pragma unroll 1
            while (true) {
#define S_(f, c) (((f(e[0].c) + f(e[1].c)) + (f(e[2].c) + f(e[3].c))) + (f(e[4].c) + f(e[5].c)))
                const float sx = S_(__uint_as_float, x), sy = S_(__uint_as_float, y), sz = S_(__uint_as_float, z), sw = S_(__uint_as_float, w), sa = (sx + sy) + (sz + sw);
#undef S_
                const uint32_t h0 = add_bf2(xres.x, pack_bf(sy, sx)), h1 = add_bf2(xres.y, pack_bf(sw, sz));
                sts64(bs, h0, h1);
                __syncwarp();
                hb0 = lds128(hl); hb1 = lds128(hl + 16); hb2 = lds64(hl + 32);
                const float a = bf_lo(h0), b = bf_hi(h0), c = bf_lo(h1), d = bf_hi(h1);
                const float s1 = (a + b) + (c + d), s2 = fmaf(a, a, b * b) + fmaf(c, c, d * d);
                sv[0] = odd ? s2 : s1;
                sv[1] = __shfl_xor_sync(0xffffffffu, odd ? s1 : s2, 1);
                sv[2] = __shfl_xor_sync(0xffffffffu, sv[0], 2);
                sv[3] = __shfl_xor_sync(0xffffffffu, odd ? s1 : s2, 3);
                bool miss = __any_sync(0xffffffffu, sa != sa);
                if (miss) {
                    miss = false;
#pragma unroll
                    for (int i = 0; i < NG; i++) {
                        const bool m = max4(e[i]) == SENT;
                        ld4p(hs + xa_h(i), e[i], m);
                        miss = miss || m;
                    }
                    ldsm_if<4096>(a3[0], a3[1], w1a + (SM_W3 - SM_W1), b1 + 16, got);
                    if (++n > SPIN_LIMIT) __trap();
                    miss = __any_sync(0xffffffffu, miss);
                }
                if (!miss) break;
            }
            float cg[3][4], cu[3][4];
#pragma unroll
            for (int i = 0; i < 3; i++) { zero4(cg[i]); zero4(cu[i]); }
            const uint32_t hb[5][2] = {{hb0.x, hb0.y}, {hb0.z, hb0.w}, {hb1.x, hb1.y}, {hb1.z, hb1.w}, {hb2.x, hb2.y}};
            const float st = (sv[0] + sv[1]) + (sv[2] + sv[3]);
#pragma unroll
            for (int i = 0; i < 4; i++) sv[i] = __shfl_down_sync(0xffffffffu, st, 4 * i + 4);
#pragma unroll
            for (int i = 0; i < 5; i++) mma_bf16(cg[i % 3], a1[i], hb[i][0], hb[i][1]);
            sts32(lnd, ((st + sv[0]) + sv[1]) + (sv[2] + sv[3]));
            sts32(rdst + 32 * 48, odd ? (cg[0][2] + cg[2][2]) + cg[1][2] : (cg[0][0] + cg[2][0]) + cg[1][0]);
            fin_arrive<4>();
            if (__any_sync(0xffffffffu, !got)) {
                mbar_wait(b1 + 16, 0);
#pragma unroll
                for (int i = 0; i < NB; i++) ldsm_x4_t(a3[i], w1a + (SM_W3 - SM_W1) + i * 4096);
            }
            mbar_wait(b1 + 24, 0);
#pragma unroll
            for (int i = NB; i < 5; i++) ldsm_x4_t(a3[i], w1a + (SM_W3 - SM_W1) + i * 4096);
#pragma unroll
            for (int i = 0; i < 5; i++) mma_bf16(cu[i % 3], a3[i], hb[i][0], hb[i][1]);
            sts32(rdst + 64 * 48, odd ? (cu[0][2] + cu[2][2]) + cu[1][2] : (cu[0][0] + cu[2][0]) + cu[1][0]);
            __syncwarp();
            if (first) mbar_arrive(bar_up);
        }
        if (f2) {
            uint32_t a2[NF2][2][4];
#pragma unroll
            for (int i = 0; i < 4; i++) a2[NF2 - 1][0][i] = a2[NF2 - 1][1][i] = 0;
#pragma unroll
            for (int j = 0; j < NF2 - 1; j++) {
                mbar_wait(b2 + 8 * j, 0);
                ldsm_x4_t(a2[j][0], w2a + j * 8192); ldsm_x4_t(a2[j][1], w2a + j * 8192 + 512);
            }
            uint32_t n = 0, got = 0;
            uint4 e[NF2];
#pragma unroll 1
            while (true) {
                const uint4 pa = ld4(as);
                if (++n > SPIN_LIMIT) __trap();
                sts128(at, pa);
                __syncwarp();
#pragma unroll
                for (int j = 0; j < 3; j++) e[j] = lds128v(al + j * 64);
                if (__all_sync(0xffffffffu, ok8(pa))) break;
            }
#pragma unroll
            for (int j = 3; j < NF2; j++) e[j] = lds128v(al + j * 64);
            ldsm_if<512>(a2[NF2 - 1][0], a2[NF2 - 1][1], w2a + (NF2 - 1) * 8192, b2 + 8 * (NF2 - 1), got);
            float c[6][4];
#pragma unroll
            for (int j = 0; j < 6; j++) zero4(c[j]);
#pragma unroll
            for (int j = 0; j < NF2; j++) { mma_bf16(c[(j % 3) * 2], a2[j][0], e[j].x, e[j].y); mma_bf16(c[(j % 3) * 2 + 1], a2[j][1], e[j].z, e[j].w); }
            if (__any_sync(0xffffffffu, !got)) {
                constexpr int j = NF2 - 1;
                mbar_wait(b2 + 8 * j, 0);
                ldsm_x4_t(a2[j][0], w2a + j * 8192); ldsm_x4_t(a2[j][1], w2a + j * 8192 + 512);
                mma_bf16(c[4], a2[j][0], e[j].x, e[j].y); mma_bf16(c[5], a2[j][1], e[j].z, e[j].w);
            }
            sts32(rdst + 96 * 48, odd ? (((c[0][2] + c[1][2]) + (c[2][2] + c[3][2])) + c[4][2]) + c[5][2] : (((c[0][0] + c[1][0]) + (c[2][0] + c[3][0])) + c[4][0]) + c[5][0]);
            fin_arrive<6>();
        }
#undef F_
    }
}

typedef CUresult (*EncodeTiledFn)(CUtensorMap*, CUtensorMapDataType, cuuint32_t, void*, const cuuint64_t*, const cuuint64_t*,
                                  const cuuint32_t*, const cuuint32_t*, CUtensorMapInterleave, CUtensorMapSwizzle,
                                  CUtensorMapL2promotion, CUtensorMapFloatOOBfill);

void make_map(EncodeTiledFn fn, CUtensorMap* tm, const void* w, const int (&d)[5], const int (&st)[4], const int (&bx)[5],
              CUtensorMapSwizzle sw, int promo) {
    cuuint64_t dims[5], strides[4];
    cuuint32_t box[5], estr[5];
    for (int i = 0; i < 5; i++) { dims[i] = (cuuint64_t)d[i]; box[i] = (cuuint32_t)bx[i]; estr[i] = 1; }
    for (int i = 0; i < 4; i++) strides[i] = (cuuint64_t)st[i];
    fn(tm, CU_TENSOR_MAP_DATA_TYPE_BFLOAT16, 5, const_cast<void*>(w), dims, strides, box, estr, CU_TENSOR_MAP_INTERLEAVE_NONE, sw,
       (CUtensorMapL2promotion)promo, CU_TENSOR_MAP_FLOAT_OOB_FILL_NONE);
}

enum { T_PER, T_LEAD, T_STAG, T_TD, T_PERO, T_F1D, T_PERF, T_F2, T_PER2, T_Q, T_PWO, T_PW13, T_PW2, T_TG, T_GA, T_TGA, T_TG0, T_SH, T_INFL, T_DZ, T_ST, T_RD, T_RL, T_PKV, T_N };
int g_tune[T_N] = {478, 1170, 4, 20, 285, 300, 109, 1391, 120, 5600, 2, 2, 2, 1520, 250, 600, 75, 15, 5, 30, 1800, 3, 1, 2};

}

extern "C" void kernel_launch(void* const* d_in, const int* in_sizes, int n_in, void* d_out, int out_size) {
    (void)in_sizes; (void)n_in; (void)out_size;
    static EncodeTiledFn encode = nullptr;
    static Scratch* scratch = nullptr;
    static unsigned char* xarea = nullptr;
    if (!encode) {
        void* sp = nullptr;
        cudaGetSymbolAddress(&sp, g_scratch);
        scratch = reinterpret_cast<Scratch*>(sp);
        cudaGetSymbolAddress(&sp, g_xarea);
        xarea = reinterpret_cast<unsigned char*>((reinterpret_cast<uintptr_t>(sp) + XA_ALIGN - 1) / XA_ALIGN * XA_ALIGN);
        void* fn = nullptr;
        cudaDriverEntryPointQueryResult st;
        cudaGetDriverEntryPoint("cuTensorMapEncodeTiled", &fn, cudaEnableDefault, &st);
        encode = reinterpret_cast<EncodeTiledFn>(fn);
        cudaFuncSetAttribute(fused_decode_kernel, cudaFuncAttributeMaxDynamicSharedMemorySize, SM_TOTAL);
        int dev = 0, khz = 0, bits = 0;
        cudaGetDevice(&dev);
        if (cudaDeviceGetAttribute(&khz, cudaDevAttrMemoryClockRate, dev) == cudaSuccess &&
            cudaDeviceGetAttribute(&bits, cudaDevAttrGlobalMemoryBusWidth, dev) == cudaSuccess && khz > 0 && bits > 0) {
            const double f = 2619000.0 * 5120.0 / ((double)khz * bits);
            for (int i : {T_PER, T_STAG, T_SH, T_PERO, T_PERF, T_F2, T_Q}) g_tune[i] = (int)(g_tune[i] * f + 0.5);
            if (f < 1.0) g_tune[T_INFL] = (int)(g_tune[T_INFL] / f + 0.5);
        }
        (void)cudaGetLastError();
    }
    const int* T = g_tune;
    KParams p;
    p.x = (const __nv_bfloat16*)d_in[0];
    p.wq = (const __nv_bfloat16*)d_in[3];
    p.out = (__nv_bfloat16*)d_out;
    p.sc = scratch;
    p.xa = xarea;
    p.per = T[T_PER];
    p.stag = T[T_STAG];
    p.t_k0 = (NQT + 1) * T[T_PER] - T[T_LEAD];
    {
        int t = p.t_k0 + 2 * NKT * T[T_PER] + T[T_STAG] * 3 / 2 + T[T_SH] * 31 / 2 + T[T_TD];
        for (int i = 0; i < NWP; i++, t += T[T_PERO]) p.item[i] = t;
        for (int i = 0, t1 = t + T[T_F1D]; i < NP1; i++, t1 += T[T_PERF]) p.item[NWP + i] = t1;
        for (int i = 0, t2 = t + T[T_F2]; i < NF2; i++, t2 += T[T_PER2]) p.item[NWP + NP1 + i] = t2;
        for (int i = NITEM; i < 32; i++) p.item[i] = 0;
    }
    p.target = T[T_TG]; p.t_q = T[T_Q]; p.t_stat = T[T_ST];
    p.rdelay = T[T_RD]; p.rlast = T[T_RL];
    p.gain = T[T_GA] / 100.f; p.tgain = T[T_TGA] / 47800.f; p.tg0 = T[T_TG0] / 10.f; p.dz = T[T_DZ] / 10.f;
    p.stagh = T[T_SH]; p.infl = T[T_INFL]; p.t_fill = p.t_k0 + 59 * T[T_PER];
    for (int i = 0, nw = 0, n1 = 0, n2 = 0; i < NCTA; i++) {
        const int grp = i >> 2;
        const bool f2 = grp % 3 == 2, both = grp == 8 || grp == 23, wo = !both, f1 = !f2 || both;
        p.role[i] = (wo ? 1 | nw / 20 << 3 | nw % 20 << 6 : 0) | (f1 ? 2 | n1 << 11 : 0) | (f2 ? 4 | n2 << 18 : 0);
        nw += wo; n1 += f1; n2 += f2;
    }
    TMaps tm;
    constexpr int R1 = FF * 2, R2 = D_MODEL * 2;
    for (int i = 0; i < 2; i++)
        make_map(encode, &tm.k + i, d_in[1 + i], {64, 96, 1, 1, NHEAD * SK / 32}, {128, TILE_BYTES, TILE_BYTES, TILE_BYTES}, {64, 96, 1, 1, 1}, CU_TENSOR_MAP_SWIZZLE_128B, T[T_PKV]);
    make_map(encode, &tm.wo, d_in[4], {D_MODEL, 2, 4, 2, NHEAD * DH / 16}, {R2, 4 * R2, 2 * R2, 16 * R2}, {32, 2, 4, 2, 8}, CU_TENSOR_MAP_SWIZZLE_64B, T[T_PWO]);
    make_map(encode, &tm.w1, d_in[6], {FF, 2, 4, 2, D_MODEL / 16}, {R1, 4 * R1, 2 * R1, 16 * R1}, {16, 2, 4, 2, 8}, CU_TENSOR_MAP_SWIZZLE_32B, T[T_PW13]);
    make_map(encode, &tm.w3, d_in[7], {FF, 2, 4, 2, D_MODEL / 16}, {R1, 4 * R1, 2 * R1, 16 * R1}, {16, 2, 4, 2, 8}, CU_TENSOR_MAP_SWIZZLE_32B, T[T_PW13]);
    make_map(encode, &tm.w2, d_in[8], {D_MODEL, 2, 4, 4, FF / 32}, {R2, 8 * R2, 2 * R2, 32 * R2}, {16, 2, 4, 4, 8}, CU_TENSOR_MAP_SWIZZLE_32B, T[T_PW2]);
    fused_decode_kernel<<<NCTA, NTHREADS, SM_TOTAL, cudaStreamPerThread>>>(p, tm);
}
```
